```python
import torch

def _softmax(x, axis=-1):
    return torch.softmax(x, dim=axis)

def _gelu(x):
    return torch.nn.functional.gelu(x, approximate='tanh')

def _silu(x):
    return torch.nn.functional.silu(x)

def _sigmoid(x):
    return torch.sigmoid(x)

def _layernorm(x, axis=-1, eps=1e-05):
    m = x.mean(dim=axis, keepdim=True)
    v = x.var(dim=axis, keepdim=True, unbiased=False)
    return (x - m) / torch.sqrt(v + eps)

def _scatter_add(tgt, idx, src, axis=0):
    return tgt.clone().index_add_(axis, idx, src)

def _segment_sum(src, seg, n):
    out = torch.zeros((n,) + src.shape[1:], dtype=src.dtype)
    return out.index_add_(0, seg, src)

def _pad(x, pw):
    flat = tuple((v for pair in reversed(pw) for v in pair))
    return torch.nn.functional.pad(x, flat)
kernel_name = 'standalone__video_timesformer__vision'

def setup_inputs():

    _w = lambda a: (lambda t: t.to(torch.bfloat16) if t.is_floating_point() else t)(torch.as_tensor(a))
    T = 7
    p = 14
    HW = 512 // p * p
    N = (HW // p) ** 2
    C = 192
    return {'x': _w((lambda *s: torch.randn(*s, dtype=torch.bfloat16) * 0.1)(1, T, N, C)), 'wqkv_t': _w((lambda *s: torch.randn(*s, dtype=torch.bfloat16) * 0.1)(C, 3 * C)), 'wo_t': _w((lambda *s: torch.randn(*s, dtype=torch.bfloat16) * 0.1)(C, C)), 'wqkv_s': _w((lambda *s: torch.randn(*s, dtype=torch.bfloat16) * 0.1)(C, 3 * C)), 'wo_s': _w((lambda *s: torch.randn(*s, dtype=torch.bfloat16) * 0.8)(C, C))}

def reference(x, wqkv_t, wo_t, wqkv_s, wo_s):
    B, T, N, C = x.shape
    scale = C ** (-0.5)
    xt = (lambda x, *d: x.permute(*d))(x, 0, 2, 1, 3).reshape(B * N, T, C)
    h = _layernorm(xt, axis=-1)
    qkv = h @ wqkv_t
    q, k, v = (qkv[..., :C].clone(), qkv[..., C:2 * C].clone(), qkv[..., 2 * C:].clone())
    a = _softmax(torch.einsum('btc,bsc->bts', q, k) * scale, axis=-1)
    xt = xt + torch.einsum('bts,bsc->btc', a, v) @ wo_t
    x1 = (lambda x, *d: x.permute(*d))(xt.reshape(B, N, T, C), 0, 2, 1, 3)
    xs = x1.reshape(B * T, N, C)
    h = _layernorm(xs, axis=-1)
    qkv = h @ wqkv_s
    q, k, v = (qkv[..., :C].clone(), qkv[..., C:2 * C].clone(), qkv[..., 2 * C:].clone())
    a = _softmax(torch.einsum('bnc,bmc->bnm', q, k) * scale, axis=-1)
    xs = xs + torch.einsum('bnm,bmc->bnc', a, v) @ wo_s
    return xs.reshape(B, T, N, C)
```

```cpp
#include <cuda_runtime.h>
#include <cuda_bf16.h>
#include <cuda.h>
#include <stdint.h>

namespace {

constexpr int TT = 7, NL = 1296, CC = 192;

__device__ __align__(1024) __nv_bfloat16 g_x1[TT * NL * CC];
__device__ __align__(1024) __nv_bfloat16 g_qkv[TT * NL * 3 * CC];
__device__ __align__(1024) float4 g_part[132 * 2 * 25 * 128];
__device__ unsigned int g_flag[256];

__device__ __forceinline__ uint32_t smem_u32(const void* p) { return (uint32_t)__cvta_generic_to_shared(p); }
__device__ __forceinline__ void mbar_init(uint32_t bar, uint32_t cnt) {
  asm volatile("mbarrier.init.shared::cta.b64 [%0], %1;" ::"r"(bar), "r"(cnt));
}
__device__ __forceinline__ void mbar_expect_tx(uint32_t bar, uint32_t bytes) {
  asm volatile("mbarrier.arrive.expect_tx.shared::cta.b64 _, [%0], %1;" ::"r"(bar), "r"(bytes) : "memory");
}
__device__ __forceinline__ void mbar_arrive(uint32_t bar) {
  asm volatile("mbarrier.arrive.shared::cta.b64 _, [%0];" ::"r"(bar) : "memory");
}
__device__ __forceinline__ bool mbar_try(uint32_t bar, uint32_t parity) {
  uint32_t ok;
  asm volatile("{\n.reg .pred p;\nmbarrier.try_wait.parity.shared::cta.b64 p, [%1], %2;\nselp.u32 %0, 1, 0, p;\n}"
               : "=r"(ok) : "r"(bar), "r"(parity) : "memory");
  return ok != 0;
}
__device__ __forceinline__ void mbar_wait(uint32_t bar, uint32_t parity) {
  if (mbar_try(bar, parity)) return;
  uint32_t n = 0;
  while (!mbar_try(bar, parity)) {
    if (++n > (1u << 22)) break;
  }
}
__device__ __forceinline__ void tma_load_2d(uint32_t dst, const CUtensorMap* m, uint32_t bar, int c0, int c1) {
  asm volatile("cp.async.bulk.tensor.2d.shared::cluster.global.mbarrier::complete_tx::bytes [%0], [%1, {%3, %4}], [%2];"
               ::"r"(dst), "l"(m), "r"(bar), "r"(c0), "r"(c1) : "memory");
}
__device__ __forceinline__ void tma_load_3d(uint32_t dst, const CUtensorMap* m, uint32_t bar, int c0, int c1, int c2) {
  asm volatile("cp.async.bulk.tensor.3d.shared::cluster.global.mbarrier::complete_tx::bytes [%0], [%1, {%3, %4, %5}], [%2];"
               ::"r"(dst), "l"(m), "r"(bar), "r"(c0), "r"(c1), "r"(c2) : "memory");
}
__device__ __forceinline__ void tma_store_3d(const CUtensorMap* m, uint32_t src, int c0, int c1, int c2) {
  asm volatile("cp.async.bulk.tensor.3d.global.shared::cta.bulk_group [%0, {%2, %3, %4}], [%1];"
               ::"l"(m), "r"(src), "r"(c0), "r"(c1), "r"(c2) : "memory");
}
__device__ __forceinline__ void bulk_commit() { asm volatile("cp.async.bulk.commit_group;" ::: "memory"); }
__device__ __forceinline__ void bulk_wait_read0() { asm volatile("cp.async.bulk.wait_group.read 0;" ::: "memory"); }
__device__ __forceinline__ void bulk_wait0() { asm volatile("cp.async.bulk.wait_group 0;" ::: "memory"); }
__device__ __forceinline__ void fence_proxy_async() { asm volatile("fence.proxy.async.shared::cta;" ::: "memory"); }
__device__ __forceinline__ void prefetch_tmap(const CUtensorMap* m) {
  asm volatile("prefetch.tensormap [%0];" ::"l"(m) : "memory");
}
__device__ __forceinline__ void wg_fence() { asm volatile("wgmma.fence.sync.aligned;" ::: "memory"); }
__device__ __forceinline__ void wg_commit() { asm volatile("wgmma.commit_group.sync.aligned;" ::: "memory"); }
template <int N> __device__ __forceinline__ void wg_wait() { asm volatile("wgmma.wait_group.sync.aligned %0;" ::"n"(N) : "memory"); }
__device__ __forceinline__ void named_bar(int id, int nthreads) {
  asm volatile("bar.sync %0, %1;" ::"r"(id), "r"(nthreads) : "memory");
}
__device__ __forceinline__ void ldsm_x4(uint32_t (&r)[4], uint32_t addr) {
  asm volatile("ldmatrix.sync.aligned.m8n8.x4.shared.b16 {%0,%1,%2,%3}, [%4];"
               : "=r"(r[0]), "=r"(r[1]), "=r"(r[2]), "=r"(r[3]) : "r"(addr) : "memory");
}
__device__ __forceinline__ void stsm_x4(uint32_t addr, const uint32_t (&r)[4]) {
  asm volatile("stmatrix.sync.aligned.m8n8.x4.shared.b16 [%0], {%1,%2,%3,%4};"
               ::"r"(addr), "r"(r[0]), "r"(r[1]), "r"(r[2]), "r"(r[3]) : "memory");
}
__device__ __forceinline__ uint32_t pack_bf16(float lo, float hi) {
  uint32_t r;
  asm("cvt.rn.bf16x2.f32 %0, %1, %2;" : "=r"(r) : "f"(hi), "f"(lo));
  return r;
}
__device__ __forceinline__ float bf_lo(uint32_t v) { return __uint_as_float(v << 16); }
__device__ __forceinline__ float bf_hi(uint32_t v) { return __uint_as_float(v & 0xffff0000u); }
__device__ __forceinline__ float ex2(float x) {
  float y;
  asm("ex2.approx.ftz.f32 %0, %1;" : "=f"(y) : "f"(x));
  return y;
}
__device__ __forceinline__ uint64_t mk_desc(uint32_t addr, uint32_t lbo, uint32_t sbo) {
  return (uint64_t)((addr & 0x3FFFF) >> 4) | ((uint64_t)((lbo & 0x3FFFF) >> 4) << 16) |
         ((uint64_t)((sbo & 0x3FFFF) >> 4) << 32) | (1ull << 62);
}
template <int N> __device__ __forceinline__ void reg_fence(float (&d)[N]) {
#pragma unroll
  for (int i = 0; i < N; i++) asm volatile("" : "+f"(d[i])::"memory");
}

template<int TB> __device__ __forceinline__ void wgmma_n144_ss(float (&d)[72], uint64_t da, uint64_t db, int sc) {
  asm volatile("{\n.reg .pred p;\nsetp.ne.b32 p, %74, 0;\n"
    "wgmma.mma_async.sync.aligned.m64n144k16.f32.bf16.bf16 {%0, %1, %2, %3, %4, %5, %6, %7, %8, %9, %10, %11, %12, %13, %14, %15, %16, %17, %18, %19, %20, %21, %22, %23, %24, %25, %26, %27, %28, %29, %30, %31, %32, %33, %34, %35, %36, %37, %38, %39, %40, %41, %42, %43, %44, %45, %46, %47, %48, %49, %50, %51, %52, %53, %54, %55, %56, %57, %58, %59, %60, %61, %62, %63, %64, %65, %66, %67, %68, %69, %70, %71}, %72, %73, p, 1, 1, 0, %75;\n}\n"
    : "+f"(d[0]), "+f"(d[1]), "+f"(d[2]), "+f"(d[3]), "+f"(d[4]), "+f"(d[5]), "+f"(d[6]), "+f"(d[7]), "+f"(d[8]), "+f"(d[9]), "+f"(d[10]), "+f"(d[11]), "+f"(d[12]), "+f"(d[13]), "+f"(d[14]), "+f"(d[15]), "+f"(d[16]), "+f"(d[17]), "+f"(d[18]), "+f"(d[19]), "+f"(d[20]), "+f"(d[21]), "+f"(d[22]), "+f"(d[23]), "+f"(d[24]), "+f"(d[25]), "+f"(d[26]), "+f"(d[27]), "+f"(d[28]), "+f"(d[29]), "+f"(d[30]), "+f"(d[31]), "+f"(d[32]), "+f"(d[33]), "+f"(d[34]), "+f"(d[35]), "+f"(d[36]), "+f"(d[37]), "+f"(d[38]), "+f"(d[39]), "+f"(d[40]), "+f"(d[41]), "+f"(d[42]), "+f"(d[43]), "+f"(d[44]), "+f"(d[45]), "+f"(d[46]), "+f"(d[47]), "+f"(d[48]), "+f"(d[49]), "+f"(d[50]), "+f"(d[51]), "+f"(d[52]), "+f"(d[53]), "+f"(d[54]), "+f"(d[55]), "+f"(d[56]), "+f"(d[57]), "+f"(d[58]), "+f"(d[59]), "+f"(d[60]), "+f"(d[61]), "+f"(d[62]), "+f"(d[63]), "+f"(d[64]), "+f"(d[65]), "+f"(d[66]), "+f"(d[67]), "+f"(d[68]), "+f"(d[69]), "+f"(d[70]), "+f"(d[71])
    : "l"(da), "l"(db), "r"(sc), "n"(TB));
}
template<int TB> __device__ __forceinline__ void wgmma_n192_rs(float (&d)[96], const uint32_t (&a)[4], uint64_t db, int sc) {
  asm volatile("{\n.reg .pred p;\nsetp.ne.b32 p, %101, 0;\n"
    "wgmma.mma_async.sync.aligned.m64n192k16.f32.bf16.bf16 {%0, %1, %2, %3, %4, %5, %6, %7, %8, %9, %10, %11, %12, %13, %14, %15, %16, %17, %18, %19, %20, %21, %22, %23, %24, %25, %26, %27, %28, %29, %30, %31, %32, %33, %34, %35, %36, %37, %38, %39, %40, %41, %42, %43, %44, %45, %46, %47, %48, %49, %50, %51, %52, %53, %54, %55, %56, %57, %58, %59, %60, %61, %62, %63, %64, %65, %66, %67, %68, %69, %70, %71, %72, %73, %74, %75, %76, %77, %78, %79, %80, %81, %82, %83, %84, %85, %86, %87, %88, %89, %90, %91, %92, %93, %94, %95}, {%96, %97, %98, %99}, %100, p, 1, 1, %102;\n}\n"
    : "+f"(d[0]), "+f"(d[1]), "+f"(d[2]), "+f"(d[3]), "+f"(d[4]), "+f"(d[5]), "+f"(d[6]), "+f"(d[7]), "+f"(d[8]), "+f"(d[9]), "+f"(d[10]), "+f"(d[11]), "+f"(d[12]), "+f"(d[13]), "+f"(d[14]), "+f"(d[15]), "+f"(d[16]), "+f"(d[17]), "+f"(d[18]), "+f"(d[19]), "+f"(d[20]), "+f"(d[21]), "+f"(d[22]), "+f"(d[23]), "+f"(d[24]), "+f"(d[25]), "+f"(d[26]), "+f"(d[27]), "+f"(d[28]), "+f"(d[29]), "+f"(d[30]), "+f"(d[31]), "+f"(d[32]), "+f"(d[33]), "+f"(d[34]), "+f"(d[35]), "+f"(d[36]), "+f"(d[37]), "+f"(d[38]), "+f"(d[39]), "+f"(d[40]), "+f"(d[41]), "+f"(d[42]), "+f"(d[43]), "+f"(d[44]), "+f"(d[45]), "+f"(d[46]), "+f"(d[47]), "+f"(d[48]), "+f"(d[49]), "+f"(d[50]), "+f"(d[51]), "+f"(d[52]), "+f"(d[53]), "+f"(d[54]), "+f"(d[55]), "+f"(d[56]), "+f"(d[57]), "+f"(d[58]), "+f"(d[59]), "+f"(d[60]), "+f"(d[61]), "+f"(d[62]), "+f"(d[63]), "+f"(d[64]), "+f"(d[65]), "+f"(d[66]), "+f"(d[67]), "+f"(d[68]), "+f"(d[69]), "+f"(d[70]), "+f"(d[71]), "+f"(d[72]), "+f"(d[73]), "+f"(d[74]), "+f"(d[75]), "+f"(d[76]), "+f"(d[77]), "+f"(d[78]), "+f"(d[79]), "+f"(d[80]), "+f"(d[81]), "+f"(d[82]), "+f"(d[83]), "+f"(d[84]), "+f"(d[85]), "+f"(d[86]), "+f"(d[87]), "+f"(d[88]), "+f"(d[89]), "+f"(d[90]), "+f"(d[91]), "+f"(d[92]), "+f"(d[93]), "+f"(d[94]), "+f"(d[95])
    : "r"(a[0]), "r"(a[1]), "r"(a[2]), "r"(a[3]), "l"(db), "r"(sc), "n"(TB));
}
template<int TB> __device__ __forceinline__ void wgmma_n64_rs(float (&d)[32], const uint32_t (&a)[4], uint64_t db, int sc) {
  asm volatile("{\n.reg .pred p;\nsetp.ne.b32 p, %37, 0;\n"
    "wgmma.mma_async.sync.aligned.m64n64k16.f32.bf16.bf16 {%0, %1, %2, %3, %4, %5, %6, %7, %8, %9, %10, %11, %12, %13, %14, %15, %16, %17, %18, %19, %20, %21, %22, %23, %24, %25, %26, %27, %28, %29, %30, %31}, {%32, %33, %34, %35}, %36, p, 1, 1, %38;\n}\n"
    : "+f"(d[0]), "+f"(d[1]), "+f"(d[2]), "+f"(d[3]), "+f"(d[4]), "+f"(d[5]), "+f"(d[6]), "+f"(d[7]), "+f"(d[8]), "+f"(d[9]), "+f"(d[10]), "+f"(d[11]), "+f"(d[12]), "+f"(d[13]), "+f"(d[14]), "+f"(d[15]), "+f"(d[16]), "+f"(d[17]), "+f"(d[18]), "+f"(d[19]), "+f"(d[20]), "+f"(d[21]), "+f"(d[22]), "+f"(d[23]), "+f"(d[24]), "+f"(d[25]), "+f"(d[26]), "+f"(d[27]), "+f"(d[28]), "+f"(d[29]), "+f"(d[30]), "+f"(d[31])
    : "r"(a[0]), "r"(a[1]), "r"(a[2]), "r"(a[3]), "l"(db), "r"(sc), "n"(TB));
}


struct FragAddr {
  uint32_t rowoff;
  uint32_t rx;
  uint32_t hi;
  __device__ __forceinline__ FragAddr(int warp_in_wg, int lane) {
    int row = 16 * warp_in_wg + (lane & 7) + ((lane >> 3) & 1) * 8;
    rowoff = row * 128;
    rx = row & 7;
    hi = lane >> 4;
  }
  __device__ __forceinline__ uint32_t at(uint32_t chunk_base, int kk4) const {
    return chunk_base + rowoff + ((((uint32_t)kk4 * 2 + hi) ^ rx) << 4);
  }
};

__device__ __forceinline__ void layernorm_frags(uint32_t (&f)[12][4]) {
  float s0 = 0.f, s1 = 0.f;
#pragma unroll
  for (int k = 0; k < 12; k++) {
    s0 += bf_lo(f[k][0]) + bf_hi(f[k][0]) + bf_lo(f[k][2]) + bf_hi(f[k][2]);
    s1 += bf_lo(f[k][1]) + bf_hi(f[k][1]) + bf_lo(f[k][3]) + bf_hi(f[k][3]);
  }
  s0 += __shfl_xor_sync(0xffffffffu, s0, 1); s0 += __shfl_xor_sync(0xffffffffu, s0, 2);
  s1 += __shfl_xor_sync(0xffffffffu, s1, 1); s1 += __shfl_xor_sync(0xffffffffu, s1, 2);
  const float m0 = s0 * (1.f / 192.f), m1 = s1 * (1.f / 192.f);
  float v0 = 0.f, v1 = 0.f;
#pragma unroll
  for (int k = 0; k < 12; k++) {
    float a;
    a = bf_lo(f[k][0]) - m0; v0 += a * a; a = bf_hi(f[k][0]) - m0; v0 += a * a;
    a = bf_lo(f[k][2]) - m0; v0 += a * a; a = bf_hi(f[k][2]) - m0; v0 += a * a;
    a = bf_lo(f[k][1]) - m1; v1 += a * a; a = bf_hi(f[k][1]) - m1; v1 += a * a;
    a = bf_lo(f[k][3]) - m1; v1 += a * a; a = bf_hi(f[k][3]) - m1; v1 += a * a;
  }
  v0 += __shfl_xor_sync(0xffffffffu, v0, 1); v0 += __shfl_xor_sync(0xffffffffu, v0, 2);
  v1 += __shfl_xor_sync(0xffffffffu, v1, 1); v1 += __shfl_xor_sync(0xffffffffu, v1, 2);
  const float r0 = rsqrtf(v0 * (1.f / 192.f) + 1e-5f), r1 = rsqrtf(v1 * (1.f / 192.f) + 1e-5f);
#pragma unroll
  for (int k = 0; k < 12; k++) {
    f[k][0] = pack_bf16((bf_lo(f[k][0]) - m0) * r0, (bf_hi(f[k][0]) - m0) * r0);
    f[k][2] = pack_bf16((bf_lo(f[k][2]) - m0) * r0, (bf_hi(f[k][2]) - m0) * r0);
    f[k][1] = pack_bf16((bf_lo(f[k][1]) - m1) * r1, (bf_hi(f[k][1]) - m1) * r1);
    f[k][3] = pack_bf16((bf_lo(f[k][3]) - m1) * r1, (bf_hi(f[k][3]) - m1) * r1);
  }
}

constexpr int A_NST = 5;
constexpr int A_XS = 0;
constexpr int A_KV = 49152;
constexpr int A_W = 98304;
constexpr int A_BAR = A_W + A_NST * 24576;
constexpr int A_SMEM = A_BAR + 256 + 1024;

__device__ __forceinline__ void a_issue(float (&acc)[32], const uint32_t (&af)[12][4], uint32_t sb, int s) {
  const int st = s % A_NST;
  mbar_wait(sb + A_BAR + st * 8, (s / A_NST) & 1);
  const uint32_t wb = sb + A_W + st * 24576;
  wg_fence();
#pragma unroll
  for (int kk = 0; kk < 12; kk++) wgmma_n64_rs<1>(acc, af[kk], mk_desc(wb + kk * 2048, 8192, 1024), kk > 0);
  wg_commit();
}
__device__ __forceinline__ void a_release(uint32_t sb, int s, int lane) {
  if (lane == 0) mbar_arrive(sb + A_BAR + 64 + (s % A_NST) * 8);
}
__device__ __forceinline__ void cvt_frags(uint32_t (*dst)[4], const float (&acc)[32]) {
#pragma unroll
  for (int k = 0; k < 4; k++) {
    dst[k][0] = pack_bf16(acc[8 * k + 0], acc[8 * k + 1]);
    dst[k][1] = pack_bf16(acc[8 * k + 2], acc[8 * k + 3]);
    dst[k][2] = pack_bf16(acc[8 * k + 4], acc[8 * k + 5]);
    dst[k][3] = pack_bf16(acc[8 * k + 6], acc[8 * k + 7]);
  }
}
__device__ __forceinline__ void store_chunk(const float (&acc)[32], uint32_t chunk_base, const FragAddr& fa) {
  uint32_t t[4][4];
  cvt_frags(t, acc);
#pragma unroll
  for (int k = 0; k < 4; k++) stsm_x4(fa.at(chunk_base, k), t[k]);
}
__device__ __forceinline__ void resid_chunk(uint32_t (*dst)[4], const float* acc, uint32_t chunk_base, const FragAddr& fa) {
#pragma unroll
  for (int k = 0; k < 4; k++) {
    uint32_t x[4];
    ldsm_x4(x, fa.at(chunk_base, k));
    uint32_t o[4];
    o[0] = pack_bf16(bf_lo(x[0]) + acc[8 * k + 0], bf_hi(x[0]) + acc[8 * k + 1]);
    o[1] = pack_bf16(bf_lo(x[1]) + acc[8 * k + 2], bf_hi(x[1]) + acc[8 * k + 3]);
    o[2] = pack_bf16(bf_lo(x[2]) + acc[8 * k + 4], bf_hi(x[2]) + acc[8 * k + 5]);
    o[3] = pack_bf16(bf_lo(x[3]) + acc[8 * k + 6], bf_hi(x[3]) + acc[8 * k + 7]);
    stsm_x4(fa.at(chunk_base, k), o);
    if (dst) { dst[k][0] = o[0]; dst[k][1] = o[1]; dst[k][2] = o[2]; dst[k][3] = o[3]; }
  }
}

__global__ void __launch_bounds__(384, 1)
kernelA(const __grid_constant__ CUtensorMap tm_x, const __grid_constant__ CUtensorMap tm_wqkvt,
        const __grid_constant__ CUtensorMap tm_wot, const __grid_constant__ CUtensorMap tm_wqkvs,
        const __grid_constant__ CUtensorMap tm_x1, const __grid_constant__ CUtensorMap tm_qkv) {
  extern __shared__ uint8_t smem_raw[];
  const uint32_t sb = (smem_u32(smem_raw) + 1023) & ~1023u;
  const int tid = threadIdx.x, warp = tid >> 5, lane = tid & 31;
  if (tid == 0) {
    for (int i = 0; i < A_NST; i++) { mbar_init(sb + A_BAR + i * 8, 1); mbar_init(sb + A_BAR + 64 + i * 8, 8); }
    mbar_init(sb + A_BAR + 128, 1); mbar_init(sb + A_BAR + 136, 1);
    asm volatile("fence.mbarrier_init.release.cluster;" ::: "memory");
  }
  if (blockIdx.x == 0 && tid < 256) g_flag[tid] = 0;
  if (tid < 48) {
    uint32_t a = sb + A_XS + (tid >> 3) * 8192 + 63 * 128 + (tid & 7) * 16;
    asm volatile("st.shared.v4.b32 [%0], {%1,%1,%1,%1};" ::"r"(a), "r"(0) : "memory");
  }
  __syncthreads();

  if (warp >= 8) {
    asm volatile("setmaxnreg.dec.sync.aligned.u32 24;");
    if (warp == 8 && lane == 0) {
      for (int w = 0; w < 2; w++) {
        const uint32_t bar = sb + A_BAR + 128 + w * 8;
        mbar_expect_tx(bar, 3 * 63 * 128);
        for (int c = 0; c < 3; c++)
          tma_load_3d(sb + A_XS + w * 24576 + c * 8192, &tm_x, bar, c * 64, (blockIdx.x * 2 + w) * 9, 0);
      }
      for (int s = 0; s < 21; s++) {
        const int st = s % A_NST;
        if (s >= A_NST) mbar_wait(sb + A_BAR + 64 + st * 8, ((s / A_NST) - 1) & 1);
        const CUtensorMap* m; int col;
        if (s < 3) { m = &tm_wqkvt; col = 192 + 64 * s; }
        else if (s < 6) { m = &tm_wqkvt; col = 64 * (s - 3); }
        else if (s < 9) { m = &tm_wqkvt; col = 384 + 64 * (s - 6); }
        else if (s < 12) { m = &tm_wot; col = 64 * (s - 9); }
        else { m = &tm_wqkvs; col = 64 * (s - 12); }
        mbar_expect_tx(sb + A_BAR + st * 8, 24576);
        tma_load_2d(sb + A_W + st * 24576, m, sb + A_BAR + st * 8, col, 0);
      }
    }
    return;
  }

  asm volatile("setmaxnreg.inc.sync.aligned.u32 240;");
  const int wg = warp >> 2, wq = warp & 3;
  const int n0 = (blockIdx.x * 2 + wg) * 9;
  const FragAddr fa(wq, lane);
  const uint32_t xs = sb + A_XS + wg * 24576, kv = sb + A_KV + wg * 24576;
  const int barid = 1 + wg;
  const bool elected = (tid & 127) == 0;

  uint32_t h[12][4];
  mbar_wait(sb + A_BAR + 128 + wg * 8, 0);
#pragma unroll
  for (int k = 0; k < 12; k++) ldsm_x4(h[k], fa.at(xs + (k >> 2) * 8192, k & 3));
  layernorm_frags(h);

  float acc0[32], acc1[32];
  uint32_t qf[12][4];
  a_issue(acc0, h, sb, 0);
  a_issue(acc1, h, sb, 1); wg_wait<1>(); reg_fence(acc0); a_release(sb, 0, lane); store_chunk(acc0, kv, fa);
  a_issue(acc0, h, sb, 2); wg_wait<1>(); reg_fence(acc1); a_release(sb, 1, lane); store_chunk(acc1, kv + 8192, fa);
  a_issue(acc1, h, sb, 3); wg_wait<1>(); reg_fence(acc0); a_release(sb, 2, lane); store_chunk(acc0, kv + 16384, fa);
  a_issue(acc0, h, sb, 4); wg_wait<1>(); reg_fence(acc1); a_release(sb, 3, lane); cvt_frags(&qf[0], acc1);
  a_issue(acc1, h, sb, 5); wg_wait<1>(); reg_fence(acc0); a_release(sb, 4, lane); cvt_frags(&qf[4], acc0);
  a_issue(acc0, h, sb, 6); wg_wait<1>(); reg_fence(acc1); a_release(sb, 5, lane); cvt_frags(&qf[8], acc1);
  fence_proxy_async();
  named_bar(barid, 128);
  float sacc[32];
  wg_fence();
#pragma unroll
  for (int kk = 0; kk < 12; kk++)
    wgmma_n64_rs<0>(sacc, qf[kk], mk_desc(kv + (kk >> 2) * 8192 + (kk & 3) * 32, 16, 1024), kk > 0);
  wg_commit();
  a_issue(acc1, h, sb, 7);
  wg_wait<1>(); reg_fence(acc0); reg_fence(sacc);
  a_release(sb, 6, lane);
  named_bar(barid, 128);
  store_chunk(acc0, kv, fa);
  a_issue(acc0, h, sb, 8);
  uint32_t pf[4][4];
  {
    const int r0 = 16 * wq + (lane >> 2), r1 = r0 + 8;
    const unsigned long long MB = 0x0040201008040201ull;
    const unsigned long long mk0 = (MB << (r0 % 9)) >> (2 * (lane & 3));
    const unsigned long long mk1 = (MB << (r1 % 9)) >> (2 * (lane & 3));
    const float cs = 0.07216878364870322f * 1.4426950408889634f;
    float mx0 = -INFINITY, mx1 = -INFINITY;
#pragma unroll
    for (int j = 0; j < 8; j++) {
#pragma unroll
      for (int e = 0; e < 2; e++) {
        bool v0 = (mk0 >> (8 * j + e)) & 1, v1 = (mk1 >> (8 * j + e)) & 1;
        sacc[4 * j + e] = v0 ? sacc[4 * j + e] * cs : -INFINITY;
        sacc[4 * j + 2 + e] = v1 ? sacc[4 * j + 2 + e] * cs : -INFINITY;
        mx0 = fmaxf(mx0, sacc[4 * j + e]);
        mx1 = fmaxf(mx1, sacc[4 * j + 2 + e]);
      }
    }
    mx0 = fmaxf(mx0, __shfl_xor_sync(0xffffffffu, mx0, 1)); mx0 = fmaxf(mx0, __shfl_xor_sync(0xffffffffu, mx0, 2));
    mx1 = fmaxf(mx1, __shfl_xor_sync(0xffffffffu, mx1, 1)); mx1 = fmaxf(mx1, __shfl_xor_sync(0xffffffffu, mx1, 2));
    float l0 = 0.f, l1 = 0.f;
#pragma unroll
    for (int j = 0; j < 8; j++) {
#pragma unroll
      for (int e = 0; e < 2; e++) {
        sacc[4 * j + e] = ex2(sacc[4 * j + e] - mx0); l0 += sacc[4 * j + e];
        sacc[4 * j + 2 + e] = ex2(sacc[4 * j + 2 + e] - mx1); l1 += sacc[4 * j + 2 + e];
      }
    }
    l0 += __shfl_xor_sync(0xffffffffu, l0, 1); l0 += __shfl_xor_sync(0xffffffffu, l0, 2);
    l1 += __shfl_xor_sync(0xffffffffu, l1, 1); l1 += __shfl_xor_sync(0xffffffffu, l1, 2);
    const float i0 = 1.f / l0, i1 = 1.f / l1;
#pragma unroll
    for (int j = 0; j < 8; j++) {
      sacc[4 * j] *= i0; sacc[4 * j + 1] *= i0; sacc[4 * j + 2] *= i1; sacc[4 * j + 3] *= i1;
    }
    cvt_frags(pf, sacc);
  }
  wg_wait<1>(); reg_fence(acc1); a_release(sb, 7, lane); store_chunk(acc1, kv + 8192, fa);
  wg_wait<0>(); reg_fence(acc0); a_release(sb, 8, lane); store_chunk(acc0, kv + 16384, fa);
  fence_proxy_async();
  named_bar(barid, 128);
  {
    float oacc[96];
    wg_fence();
#pragma unroll
    for (int kk = 0; kk < 4; kk++) wgmma_n192_rs<1>(oacc, pf[kk], mk_desc(kv + kk * 2048, 8192, 1024), kk > 0);
    wg_commit();
    wg_wait<0>(); reg_fence(oacc);
#pragma unroll
    for (int k = 0; k < 12; k++) {
      qf[k][0] = pack_bf16(oacc[8 * k + 0], oacc[8 * k + 1]);
      qf[k][1] = pack_bf16(oacc[8 * k + 2], oacc[8 * k + 3]);
      qf[k][2] = pack_bf16(oacc[8 * k + 4], oacc[8 * k + 5]);
      qf[k][3] = pack_bf16(oacc[8 * k + 6], oacc[8 * k + 7]);
    }
  }
  a_issue(acc0, qf, sb, 9);
  a_issue(acc1, qf, sb, 10); wg_wait<1>(); reg_fence(acc0); a_release(sb, 9, lane); resid_chunk(&h[0], acc0, xs, fa);
  a_issue(acc0, qf, sb, 11); wg_wait<1>(); reg_fence(acc1); a_release(sb, 10, lane); resid_chunk(&h[4], acc1, xs + 8192, fa);
  wg_wait<0>(); reg_fence(acc0); a_release(sb, 11, lane); resid_chunk(&h[8], acc0, xs + 16384, fa);
  fence_proxy_async();
  named_bar(barid, 128);
  if (elected) {
    for (int c = 0; c < 3; c++) tma_store_3d(&tm_x1, xs + c * 8192, c * 64, n0, 0);
    bulk_commit();
  }
  layernorm_frags(h);
  a_issue(acc0, h, sb, 12);
#pragma unroll
  for (int g = 0; g < 3; g++) {
    if ((g & 1) == 0) {
      a_issue(acc1, h, sb, 13 + 3 * g); wg_wait<1>(); reg_fence(acc0); a_release(sb, 12 + 3 * g, lane);
      if (g > 0) { if (elected) bulk_wait_read0(); named_bar(barid, 128); }
      store_chunk(acc0, kv, fa);
      a_issue(acc0, h, sb, 14 + 3 * g); wg_wait<1>(); reg_fence(acc1); a_release(sb, 13 + 3 * g, lane);
      store_chunk(acc1, kv + 8192, fa);
      if (g < 2) { a_issue(acc1, h, sb, 15 + 3 * g); wg_wait<1>(); } else { wg_wait<0>(); }
      reg_fence(acc0); a_release(sb, 14 + 3 * g, lane);
      store_chunk(acc0, kv + 16384, fa);
    } else {
      a_issue(acc0, h, sb, 13 + 3 * g); wg_wait<1>(); reg_fence(acc1); a_release(sb, 12 + 3 * g, lane);
      if (elected) bulk_wait_read0();
      named_bar(barid, 128);
      store_chunk(acc1, kv, fa);
      a_issue(acc1, h, sb, 14 + 3 * g); wg_wait<1>(); reg_fence(acc0); a_release(sb, 13 + 3 * g, lane);
      store_chunk(acc0, kv + 8192, fa);
      a_issue(acc0, h, sb, 15 + 3 * g); wg_wait<1>();
      reg_fence(acc1); a_release(sb, 14 + 3 * g, lane);
      store_chunk(acc1, kv + 16384, fa);
    }
    fence_proxy_async();
    named_bar(barid, 128);
    if (elected) {
      for (int c = 0; c < 3; c++) tma_store_3d(&tm_qkv, kv + c * 8192, g * 192 + c * 64, n0, 0);
      bulk_commit();
    }
  }
  if (elected) bulk_wait0();
}

constexpr int B_TILES = 77;
constexpr int B_STEPS = B_TILES * 9;
constexpr int B_GRID = 116;
constexpr int B_SLOT = 55296;
constexpr int B_Q = 0;
constexpr int B_KV = 49152;
constexpr int B_BAR = B_KV + 3 * B_SLOT;
constexpr int B_SMEM = B_BAR + 256 + 1024;
__device__ __forceinline__ int b_start(int c) { return c >= B_GRID ? B_STEPS : min(B_STEPS, c * 6); }

__global__ void __launch_bounds__(384, 1)
kernelB(const __grid_constant__ CUtensorMap tm_q, const __grid_constant__ CUtensorMap tm_kv,
        const __grid_constant__ CUtensorMap tm_wos, const __grid_constant__ CUtensorMap tm_x1,
        const __grid_constant__ CUtensorMap tm_out) {
  extern __shared__ uint8_t smem_raw[];
  const uint32_t sb = (smem_u32(smem_raw) + 1023) & ~1023u;
  const int tid = threadIdx.x, warp = tid >> 5, lane = tid & 31;
  const uint32_t bF = sb + B_BAR, bE = sb + B_BAR + 32, bQF = sb + B_BAR + 64, bQE = sb + B_BAR + 72;
  if (tid == 0) {
    for (int i = 0; i < 3; i++) { mbar_init(bF + i * 8, 1); mbar_init(bE + i * 8, 8); }
    mbar_init(bQF, 1); mbar_init(bQE, 8);
    asm volatile("fence.mbarrier_init.release.cluster;" ::: "memory");
  }
  __syncthreads();
  const int cta = blockIdx.x;
  const int s_begin = b_start(cta), s_end = b_start(cta + 1);
  const int last_tile = (s_end - 1) / 9;
  const bool owner = (last_tile * 9 >= s_begin);

  if (warp >= 8) {
    asm volatile("setmaxnreg.dec.sync.aligned.u32 24;");
    if (warp == 8 && lane == 0) {
      int it = 0, qn = 0;
      for (int s = s_begin; s < s_end; s++) {
        const int tile = s / 9, kb = s - tile * 9;
        const int t = tile / 11, qt = tile - t * 11;
        if (s == s_begin || kb == 0) {
          if (qn > 0) mbar_wait(bQE, (qn - 1) & 1);
          mbar_expect_tx(bQF, 49152);
          for (int c = 0; c < 3; c++) tma_load_3d(sb + B_Q + c * 16384, &tm_q, bQF, c * 64, qt * 128, t);
          qn++;
        }
        for (int kvsel = 0; kvsel < 2; kvsel++) {
          const int sl = it % 3;
          if (it >= 3) mbar_wait(bE + sl * 8, ((it / 3) - 1) & 1);
          mbar_expect_tx(bF + sl * 8, B_SLOT);
          for (int c = 0; c < 3; c++)
            tma_load_3d(sb + B_KV + sl * B_SLOT + c * 18432, &tm_kv, bF + sl * 8, 192 + kvsel * 192 + c * 64, kb * 144, t);
          it++;
        }
      }
      if (owner) {
        for (int i = 0; i < 3; i++) {
          const int sl = it % 3;
          if (it >= 3) mbar_wait(bE + sl * 8, ((it / 3) - 1) & 1);
          mbar_expect_tx(bF + sl * 8, 24576);
          tma_load_2d(sb + B_KV + sl * B_SLOT, &tm_wos, bF + sl * 8, sl * 64, 0);
          it++;
        }
        const int t = last_tile / 11, qt = last_tile - t * 11;
        mbar_wait(bQE, (qn - 1) & 1);
        mbar_expect_tx(bQF, 49152);
        for (int c = 0; c < 3; c++) tma_load_3d(sb + B_Q + c * 16384, &tm_x1, bQF, c * 64, qt * 128, t);
      }
    }
    return;
  }

  asm volatile("setmaxnreg.inc.sync.aligned.u32 240;");
  const int wg = warp >> 2, wq = warp & 3;
  const int wtid = tid & 127;
  const float cs = 0.07216878364870322f * 1.4426950408889634f;
  float oacc[96];
  float m0 = -INFINITY, m1 = -INFINITY, l0 = 0.f, l1 = 0.f;
#pragma unroll
  for (int i = 0; i < 96; i++) oacc[i] = 0.f;
  int it = 0, qn = 0;
  const uint32_t qb = sb + B_Q + wg * 8192;

  for (int s = s_begin; s < s_end; s++) {
    const int tile = s / 9, kb = s - tile * 9;
    if (s == s_begin || kb == 0) {
      mbar_wait(bQF, qn & 1);
      qn++;
    }
    float sacc[72];
    {
      const int sl = it % 3;
      mbar_wait(bF + sl * 8, (it / 3) & 1);
      const uint32_t kbase = sb + B_KV + sl * B_SLOT;
      wg_fence();
#pragma unroll
      for (int kk = 0; kk < 12; kk++)
        wgmma_n144_ss<0>(sacc, mk_desc(qb + (kk >> 2) * 16384 + (kk & 3) * 32, 16, 1024),
                         mk_desc(kbase + (kk >> 2) * 18432 + (kk & 3) * 32, 16, 1024), kk > 0);
      wg_commit();
      wg_wait<0>(); reg_fence(sacc);
      if (lane == 0) mbar_arrive(bE + sl * 8);
      it++;
    }
    const bool seg_last = (s + 1 == s_end) || (kb == 8);
    if (seg_last && lane == 0) mbar_arrive(bQE);
    float mx0 = m0, mx1 = m1;
#pragma unroll
    for (int j = 0; j < 18; j++) {
      mx0 = fmaxf(mx0, fmaxf(sacc[4 * j], sacc[4 * j + 1]));
      mx1 = fmaxf(mx1, fmaxf(sacc[4 * j + 2], sacc[4 * j + 3]));
    }
    mx0 = fmaxf(mx0, __shfl_xor_sync(0xffffffffu, mx0, 1)); mx0 = fmaxf(mx0, __shfl_xor_sync(0xffffffffu, mx0, 2));
    mx1 = fmaxf(mx1, __shfl_xor_sync(0xffffffffu, mx1, 1)); mx1 = fmaxf(mx1, __shfl_xor_sync(0xffffffffu, mx1, 2));
    const float a0 = ex2((m0 - mx0) * cs), a1 = ex2((m1 - mx1) * cs);
    m0 = mx0; m1 = mx1;
    const float mc0 = mx0 * cs, mc1 = mx1 * cs;
    float rs0 = 0.f, rs1 = 0.f;
    uint32_t pf[9][4];
#pragma unroll
    for (int k = 0; k < 9; k++) {
      float p[8];
#pragma unroll
      for (int e = 0; e < 8; e++) p[e] = ex2(fmaf(sacc[8 * k + e], cs, (e & 2) ? -mc1 : -mc0));
      rs0 += (p[0] + p[1]) + (p[4] + p[5]);
      rs1 += (p[2] + p[3]) + (p[6] + p[7]);
      pf[k][0] = pack_bf16(p[0], p[1]); pf[k][1] = pack_bf16(p[2], p[3]);
      pf[k][2] = pack_bf16(p[4], p[5]); pf[k][3] = pack_bf16(p[6], p[7]);
    }
    l0 = l0 * a0 + rs0; l1 = l1 * a1 + rs1;
#pragma unroll
    for (int j = 0; j < 24; j++) {
      oacc[4 * j] *= a0; oacc[4 * j + 1] *= a0; oacc[4 * j + 2] *= a1; oacc[4 * j + 3] *= a1;
    }
    {
      const int sl = it % 3;
      mbar_wait(bF + sl * 8, (it / 3) & 1);
      const uint32_t vbase = sb + B_KV + sl * B_SLOT;
      wg_fence();
#pragma unroll
      for (int kk = 0; kk < 9; kk++) wgmma_n192_rs<1>(oacc, pf[kk], mk_desc(vbase + kk * 2048, 18432, 1024), 1);
      wg_commit();
      wg_wait<0>(); reg_fence(oacc);
      if (lane == 0) mbar_arrive(bE + sl * 8);
      it++;
    }
    if (seg_last && !(owner && s + 1 == s_end)) {
      float4* dst = g_part + (size_t)(cta * 2 + wg) * 25 * 128 + wtid;
#pragma unroll
      for (int i = 0; i < 24; i++) dst[i * 128] = make_float4(oacc[4 * i], oacc[4 * i + 1], oacc[4 * i + 2], oacc[4 * i + 3]);
      dst[24 * 128] = make_float4(m0, m1, l0, l1);
      __threadfence();
      named_bar(1 + wg, 128);
      if (wtid == 0) atomicAdd(&g_flag[cta], 1u);
      m0 = m1 = -INFINITY; l0 = l1 = 0.f;
#pragma unroll
      for (int i = 0; i < 96; i++) oacc[i] = 0.f;
    }
  }
  if (!owner) return;

  {
    const int tile_end = (last_tile + 1) * 9;
    for (int c2 = cta + 1; c2 < B_GRID && b_start(c2) < tile_end; c2++) {
      if (wtid == 0) {
        uint32_t n = 0, v;
        do {
          asm volatile("ld.acquire.gpu.global.u32 %0, [%1];" : "=r"(v) : "l"(&g_flag[c2]) : "memory");
        } while (v < 2u && ++n < (1u << 24));
      }
      named_bar(1 + wg, 128);
      const float4* src = g_part + (size_t)(c2 * 2 + wg) * 25 * 128 + wtid;
      const float4 ml = __ldcg(src + 24 * 128);
      const float mx0 = fmaxf(m0, ml.x), mx1 = fmaxf(m1, ml.y);
      const float a0 = ex2((m0 - mx0) * cs), a1 = ex2((m1 - mx1) * cs);
      const float b0 = ex2((ml.x - mx0) * cs), b1 = ex2((ml.y - mx1) * cs);
      m0 = mx0; m1 = mx1;
      l0 = l0 * a0 + ml.z * b0; l1 = l1 * a1 + ml.w * b1;
#pragma unroll
      for (int i = 0; i < 24; i++) {
        const float4 v = __ldcg(src + i * 128);
        oacc[4 * i] = oacc[4 * i] * a0 + v.x * b0; oacc[4 * i + 1] = oacc[4 * i + 1] * a0 + v.y * b0;
        oacc[4 * i + 2] = oacc[4 * i + 2] * a1 + v.z * b1; oacc[4 * i + 3] = oacc[4 * i + 3] * a1 + v.w * b1;
      }
    }
  }
  l0 += __shfl_xor_sync(0xffffffffu, l0, 1); l0 += __shfl_xor_sync(0xffffffffu, l0, 2);
  l1 += __shfl_xor_sync(0xffffffffu, l1, 1); l1 += __shfl_xor_sync(0xffffffffu, l1, 2);
  const float i0 = 1.f / l0, i1 = 1.f / l1;
  uint32_t of[12][4];
#pragma unroll
  for (int k = 0; k < 12; k++) {
    of[k][0] = pack_bf16(oacc[8 * k + 0] * i0, oacc[8 * k + 1] * i0);
    of[k][1] = pack_bf16(oacc[8 * k + 2] * i1, oacc[8 * k + 3] * i1);
    of[k][2] = pack_bf16(oacc[8 * k + 4] * i0, oacc[8 * k + 5] * i0);
    of[k][3] = pack_bf16(oacc[8 * k + 6] * i1, oacc[8 * k + 7] * i1);
  }
  for (int i = 0; i < 3; i++) { mbar_wait(bF + (it % 3) * 8, (it / 3) & 1); it++; }
  wg_fence();
#pragma unroll
  for (int kk = 0; kk < 12; kk++) wgmma_n192_rs<1>(oacc, of[kk], mk_desc(sb + B_KV + kk * 2048, B_SLOT, 1024), kk > 0);
  wg_commit();
  wg_wait<0>(); reg_fence(oacc);
  mbar_wait(bQF, qn & 1);
  const FragAddr fa(wq, lane);
#pragma unroll
  for (int c = 0; c < 3; c++) resid_chunk(nullptr, &oacc[32 * c], qb + c * 16384, fa);
  fence_proxy_async();
  named_bar(1 + wg, 128);
  if (wtid == 0) {
    const int t = last_tile / 11, qt = last_tile - t * 11;
    if (qt * 128 + wg * 64 < NL) {
      for (int c = 0; c < 3; c++) tma_store_3d(&tm_out, qb + c * 16384, c * 64, qt * 128 + wg * 64, t);
      bulk_commit();
      bulk_wait0();
    }
  }
}

typedef CUresult (*EncodeFn)(CUtensorMap*, CUtensorMapDataType, cuuint32_t, void*, const cuuint64_t*, const cuuint64_t*,
                             const cuuint32_t*, const cuuint32_t*, CUtensorMapInterleave, CUtensorMapSwizzle,
                             CUtensorMapL2promotion, CUtensorMapFloatOOBfill);

void make_map(EncodeFn enc, CUtensorMap* m, const void* ptr, int rank, const uint64_t* dims, const uint32_t* box) {
  cuuint64_t gd[3], gs[2];
  cuuint32_t bx[3], es[3] = {1, 1, 1};
  uint64_t stride = 2;
  for (int i = 0; i < rank; i++) {
    gd[i] = dims[i]; bx[i] = box[i];
    stride *= dims[i];
    if (i < rank - 1) gs[i] = stride;
  }
  enc(m, CU_TENSOR_MAP_DATA_TYPE_BFLOAT16, rank, const_cast<void*>(ptr), gd, gs, bx, es, CU_TENSOR_MAP_INTERLEAVE_NONE,
      CU_TENSOR_MAP_SWIZZLE_128B, CU_TENSOR_MAP_L2_PROMOTION_L2_256B, CU_TENSOR_MAP_FLOAT_OOB_FILL_NONE);
}

}

extern "C" void kernel_launch(void* const* d_in, const int* in_sizes, int n_in, void* d_out, int out_size) {
  (void)in_sizes; (void)n_in; (void)out_size;
  EncodeFn enc = nullptr;
  cudaDriverEntryPointQueryResult qres;
  cudaGetDriverEntryPoint("cuTensorMapEncodeTiled", (void**)&enc, cudaEnableDefault, &qres);
  void *p_x1, *p_qkv;
  cudaGetSymbolAddress(&p_x1, g_x1);
  cudaGetSymbolAddress(&p_qkv, g_qkv);
  cudaFuncSetAttribute(kernelA, cudaFuncAttributeMaxDynamicSharedMemorySize, A_SMEM);
  cudaFuncSetAttribute(kernelB, cudaFuncAttributeMaxDynamicSharedMemorySize, B_SMEM);

  CUtensorMap tm_x, tm_wqkvt, tm_wot, tm_wqkvs, tm_x1s, tm_qkvs, tm_q, tm_kv, tm_wos, tm_x1l, tm_out;
  const uint64_t d_act[3] = {192, 1296, 7}, d_qkv[3] = {576, 1296, 7}, d_w3[2] = {576, 192}, d_w1[2] = {192, 192};
  const uint32_t b_a[3] = {64, 9, 7}, b_w[2] = {64, 192}, b_q[3] = {64, 128, 1}, b_kv[3] = {64, 144, 1}, b_o[3] = {64, 64, 1};
  make_map(enc, &tm_x, d_in[0], 3, d_act, b_a);
  make_map(enc, &tm_wqkvt, d_in[1], 2, d_w3, b_w);
  make_map(enc, &tm_wot, d_in[2], 2, d_w1, b_w);
  make_map(enc, &tm_wqkvs, d_in[3], 2, d_w3, b_w);
  make_map(enc, &tm_wos, d_in[4], 2, d_w1, b_w);
  make_map(enc, &tm_x1s, p_x1, 3, d_act, b_a);
  make_map(enc, &tm_qkvs, p_qkv, 3, d_qkv, b_a);
  make_map(enc, &tm_q, p_qkv, 3, d_qkv, b_q);
  make_map(enc, &tm_kv, p_qkv, 3, d_qkv, b_kv);
  make_map(enc, &tm_x1l, p_x1, 3, d_act, b_q);
  make_map(enc, &tm_out, d_out, 3, d_act, b_o);

  kernelA<<<72, 384, A_SMEM>>>(tm_x, tm_wqkvt, tm_wot, tm_wqkvs, tm_x1s, tm_qkvs);
  kernelB<<<B_GRID, 384, B_SMEM>>>(tm_q, tm_kv, tm_wos, tm_x1l, tm_out);
}
```

```cpp
#include <cuda_runtime.h>
#include <cuda_bf16.h>
#include <cuda.h>
#include <stdint.h>

namespace {

constexpr int TT = 7, NL = 1296, CC = 192;

__device__ __align__(1024) __nv_bfloat16 g_x1[TT * NL * CC];
__device__ __align__(1024) __nv_bfloat16 g_qkv[TT * NL * 3 * CC];
__device__ __align__(1024) __nv_bfloat16 g_wf[2 * CC * 2 * CC];
__device__ __align__(1024) float4 g_part[110 * 2 * 25 * 128];
__device__ unsigned int g_flag[128];
__device__ unsigned int g_wflag[4];

#define TS(k, i)

__device__ __forceinline__ uint32_t smem_u32(const void* p) { return (uint32_t)__cvta_generic_to_shared(p); }
__device__ __forceinline__ void mbar_init(uint32_t bar, uint32_t cnt) {
  asm volatile("mbarrier.init.shared::cta.b64 [%0], %1;" ::"r"(bar), "r"(cnt));
}
__device__ __forceinline__ void mbar_expect_tx(uint32_t bar, uint32_t bytes) {
  asm volatile("mbarrier.arrive.expect_tx.shared::cta.b64 _, [%0], %1;" ::"r"(bar), "r"(bytes) : "memory");
}
__device__ __forceinline__ void mbar_arrive(uint32_t bar) {
  asm volatile("mbarrier.arrive.shared::cta.b64 _, [%0];" ::"r"(bar) : "memory");
}
__device__ __forceinline__ bool mbar_try(uint32_t bar, uint32_t parity) {
  uint32_t ok;
  asm volatile("{\n.reg .pred p;\nmbarrier.try_wait.parity.shared::cta.b64 p, [%1], %2;\nselp.u32 %0, 1, 0, p;\n}"
               : "=r"(ok) : "r"(bar), "r"(parity) : "memory");
  return ok != 0;
}
__device__ __forceinline__ void mbar_wait(uint32_t bar, uint32_t parity) {
  if (mbar_try(bar, parity)) return;
  uint32_t n = 0;
  while (!mbar_try(bar, parity)) {
    if (++n > (1u << 22)) break;
  }
}
__device__ __forceinline__ void tma_load_2d(uint32_t dst, const CUtensorMap* m, uint32_t bar, int c0, int c1) {
  asm volatile("cp.async.bulk.tensor.2d.shared::cluster.global.mbarrier::complete_tx::bytes [%0], [%1, {%3, %4}], [%2];"
               ::"r"(dst), "l"(m), "r"(bar), "r"(c0), "r"(c1) : "memory");
}
__device__ __forceinline__ void tma_load_3d(uint32_t dst, const CUtensorMap* m, uint32_t bar, int c0, int c1, int c2) {
  asm volatile("cp.async.bulk.tensor.3d.shared::cluster.global.mbarrier::complete_tx::bytes [%0], [%1, {%3, %4, %5}], [%2];"
               ::"r"(dst), "l"(m), "r"(bar), "r"(c0), "r"(c1), "r"(c2) : "memory");
}
__device__ __forceinline__ void tma_store_3d(const CUtensorMap* m, uint32_t src, int c0, int c1, int c2) {
  asm volatile("cp.async.bulk.tensor.3d.global.shared::cta.bulk_group [%0, {%2, %3, %4}], [%1];"
               ::"l"(m), "r"(src), "r"(c0), "r"(c1), "r"(c2) : "memory");
}
__device__ __forceinline__ void bulk_commit() { asm volatile("cp.async.bulk.commit_group;" ::: "memory"); }
__device__ __forceinline__ void bulk_wait_read0() { asm volatile("cp.async.bulk.wait_group.read 0;" ::: "memory"); }
__device__ __forceinline__ void bulk_wait0() { asm volatile("cp.async.bulk.wait_group 0;" ::: "memory"); }
__device__ __forceinline__ void fence_proxy_async() { asm volatile("fence.proxy.async.shared::cta;" ::: "memory"); }
__device__ __forceinline__ void prefetch_tmap(const CUtensorMap* m) {
  asm volatile("prefetch.tensormap [%0];" ::"l"(m) : "memory");
}
__device__ __forceinline__ void wg_fence() { asm volatile("wgmma.fence.sync.aligned;" ::: "memory"); }
__device__ __forceinline__ void wg_commit() { asm volatile("wgmma.commit_group.sync.aligned;" ::: "memory"); }
template <int N> __device__ __forceinline__ void wg_wait() { asm volatile("wgmma.wait_group.sync.aligned %0;" ::"n"(N) : "memory"); }
__device__ __forceinline__ void named_bar(int id, int nthreads) {
  asm volatile("bar.sync %0, %1;" ::"r"(id), "r"(nthreads) : "memory");
}
__device__ __forceinline__ void ldsm_x4(uint32_t (&r)[4], uint32_t addr) {
  asm volatile("ldmatrix.sync.aligned.m8n8.x4.shared.b16 {%0,%1,%2,%3}, [%4];"
               : "=r"(r[0]), "=r"(r[1]), "=r"(r[2]), "=r"(r[3]) : "r"(addr) : "memory");
}
__device__ __forceinline__ void stsm_x4(uint32_t addr, const uint32_t (&r)[4]) {
  asm volatile("stmatrix.sync.aligned.m8n8.x4.shared.b16 [%0], {%1,%2,%3,%4};"
               ::"r"(addr), "r"(r[0]), "r"(r[1]), "r"(r[2]), "r"(r[3]) : "memory");
}
__device__ __forceinline__ uint32_t pack_bf16(float lo, float hi) {
  uint32_t r;
  asm("cvt.rn.bf16x2.f32 %0, %1, %2;" : "=r"(r) : "f"(hi), "f"(lo));
  return r;
}
__device__ __forceinline__ float bf_lo(uint32_t v) { return __uint_as_float(v << 16); }
__device__ __forceinline__ float bf_hi(uint32_t v) { return __uint_as_float(v & 0xffff0000u); }
__device__ __forceinline__ float ex2(float x) {
  float y;
  asm("ex2.approx.ftz.f32 %0, %1;" : "=f"(y) : "f"(x));
  return y;
}
__device__ __forceinline__ uint64_t mk_desc(uint32_t addr, uint32_t lbo, uint32_t sbo) {
  return (uint64_t)((addr & 0x3FFFF) >> 4) | ((uint64_t)((lbo & 0x3FFFF) >> 4) << 16) |
         ((uint64_t)((sbo & 0x3FFFF) >> 4) << 32) | (1ull << 62);
}
__device__ __forceinline__ uint64_t mk_desc_o(uint32_t addr, uint32_t lbo, uint32_t sbo) {
  asm volatile("" : "+r"(addr));
  return mk_desc(addr, lbo, sbo);
}
template <int N> __device__ __forceinline__ void reg_fence(float (&d)[N]) {
#pragma unroll
  for (int i = 0; i < N; i++) asm volatile("" : "+f"(d[i])::"memory");
}

template<int TB> __device__ __forceinline__ void wgmma_n144_ss(float (&d)[72], uint64_t da, uint64_t db, int sc) {
  asm volatile("{\n.reg .pred p;\nsetp.ne.b32 p, %74, 0;\n"
    "wgmma.mma_async.sync.aligned.m64n144k16.f32.bf16.bf16 {%0, %1, %2, %3, %4, %5, %6, %7, %8, %9, %10, %11, %12, %13, %14, %15, %16, %17, %18, %19, %20, %21, %22, %23, %24, %25, %26, %27, %28, %29, %30, %31, %32, %33, %34, %35, %36, %37, %38, %39, %40, %41, %42, %43, %44, %45, %46, %47, %48, %49, %50, %51, %52, %53, %54, %55, %56, %57, %58, %59, %60, %61, %62, %63, %64, %65, %66, %67, %68, %69, %70, %71}, %72, %73, p, 1, 1, 0, %75;\n}\n"
    : "+f"(d[0]), "+f"(d[1]), "+f"(d[2]), "+f"(d[3]), "+f"(d[4]), "+f"(d[5]), "+f"(d[6]), "+f"(d[7]), "+f"(d[8]), "+f"(d[9]), "+f"(d[10]), "+f"(d[11]), "+f"(d[12]), "+f"(d[13]), "+f"(d[14]), "+f"(d[15]), "+f"(d[16]), "+f"(d[17]), "+f"(d[18]), "+f"(d[19]), "+f"(d[20]), "+f"(d[21]), "+f"(d[22]), "+f"(d[23]), "+f"(d[24]), "+f"(d[25]), "+f"(d[26]), "+f"(d[27]), "+f"(d[28]), "+f"(d[29]), "+f"(d[30]), "+f"(d[31]), "+f"(d[32]), "+f"(d[33]), "+f"(d[34]), "+f"(d[35]), "+f"(d[36]), "+f"(d[37]), "+f"(d[38]), "+f"(d[39]), "+f"(d[40]), "+f"(d[41]), "+f"(d[42]), "+f"(d[43]), "+f"(d[44]), "+f"(d[45]), "+f"(d[46]), "+f"(d[47]), "+f"(d[48]), "+f"(d[49]), "+f"(d[50]), "+f"(d[51]), "+f"(d[52]), "+f"(d[53]), "+f"(d[54]), "+f"(d[55]), "+f"(d[56]), "+f"(d[57]), "+f"(d[58]), "+f"(d[59]), "+f"(d[60]), "+f"(d[61]), "+f"(d[62]), "+f"(d[63]), "+f"(d[64]), "+f"(d[65]), "+f"(d[66]), "+f"(d[67]), "+f"(d[68]), "+f"(d[69]), "+f"(d[70]), "+f"(d[71])
    : "l"(da), "l"(db), "r"(sc), "n"(TB));
}
template<int TB> __device__ __forceinline__ void wgmma_n192_rs(float (&d)[96], const uint32_t (&a)[4], uint64_t db, int sc) {
  asm volatile("{\n.reg .pred p;\nsetp.ne.b32 p, %101, 0;\n"
    "wgmma.mma_async.sync.aligned.m64n192k16.f32.bf16.bf16 {%0, %1, %2, %3, %4, %5, %6, %7, %8, %9, %10, %11, %12, %13, %14, %15, %16, %17, %18, %19, %20, %21, %22, %23, %24, %25, %26, %27, %28, %29, %30, %31, %32, %33, %34, %35, %36, %37, %38, %39, %40, %41, %42, %43, %44, %45, %46, %47, %48, %49, %50, %51, %52, %53, %54, %55, %56, %57, %58, %59, %60, %61, %62, %63, %64, %65, %66, %67, %68, %69, %70, %71, %72, %73, %74, %75, %76, %77, %78, %79, %80, %81, %82, %83, %84, %85, %86, %87, %88, %89, %90, %91, %92, %93, %94, %95}, {%96, %97, %98, %99}, %100, p, 1, 1, %102;\n}\n"
    : "+f"(d[0]), "+f"(d[1]), "+f"(d[2]), "+f"(d[3]), "+f"(d[4]), "+f"(d[5]), "+f"(d[6]), "+f"(d[7]), "+f"(d[8]), "+f"(d[9]), "+f"(d[10]), "+f"(d[11]), "+f"(d[12]), "+f"(d[13]), "+f"(d[14]), "+f"(d[15]), "+f"(d[16]), "+f"(d[17]), "+f"(d[18]), "+f"(d[19]), "+f"(d[20]), "+f"(d[21]), "+f"(d[22]), "+f"(d[23]), "+f"(d[24]), "+f"(d[25]), "+f"(d[26]), "+f"(d[27]), "+f"(d[28]), "+f"(d[29]), "+f"(d[30]), "+f"(d[31]), "+f"(d[32]), "+f"(d[33]), "+f"(d[34]), "+f"(d[35]), "+f"(d[36]), "+f"(d[37]), "+f"(d[38]), "+f"(d[39]), "+f"(d[40]), "+f"(d[41]), "+f"(d[42]), "+f"(d[43]), "+f"(d[44]), "+f"(d[45]), "+f"(d[46]), "+f"(d[47]), "+f"(d[48]), "+f"(d[49]), "+f"(d[50]), "+f"(d[51]), "+f"(d[52]), "+f"(d[53]), "+f"(d[54]), "+f"(d[55]), "+f"(d[56]), "+f"(d[57]), "+f"(d[58]), "+f"(d[59]), "+f"(d[60]), "+f"(d[61]), "+f"(d[62]), "+f"(d[63]), "+f"(d[64]), "+f"(d[65]), "+f"(d[66]), "+f"(d[67]), "+f"(d[68]), "+f"(d[69]), "+f"(d[70]), "+f"(d[71]), "+f"(d[72]), "+f"(d[73]), "+f"(d[74]), "+f"(d[75]), "+f"(d[76]), "+f"(d[77]), "+f"(d[78]), "+f"(d[79]), "+f"(d[80]), "+f"(d[81]), "+f"(d[82]), "+f"(d[83]), "+f"(d[84]), "+f"(d[85]), "+f"(d[86]), "+f"(d[87]), "+f"(d[88]), "+f"(d[89]), "+f"(d[90]), "+f"(d[91]), "+f"(d[92]), "+f"(d[93]), "+f"(d[94]), "+f"(d[95])
    : "r"(a[0]), "r"(a[1]), "r"(a[2]), "r"(a[3]), "l"(db), "r"(sc), "n"(TB));
}
template<int TB> __device__ __forceinline__ void wgmma_n192_ss(float (&d)[96], uint64_t da, uint64_t db, int sc) {
  asm volatile("{\n.reg .pred p;\nsetp.ne.b32 p, %98, 0;\n"
    "wgmma.mma_async.sync.aligned.m64n192k16.f32.bf16.bf16 {%0, %1, %2, %3, %4, %5, %6, %7, %8, %9, %10, %11, %12, %13, %14, %15, %16, %17, %18, %19, %20, %21, %22, %23, %24, %25, %26, %27, %28, %29, %30, %31, %32, %33, %34, %35, %36, %37, %38, %39, %40, %41, %42, %43, %44, %45, %46, %47, %48, %49, %50, %51, %52, %53, %54, %55, %56, %57, %58, %59, %60, %61, %62, %63, %64, %65, %66, %67, %68, %69, %70, %71, %72, %73, %74, %75, %76, %77, %78, %79, %80, %81, %82, %83, %84, %85, %86, %87, %88, %89, %90, %91, %92, %93, %94, %95}, %96, %97, p, 1, 1, 0, %99;\n}\n"
    : "+f"(d[0]), "+f"(d[1]), "+f"(d[2]), "+f"(d[3]), "+f"(d[4]), "+f"(d[5]), "+f"(d[6]), "+f"(d[7]), "+f"(d[8]), "+f"(d[9]), "+f"(d[10]), "+f"(d[11]), "+f"(d[12]), "+f"(d[13]), "+f"(d[14]), "+f"(d[15]), "+f"(d[16]), "+f"(d[17]), "+f"(d[18]), "+f"(d[19]), "+f"(d[20]), "+f"(d[21]), "+f"(d[22]), "+f"(d[23]), "+f"(d[24]), "+f"(d[25]), "+f"(d[26]), "+f"(d[27]), "+f"(d[28]), "+f"(d[29]), "+f"(d[30]), "+f"(d[31]), "+f"(d[32]), "+f"(d[33]), "+f"(d[34]), "+f"(d[35]), "+f"(d[36]), "+f"(d[37]), "+f"(d[38]), "+f"(d[39]), "+f"(d[40]), "+f"(d[41]), "+f"(d[42]), "+f"(d[43]), "+f"(d[44]), "+f"(d[45]), "+f"(d[46]), "+f"(d[47]), "+f"(d[48]), "+f"(d[49]), "+f"(d[50]), "+f"(d[51]), "+f"(d[52]), "+f"(d[53]), "+f"(d[54]), "+f"(d[55]), "+f"(d[56]), "+f"(d[57]), "+f"(d[58]), "+f"(d[59]), "+f"(d[60]), "+f"(d[61]), "+f"(d[62]), "+f"(d[63]), "+f"(d[64]), "+f"(d[65]), "+f"(d[66]), "+f"(d[67]), "+f"(d[68]), "+f"(d[69]), "+f"(d[70]), "+f"(d[71]), "+f"(d[72]), "+f"(d[73]), "+f"(d[74]), "+f"(d[75]), "+f"(d[76]), "+f"(d[77]), "+f"(d[78]), "+f"(d[79]), "+f"(d[80]), "+f"(d[81]), "+f"(d[82]), "+f"(d[83]), "+f"(d[84]), "+f"(d[85]), "+f"(d[86]), "+f"(d[87]), "+f"(d[88]), "+f"(d[89]), "+f"(d[90]), "+f"(d[91]), "+f"(d[92]), "+f"(d[93]), "+f"(d[94]), "+f"(d[95])
    : "l"(da), "l"(db), "r"(sc), "n"(TB));
}
template<int TB> __device__ __forceinline__ void wgmma_n64_rs(float (&d)[32], const uint32_t (&a)[4], uint64_t db, int sc) {
  asm volatile("{\n.reg .pred p;\nsetp.ne.b32 p, %37, 0;\n"
    "wgmma.mma_async.sync.aligned.m64n64k16.f32.bf16.bf16 {%0, %1, %2, %3, %4, %5, %6, %7, %8, %9, %10, %11, %12, %13, %14, %15, %16, %17, %18, %19, %20, %21, %22, %23, %24, %25, %26, %27, %28, %29, %30, %31}, {%32, %33, %34, %35}, %36, p, 1, 1, %38;\n}\n"
    : "+f"(d[0]), "+f"(d[1]), "+f"(d[2]), "+f"(d[3]), "+f"(d[4]), "+f"(d[5]), "+f"(d[6]), "+f"(d[7]), "+f"(d[8]), "+f"(d[9]), "+f"(d[10]), "+f"(d[11]), "+f"(d[12]), "+f"(d[13]), "+f"(d[14]), "+f"(d[15]), "+f"(d[16]), "+f"(d[17]), "+f"(d[18]), "+f"(d[19]), "+f"(d[20]), "+f"(d[21]), "+f"(d[22]), "+f"(d[23]), "+f"(d[24]), "+f"(d[25]), "+f"(d[26]), "+f"(d[27]), "+f"(d[28]), "+f"(d[29]), "+f"(d[30]), "+f"(d[31])
    : "r"(a[0]), "r"(a[1]), "r"(a[2]), "r"(a[3]), "l"(db), "r"(sc), "n"(TB));
}

struct FragAddr {
  uint32_t rowoff;
  uint32_t rx;
  uint32_t hi;
  __device__ __forceinline__ FragAddr(int warp_in_wg, int lane) {
    int row = 16 * warp_in_wg + (lane & 7) + ((lane >> 3) & 1) * 8;
    rowoff = row * 128;
    rx = row & 7;
    hi = lane >> 4;
  }
  __device__ __forceinline__ uint32_t at(uint32_t chunk_base, int kk4) const {
    return chunk_base + rowoff + ((((uint32_t)kk4 * 2 + hi) ^ rx) << 4);
  }
};

__device__ __forceinline__ void layernorm_frags(uint32_t (&f)[12][4]) {
  float s0 = 0.f, s1 = 0.f;
#pragma unroll
  for (int k = 0; k < 12; k++) {
    s0 += bf_lo(f[k][0]) + bf_hi(f[k][0]) + bf_lo(f[k][2]) + bf_hi(f[k][2]);
    s1 += bf_lo(f[k][1]) + bf_hi(f[k][1]) + bf_lo(f[k][3]) + bf_hi(f[k][3]);
  }
  s0 += __shfl_xor_sync(0xffffffffu, s0, 1); s0 += __shfl_xor_sync(0xffffffffu, s0, 2);
  s1 += __shfl_xor_sync(0xffffffffu, s1, 1); s1 += __shfl_xor_sync(0xffffffffu, s1, 2);
  const float m0 = s0 * (1.f / 192.f), m1 = s1 * (1.f / 192.f);
  float v0 = 0.f, v1 = 0.f;
#pragma unroll
  for (int k = 0; k < 12; k++) {
    float a;
    a = bf_lo(f[k][0]) - m0; v0 += a * a; a = bf_hi(f[k][0]) - m0; v0 += a * a;
    a = bf_lo(f[k][2]) - m0; v0 += a * a; a = bf_hi(f[k][2]) - m0; v0 += a * a;
    a = bf_lo(f[k][1]) - m1; v1 += a * a; a = bf_hi(f[k][1]) - m1; v1 += a * a;
    a = bf_lo(f[k][3]) - m1; v1 += a * a; a = bf_hi(f[k][3]) - m1; v1 += a * a;
  }
  v0 += __shfl_xor_sync(0xffffffffu, v0, 1); v0 += __shfl_xor_sync(0xffffffffu, v0, 2);
  v1 += __shfl_xor_sync(0xffffffffu, v1, 1); v1 += __shfl_xor_sync(0xffffffffu, v1, 2);
  const float r0 = rsqrtf(v0 * (1.f / 192.f) + 1e-5f), r1 = rsqrtf(v1 * (1.f / 192.f) + 1e-5f);
#pragma unroll
  for (int k = 0; k < 12; k++) {
    f[k][0] = pack_bf16((bf_lo(f[k][0]) - m0) * r0, (bf_hi(f[k][0]) - m0) * r0);
    f[k][2] = pack_bf16((bf_lo(f[k][2]) - m0) * r0, (bf_hi(f[k][2]) - m0) * r0);
    f[k][1] = pack_bf16((bf_lo(f[k][1]) - m1) * r1, (bf_hi(f[k][1]) - m1) * r1);
    f[k][3] = pack_bf16((bf_lo(f[k][3]) - m1) * r1, (bf_hi(f[k][3]) - m1) * r1);
  }
}

constexpr int A_NST = 3;
constexpr int A_XS = 0;
constexpr int A_KB = 49152;
constexpr int A_VB = 98304;
constexpr int A_W = 147456;
constexpr int A_BAR = A_W + A_NST * 24576;
constexpr int A_SMEM = A_BAR + 256 + 1024;
constexpr int A_FOLD = 12;

__device__ __forceinline__ void a_issue(float (&acc)[32], const uint32_t (&af)[12][4], uint32_t sb, int s) {
  const int st = s % A_NST;
  mbar_wait(sb + A_BAR + st * 8, (s / A_NST) & 1);
  const uint64_t wd = mk_desc_o(sb + A_W + st * 24576, 8192, 1024);
  wg_fence();
#pragma unroll
  for (int kk = 0; kk < 12; kk++) wgmma_n64_rs<1>(acc, af[kk], wd + kk * 128, kk > 0);
  wg_commit();
}
__device__ __forceinline__ void a_release(uint32_t sb, int s, int lane) {
  if (lane == 0) mbar_arrive(sb + A_BAR + 64 + (s % A_NST) * 8);
}
__device__ __forceinline__ void cvt_frags(uint32_t (*dst)[4], const float (&acc)[32]) {
#pragma unroll
  for (int k = 0; k < 4; k++) {
    dst[k][0] = pack_bf16(acc[8 * k + 0], acc[8 * k + 1]);
    dst[k][1] = pack_bf16(acc[8 * k + 2], acc[8 * k + 3]);
    dst[k][2] = pack_bf16(acc[8 * k + 4], acc[8 * k + 5]);
    dst[k][3] = pack_bf16(acc[8 * k + 6], acc[8 * k + 7]);
  }
}
__device__ __forceinline__ void store_chunk(const float (&acc)[32], uint32_t chunk_base, const FragAddr& fa) {
  uint32_t t[4][4];
  cvt_frags(t, acc);
#pragma unroll
  for (int k = 0; k < 4; k++) stsm_x4(fa.at(chunk_base, k), t[k]);
}
__device__ __forceinline__ void resid_chunk(uint32_t (*dst)[4], const float* acc, float s0, float s1, uint32_t chunk_base,
                                            const FragAddr& fa) {
#pragma unroll
  for (int k = 0; k < 4; k++) {
    uint32_t x[4];
    ldsm_x4(x, fa.at(chunk_base, k));
    uint32_t o[4];
    o[0] = pack_bf16(fmaf(acc[8 * k + 0], s0, bf_lo(x[0])), fmaf(acc[8 * k + 1], s0, bf_hi(x[0])));
    o[1] = pack_bf16(fmaf(acc[8 * k + 2], s1, bf_lo(x[1])), fmaf(acc[8 * k + 3], s1, bf_hi(x[1])));
    o[2] = pack_bf16(fmaf(acc[8 * k + 4], s0, bf_lo(x[2])), fmaf(acc[8 * k + 5], s0, bf_hi(x[2])));
    o[3] = pack_bf16(fmaf(acc[8 * k + 6], s1, bf_lo(x[3])), fmaf(acc[8 * k + 7], s1, bf_hi(x[3])));
    stsm_x4(fa.at(chunk_base, k), o);
    if (dst) { dst[k][0] = o[0]; dst[k][1] = o[1]; dst[k][2] = o[2]; dst[k][3] = o[3]; }
  }
}

__global__ void __launch_bounds__(384, 1)
kernelA(const __grid_constant__ CUtensorMap tm_x, const __grid_constant__ CUtensorMap tm_wqkvt,
        const __grid_constant__ CUtensorMap tm_wot, const __grid_constant__ CUtensorMap tm_wqkvs,
        const __grid_constant__ CUtensorMap tm_wos, const __grid_constant__ CUtensorMap tm_wf,
        const __grid_constant__ CUtensorMap tm_x1, const __grid_constant__ CUtensorMap tm_qkv) {
  extern __shared__ uint8_t smem_raw[];
  const uint32_t sb = (smem_u32(smem_raw) + 1023) & ~1023u;
  const int tid = threadIdx.x, warp = tid >> 5, lane = tid & 31;
  const bool is_fold = blockIdx.x < A_FOLD;
  const int blk = blockIdx.x - A_FOLD;
  if (tid == 256) {
    for (int i = 0; i < A_NST; i++) { mbar_init(sb + A_BAR + i * 8, 1); mbar_init(sb + A_BAR + 64 + i * 8, 8); }
    mbar_init(sb + A_BAR + 128, 1); mbar_init(sb + A_BAR + 136, 1);
    asm volatile("fence.mbarrier_init.release.cluster;" ::: "memory");
    if (!is_fold) {
      for (int w = 0; w < 2; w++) {
        const uint32_t bar = sb + A_BAR + 128 + w * 8;
        mbar_expect_tx(bar, 3 * 63 * 128);
        for (int c = 0; c < 3; c++)
          tma_load_3d(sb + A_XS + w * 24576 + c * 8192, &tm_x, bar, c * 64, (blk * 2 + w) * 9, 0);
      }
    } else {
      const int mat = blockIdx.x / 3;
      const CUtensorMap* mq = (mat < 2) ? &tm_wqkvt : &tm_wqkvs;
      const CUtensorMap* mo = (mat < 2) ? &tm_wot : &tm_wos;
      const uint32_t bar = sb + A_BAR + 128;
      mbar_expect_tx(bar, 6 * 24576);
      for (int c = 0; c < 3; c++) {
        tma_load_2d(sb + c * 24576, mq, bar, ((mat & 1) ? 384 : 0) + c * 64, 0);
        if (mat & 1) tma_load_2d(sb + 73728 + c * 24576, mo, bar, c * 64, 0);
        else tma_load_2d(sb + 73728 + c * 24576, mq, bar, 192 + c * 64, 0);
      }
    }
  }
  if (blockIdx.x == 0 && tid < 128) g_flag[tid] = 0;
  if (!is_fold && tid < 48) {
    uint32_t a = sb + A_XS + (tid >> 3) * 8192 + 63 * 128 + (tid & 7) * 16;
    asm volatile("st.shared.v4.b32 [%0], {%1,%1,%1,%1};" ::"r"(a), "r"(0) : "memory");
  }
  __syncthreads();

  if (warp >= 8) {
    asm volatile("setmaxnreg.dec.sync.aligned.u32 24;");
    if (warp == 8 && lane == 0 && !is_fold) {
      for (int s = 0; s < 12; s++) {
        const int st = s % A_NST;
        const int g = s / 3;
        const int mat = (g == 0) ? 1 : (g == 1) ? 0 : g;
        if (s % 3 == 0) {
          uint32_t n = 0, v;
          do {
            asm volatile("ld.acquire.gpu.global.u32 %0, [%1];" : "=r"(v) : "l"(&g_wflag[mat]) : "memory");
          } while (v < 3u && ++n < (1u << 22));
          asm volatile("fence.proxy.async;" ::: "memory");
        }
        if (s >= A_NST) mbar_wait(sb + A_BAR + 64 + st * 8, ((s / A_NST) - 1) & 1);
        mbar_expect_tx(sb + A_BAR + st * 8, 24576);
        tma_load_2d(sb + A_W + st * 24576, &tm_wf, sb + A_BAR + st * 8, (mat & 1) * 192 + (s % 3) * 64, (mat >> 1) * 192);
      }
    }
    return;
  }

  asm volatile("setmaxnreg.inc.sync.aligned.u32 240;");
  const int wg = warp >> 2, wq = warp & 3;

  if (is_fold) {
    if (wg == 0) {
      const int mat = blockIdx.x / 3, slab = blockIdx.x % 3;
      float d[96];
      mbar_wait(sb + A_BAR + 128, 0);
      const uint64_t ad = mk_desc_o(sb + slab * 8192, 16, 1024);
      wg_fence();
      if (mat & 1) {
        const uint64_t bd = mk_desc_o(sb + 73728, 24576, 1024);
#pragma unroll
        for (int kk = 0; kk < 12; kk++) wgmma_n192_ss<1>(d, ad + (kk >> 2) * 1536 + (kk & 3) * 2, bd + kk * 128, kk > 0);
      } else {
        const uint64_t bd = mk_desc_o(sb + 73728, 16, 1024);
#pragma unroll
        for (int kk = 0; kk < 12; kk++)
          wgmma_n192_ss<0>(d, ad + (kk >> 2) * 1536 + (kk & 3) * 2, bd + (kk >> 2) * 1536 + (kk & 3) * 2, kk > 0);
      }
      wg_commit();
      wg_wait<0>(); reg_fence(d);
      const int r0 = slab * 64 + wq * 16 + (lane >> 2);
      uint32_t* dst = reinterpret_cast<uint32_t*>(g_wf + ((size_t)(mat >> 1) * 192 + r0) * 384 + (mat & 1) * 192 + (lane & 3) * 2);
#pragma unroll
      for (int j = 0; j < 24; j++) {
        dst[j * 4] = pack_bf16(d[4 * j], d[4 * j + 1]);
        dst[8 * 192 + j * 4] = pack_bf16(d[4 * j + 2], d[4 * j + 3]);
      }
      asm volatile("fence.proxy.async;" ::: "memory");
      __threadfence();
      named_bar(1, 128);
      if (tid == 0) atomicAdd(&g_wflag[mat], 1u);
    }
    return;
  }

  const int n0 = (blk * 2 + wg) * 9;
  const FragAddr fa(wq, lane);
  const uint32_t xs = sb + A_XS + wg * 24576, kb = sb + A_KB + wg * 24576, vb = sb + A_VB + wg * 24576;
  const int barid = 1 + wg;
  const bool elected = (tid & 127) == 0;

  uint32_t h[12][4];
  TS(0, 0);
  mbar_wait(sb + A_BAR + 128 + wg * 8, 0);
  TS(0, 1);
#pragma unroll
  for (int k = 0; k < 12; k++) ldsm_x4(h[k], fa.at(xs + (k >> 2) * 8192, k & 3));
  layernorm_frags(h);
#pragma unroll
  for (int k = 0; k < 12; k++) stsm_x4(fa.at(kb + (k >> 2) * 8192, k & 3), h[k]);

  float acc0[32], acc1[32];
  uint32_t qf[12][4];
  TS(0, 2);
  a_issue(acc0, h, sb, 0);
  TS(0, 3);
  a_issue(acc1, h, sb, 1); wg_wait<1>(); reg_fence(acc0); a_release(sb, 0, lane); store_chunk(acc0, vb, fa);
  a_issue(acc0, h, sb, 2); wg_wait<1>(); reg_fence(acc1); a_release(sb, 1, lane); store_chunk(acc1, vb + 8192, fa);
  a_issue(acc1, h, sb, 3); wg_wait<1>(); reg_fence(acc0); a_release(sb, 2, lane); store_chunk(acc0, vb + 16384, fa);
  fence_proxy_async();
  named_bar(barid, 128);
  a_issue(acc0, h, sb, 4); wg_wait<1>(); reg_fence(acc1); a_release(sb, 3, lane); cvt_frags(&qf[0], acc1);
  a_issue(acc1, h, sb, 5); wg_wait<1>(); reg_fence(acc0); a_release(sb, 4, lane); cvt_frags(&qf[4], acc0);
  wg_wait<0>(); reg_fence(acc1); a_release(sb, 5, lane); cvt_frags(&qf[8], acc1);
  TS(0, 4);
  {
    const uint64_t kd = mk_desc_o(kb, 16, 1024);
    wg_fence();
#pragma unroll
    for (int kk = 0; kk < 12; kk++) wgmma_n64_rs<0>(acc0, qf[kk], kd + (kk >> 2) * 512 + (kk & 3) * 2, kk > 0);
    wg_commit();
    wg_wait<0>(); reg_fence(acc0);
  }
  uint32_t pf[4][4];
  {
    const int r0 = 16 * wq + (lane >> 2), r1 = r0 + 8;
    const unsigned long long MB = 0x0040201008040201ull;
    const unsigned long long mk0 = (MB << (r0 % 9)) >> (2 * (lane & 3));
    const unsigned long long mk1 = (MB << (r1 % 9)) >> (2 * (lane & 3));
    const float cs = 0.07216878364870322f * 1.4426950408889634f;
    float mx0 = -INFINITY, mx1 = -INFINITY;
#pragma unroll
    for (int j = 0; j < 8; j++) {
#pragma unroll
      for (int e = 0; e < 2; e++) {
        bool v0 = (mk0 >> (8 * j + e)) & 1, v1 = (mk1 >> (8 * j + e)) & 1;
        acc0[4 * j + e] = v0 ? acc0[4 * j + e] * cs : -INFINITY;
        acc0[4 * j + 2 + e] = v1 ? acc0[4 * j + 2 + e] * cs : -INFINITY;
        mx0 = fmaxf(mx0, acc0[4 * j + e]);
        mx1 = fmaxf(mx1, acc0[4 * j + 2 + e]);
      }
    }
    mx0 = fmaxf(mx0, __shfl_xor_sync(0xffffffffu, mx0, 1)); mx0 = fmaxf(mx0, __shfl_xor_sync(0xffffffffu, mx0, 2));
    mx1 = fmaxf(mx1, __shfl_xor_sync(0xffffffffu, mx1, 1)); mx1 = fmaxf(mx1, __shfl_xor_sync(0xffffffffu, mx1, 2));
    float l0 = 0.f, l1 = 0.f;
#pragma unroll
    for (int j = 0; j < 8; j++) {
#pragma unroll
      for (int e = 0; e < 2; e++) {
        acc0[4 * j + e] = ex2(acc0[4 * j + e] - mx0); l0 += acc0[4 * j + e];
        acc0[4 * j + 2 + e] = ex2(acc0[4 * j + 2 + e] - mx1); l1 += acc0[4 * j + 2 + e];
      }
    }
    l0 += __shfl_xor_sync(0xffffffffu, l0, 1); l0 += __shfl_xor_sync(0xffffffffu, l0, 2);
    l1 += __shfl_xor_sync(0xffffffffu, l1, 1); l1 += __shfl_xor_sync(0xffffffffu, l1, 2);
    const float i0 = 1.f / l0, i1 = 1.f / l1;
#pragma unroll
    for (int j = 0; j < 8; j++) {
      acc0[4 * j] *= i0; acc0[4 * j + 1] *= i0; acc0[4 * j + 2] *= i1; acc0[4 * j + 3] *= i1;
    }
    cvt_frags(pf, acc0);
  }
  TS(0, 5);
  {
    float oacc[96];
    const uint64_t vd = mk_desc_o(vb, 8192, 1024);
    wg_fence();
#pragma unroll
    for (int kk = 0; kk < 4; kk++) wgmma_n192_rs<1>(oacc, pf[kk], vd + kk * 128, kk > 0);
    wg_commit();
    wg_wait<0>(); reg_fence(oacc);
    TS(0, 6);
#pragma unroll
    for (int c = 0; c < 3; c++) resid_chunk(&h[4 * c], &oacc[32 * c], 1.f, 1.f, xs + c * 8192, fa);
  }
  TS(0, 7);
  layernorm_frags(h);
  named_bar(barid, 128);
#pragma unroll
  for (int k = 0; k < 12; k++) stsm_x4(fa.at(kb + (k >> 2) * 8192, k & 3), h[k]);
  TS(0, 8);
  a_issue(acc0, h, sb, 6);
  fence_proxy_async();
  named_bar(barid, 128);
  if (elected) {
    for (int c = 0; c < 3; c++) tma_store_3d(&tm_x1, xs + c * 8192, c * 64, n0, 0);
    for (int c = 0; c < 3; c++) tma_store_3d(&tm_qkv, kb + c * 8192, 192 + c * 64, n0, 0);
    bulk_commit();
  }
  a_issue(acc1, h, sb, 7); wg_wait<1>(); reg_fence(acc0); a_release(sb, 6, lane); store_chunk(acc0, vb, fa);
  a_issue(acc0, h, sb, 8); wg_wait<1>(); reg_fence(acc1); a_release(sb, 7, lane); store_chunk(acc1, vb + 8192, fa);
  a_issue(acc1, h, sb, 9); wg_wait<1>(); reg_fence(acc0); a_release(sb, 8, lane); store_chunk(acc0, vb + 16384, fa);
  fence_proxy_async();
  if (elected) bulk_wait_read0();
  named_bar(barid, 128);
  if (elected) {
    for (int c = 0; c < 3; c++) tma_store_3d(&tm_qkv, vb + c * 8192, c * 64, n0, 0);
    bulk_commit();
  }
  a_issue(acc0, h, sb, 10); wg_wait<1>(); reg_fence(acc1); store_chunk(acc1, xs, fa);
  a_issue(acc1, h, sb, 11); wg_wait<1>(); reg_fence(acc0); store_chunk(acc0, xs + 8192, fa);
  wg_wait<0>(); reg_fence(acc1); store_chunk(acc1, xs + 16384, fa);
  fence_proxy_async();
  named_bar(barid, 128);
  TS(0, 9);
  if (elected) {
    for (int c = 0; c < 3; c++) tma_store_3d(&tm_qkv, xs + c * 8192, 384 + c * 64, n0, 0);
    bulk_commit();
    bulk_wait0();
  }
  TS(0, 10);
}

constexpr int B_GRID = 132;
constexpr int B_SLOT = 55296;
constexpr int B_Q = 0;
constexpr int B_KV = 49152;
constexpr int B_BAR = B_KV + 3 * B_SLOT;
constexpr int B_SMEM = B_BAR + 256 + 1024;

__device__ __forceinline__ void bar_arrive(int id, int nthreads) {
  asm volatile("bar.arrive %0, %1;" ::"r"(id), "r"(nthreads) : "memory");
}

__global__ void __launch_bounds__(384, 1)
kernelB(const __grid_constant__ CUtensorMap tm_q, const __grid_constant__ CUtensorMap tm_kv,
        const __grid_constant__ CUtensorMap tm_x1, const __grid_constant__ CUtensorMap tm_out) {
  extern __shared__ uint8_t smem_raw[];
  const uint32_t sb = (smem_u32(smem_raw) + 1023) & ~1023u;
  const int tid = threadIdx.x, warp = tid >> 5, lane = tid & 31;
  const uint32_t bF = sb + B_BAR, bE = sb + B_BAR + 32, bQF = sb + B_BAR + 64, bQE = sb + B_BAR + 72;
  if (tid == 0) {
    for (int i = 0; i < 3; i++) { mbar_init(bF + i * 8, 1); mbar_init(bE + i * 8, 8); }
    mbar_init(bQF, 1); mbar_init(bQE, 8);
    asm volatile("fence.mbarrier_init.release.cluster;" ::: "memory");
  }
  __syncthreads();
  const int grp = blockIdx.x / 12, ci = blockIdx.x - grp * 12;
  const bool owner = ci < 7;
  int nseg, seg_tile[2], seg_k0[2], seg_k1[2];
  if (owner) {
    nseg = 1; seg_tile[0] = grp * 7 + ci; seg_k0[0] = 3; seg_k1[0] = 9;
    seg_tile[1] = 0; seg_k0[1] = 0; seg_k1[1] = 0;
  } else {
    const int hh = ci - 7;
    nseg = 2;
    seg_tile[0] = grp * 7 + ((0x54210 >> (4 * hh)) & 15); seg_k0[0] = (0x10210 >> (4 * hh)) & 15; seg_k1[0] = 3;
    seg_tile[1] = seg_tile[0] + 1; seg_k0[1] = 0; seg_k1[1] = (0x31321 >> (4 * hh)) & 15;
  }

  if (warp >= 8) {
    asm volatile("setmaxnreg.dec.sync.aligned.u32 24;");
    if (warp == 8 && lane == 0) {
      if (blockIdx.x == 0) { g_wflag[0] = 0; g_wflag[1] = 0; g_wflag[2] = 0; g_wflag[3] = 0; }
      int it = 0;
      for (int sg = 0; sg < nseg; sg++) {
        const int tile = sg ? seg_tile[1] : seg_tile[0];
        const int k0 = sg ? seg_k0[1] : seg_k0[0], k1 = sg ? seg_k1[1] : seg_k1[0];
        const int t = tile / 11, qt = tile - t * 11;
        if (sg > 0) mbar_wait(bQE, 0);
        mbar_expect_tx(bQF, 49152);
        for (int c = 0; c < 3; c++) tma_load_3d(sb + B_Q + c * 16384, &tm_q, bQF, c * 64, qt * 128, t);
        const int n = k1 - k0;
        for (int e = 0; e < 2 * n; e++) {
          int isv, kbi;
          if (e == 0) { isv = 0; kbi = 0; }
          else if (e == 2 * n - 1) { isv = 1; kbi = n - 1; }
          else { isv = (e & 1) ^ 1; kbi = isv ? (e >> 1) - 1 : (e + 1) >> 1; }
          const int sl = it % 3;
          if (it >= 3) mbar_wait(bE + sl * 8, ((it / 3) - 1) & 1);
          mbar_expect_tx(bF + sl * 8, B_SLOT);
          for (int c = 0; c < 3; c++)
            tma_load_3d(sb + B_KV + sl * B_SLOT + c * 18432, &tm_kv, bF + sl * 8, 192 + isv * 192 + c * 64, (k0 + kbi) * 144, t);
          it++;
        }
      }
      if (owner) {
        const int t = seg_tile[0] / 11, qt = seg_tile[0] - t * 11;
        mbar_wait(bQE, 0);
        mbar_expect_tx(bQF, 49152);
        for (int c = 0; c < 3; c++) tma_load_3d(sb + B_Q + c * 16384, &tm_x1, bQF, c * 64, qt * 128, t);
      }
    }
    return;
  }

  asm volatile("setmaxnreg.inc.sync.aligned.u32 240;");
  const int wg = warp >> 2, wq = warp & 3;
  const int wtid = tid & 127;
  const float cs = 0.07216878364870322f * 1.4426950408889634f;
  float oacc[96], sacc[72];
  uint32_t pf[9][4];
  float m0, m1, l0, l1;
  int it = 0;
  const uint32_t qb = sb + B_Q + wg * 8192;
  if (wg == 1) bar_arrive(3, 256);
  TS(1, 0);
  int tsi = 1;

  auto issue_qk = [&](int slot) {
    const uint64_t kd = mk_desc_o(sb + B_KV + slot * B_SLOT, 16, 1024);
    const uint64_t qd = mk_desc_o(qb, 16, 1024);
#pragma unroll
    for (int kk = 0; kk < 12; kk++)
      wgmma_n144_ss<0>(sacc, qd + (kk >> 2) * 1024 + (kk & 3) * 2, kd + (kk >> 2) * 1152 + (kk & 3) * 2, kk > 0);
    wg_commit();
  };
  auto issue_pv = [&](int slot, int accum) {
    const uint64_t vd = mk_desc_o(sb + B_KV + slot * B_SLOT, 18432, 1024);
#pragma unroll
    for (int kk = 0; kk < 9; kk++) wgmma_n192_rs<1>(oacc, pf[kk], vd + kk * 128, kk > 0 ? 1 : accum);
    wg_commit();
  };
  auto softmax1 = [&](float& a0, float& a1) {
    float mx0 = m0, mx1 = m1;
#pragma unroll
    for (int j = 0; j < 18; j++) {
      mx0 = fmaxf(mx0, fmaxf(sacc[4 * j], sacc[4 * j + 1]));
      mx1 = fmaxf(mx1, fmaxf(sacc[4 * j + 2], sacc[4 * j + 3]));
    }
    mx0 = fmaxf(mx0, __shfl_xor_sync(0xffffffffu, mx0, 1)); mx0 = fmaxf(mx0, __shfl_xor_sync(0xffffffffu, mx0, 2));
    mx1 = fmaxf(mx1, __shfl_xor_sync(0xffffffffu, mx1, 1)); mx1 = fmaxf(mx1, __shfl_xor_sync(0xffffffffu, mx1, 2));
    a0 = ex2((m0 - mx0) * cs); a1 = ex2((m1 - mx1) * cs);
    m0 = mx0; m1 = mx1;
    const float mc0 = mx0 * cs, mc1 = mx1 * cs;
    float rs0 = 0.f, rs1 = 0.f;
#pragma unroll
    for (int j = 0; j < 18; j++) {
      sacc[4 * j] = ex2(fmaf(sacc[4 * j], cs, -mc0)); sacc[4 * j + 1] = ex2(fmaf(sacc[4 * j + 1], cs, -mc0));
      sacc[4 * j + 2] = ex2(fmaf(sacc[4 * j + 2], cs, -mc1)); sacc[4 * j + 3] = ex2(fmaf(sacc[4 * j + 3], cs, -mc1));
      rs0 += sacc[4 * j] + sacc[4 * j + 1];
      rs1 += sacc[4 * j + 2] + sacc[4 * j + 3];
    }
    l0 = l0 * a0 + rs0; l1 = l1 * a1 + rs1;
  };
  auto cvt_p = [&]() {
#pragma unroll
    for (int k = 0; k < 9; k++) {
      pf[k][0] = pack_bf16(sacc[8 * k + 0], sacc[8 * k + 1]); pf[k][1] = pack_bf16(sacc[8 * k + 2], sacc[8 * k + 3]);
      pf[k][2] = pack_bf16(sacc[8 * k + 4], sacc[8 * k + 5]); pf[k][3] = pack_bf16(sacc[8 * k + 6], sacc[8 * k + 7]);
    }
  };

  for (int sg = 0; sg < nseg; sg++) {
    const int n = sg ? (seg_k1[1] - seg_k0[1]) : (seg_k1[0] - seg_k0[0]);
    m0 = m1 = -INFINITY; l0 = l1 = 0.f;
    mbar_wait(bQF, sg & 1);
    {
      const int sl = it % 3;
      mbar_wait(bF + sl * 8, (it / 3) & 1);
      named_bar(3 + wg, 256);
      wg_fence();
      issue_qk(sl);
      bar_arrive(3 + (wg ^ 1), 256);
      wg_wait<0>(); reg_fence(sacc);
      if (lane == 0) { mbar_arrive(bE + sl * 8); if (n == 1) mbar_arrive(bQE); }
      it++;
      float a0, a1;
      softmax1(a0, a1);
      cvt_p();
    }
    TS(1, tsi); tsi++;
    for (int j = 1; j < n; j++) {
      const int slk = it % 3, slv = (it + 1) % 3;
      mbar_wait(bF + slk * 8, (it / 3) & 1);
      mbar_wait(bF + slv * 8, ((it + 1) / 3) & 1);
      named_bar(3 + wg, 256);
      wg_fence();
      issue_qk(slk);
      issue_pv(slv, j > 1);
      bar_arrive(3 + (wg ^ 1), 256);
      wg_wait<1>(); reg_fence(sacc);
      if (lane == 0) { mbar_arrive(bE + slk * 8); if (j == n - 1) mbar_arrive(bQE); }
      float a0, a1;
      softmax1(a0, a1);
      wg_wait<0>(); reg_fence(oacc);
      if (lane == 0) mbar_arrive(bE + slv * 8);
      it += 2;
#pragma unroll
      for (int i = 0; i < 24; i++) {
        oacc[4 * i] *= a0; oacc[4 * i + 1] *= a0; oacc[4 * i + 2] *= a1; oacc[4 * i + 3] *= a1;
      }
      cvt_p();
      TS(1, tsi); tsi++;
    }
    {
      const int sl = it % 3;
      mbar_wait(bF + sl * 8, (it / 3) & 1);
      named_bar(3 + wg, 256);
      wg_fence();
      issue_pv(sl, n > 1);
      if (!(wg == 1 && sg == nseg - 1)) bar_arrive(3 + (wg ^ 1), 256);
      wg_wait<0>(); reg_fence(oacc);
      if (lane == 0) mbar_arrive(bE + sl * 8);
      it++;
    }
    TS(1, tsi); tsi++;
    if (!owner) {
      const int slot = (grp * 5 + (ci - 7)) * 2 + sg;
      float4* dst = g_part + (size_t)(slot * 2 + wg) * 25 * 128 + wtid;
#pragma unroll
      for (int i = 0; i < 24; i++) dst[i * 128] = make_float4(oacc[4 * i], oacc[4 * i + 1], oacc[4 * i + 2], oacc[4 * i + 3]);
      dst[24 * 128] = make_float4(m0, m1, l0, l1);
      __threadfence();
      named_bar(1 + wg, 128);
      if (wtid == 0) atomicAdd(&g_flag[slot], 1u);
      TS(1, tsi); tsi++;
    }
  }
  if (!owner) return;

  {
    const int first = (0x9765310 >> (4 * ci)) & 15, cnt = (0x1211221 >> (4 * ci)) & 15;
    for (int q = 0; q < cnt; q++) {
      const int slot = grp * 10 + first + q;
      if (wtid == 0) {
        uint32_t n = 0, v;
        do {
          asm volatile("ld.acquire.gpu.global.u32 %0, [%1];" : "=r"(v) : "l"(&g_flag[slot]) : "memory");
        } while (v < 2u && ++n < (1u << 22));
      }
      named_bar(1 + wg, 128);
      const float4* src = g_part + (size_t)(slot * 2 + wg) * 25 * 128 + wtid;
      const float4 ml = __ldcg(src + 24 * 128);
      const float mx0 = fmaxf(m0, ml.x), mx1 = fmaxf(m1, ml.y);
      const float a0 = ex2((m0 - mx0) * cs), a1 = ex2((m1 - mx1) * cs);
      const float b0 = ex2((ml.x - mx0) * cs), b1 = ex2((ml.y - mx1) * cs);
      m0 = mx0; m1 = mx1;
      l0 = l0 * a0 + ml.z * b0; l1 = l1 * a1 + ml.w * b1;
#pragma unroll
      for (int i = 0; i < 24; i++) {
        const float4 v = __ldcg(src + i * 128);
        oacc[4 * i] = oacc[4 * i] * a0 + v.x * b0; oacc[4 * i + 1] = oacc[4 * i + 1] * a0 + v.y * b0;
        oacc[4 * i + 2] = oacc[4 * i + 2] * a1 + v.z * b1; oacc[4 * i + 3] = oacc[4 * i + 3] * a1 + v.w * b1;
      }
    }
  }
  TS(1, 21);
  l0 += __shfl_xor_sync(0xffffffffu, l0, 1); l0 += __shfl_xor_sync(0xffffffffu, l0, 2);
  l1 += __shfl_xor_sync(0xffffffffu, l1, 1); l1 += __shfl_xor_sync(0xffffffffu, l1, 2);
  const float i0 = 1.f / l0, i1 = 1.f / l1;
  mbar_wait(bQF, 1);
  const FragAddr fa(wq, lane);
#pragma unroll
  for (int c = 0; c < 3; c++) resid_chunk(nullptr, &oacc[32 * c], i0, i1, qb + c * 16384, fa);
  fence_proxy_async();
  named_bar(1 + wg, 128);
  TS(1, 22);
  if (wtid == 0) {
    const int t = seg_tile[0] / 11, qt = seg_tile[0] - t * 11;
    if (qt * 128 + wg * 64 < NL) {
      for (int c = 0; c < 3; c++) tma_store_3d(&tm_out, qb + c * 16384, c * 64, qt * 128 + wg * 64, t);
      bulk_commit();
      bulk_wait0();
    }
  }
  TS(1, 23);
}

typedef CUresult (*EncodeFn)(CUtensorMap*, CUtensorMapDataType, cuuint32_t, void*, const cuuint64_t*, const cuuint64_t*,
                             const cuuint32_t*, const cuuint32_t*, CUtensorMapInterleave, CUtensorMapSwizzle,
                             CUtensorMapL2promotion, CUtensorMapFloatOOBfill);

void make_map(EncodeFn enc, CUtensorMap* m, const void* ptr, int rank, const uint64_t* dims, const uint32_t* box) {
  cuuint64_t gd[3], gs[2];
  cuuint32_t bx[3], es[3] = {1, 1, 1};
  uint64_t stride = 2;
  for (int i = 0; i < rank; i++) {
    gd[i] = dims[i]; bx[i] = box[i];
    stride *= dims[i];
    if (i < rank - 1) gs[i] = stride;
  }
  enc(m, CU_TENSOR_MAP_DATA_TYPE_BFLOAT16, rank, const_cast<void*>(ptr), gd, gs, bx, es, CU_TENSOR_MAP_INTERLEAVE_NONE,
      CU_TENSOR_MAP_SWIZZLE_128B, CU_TENSOR_MAP_L2_PROMOTION_L2_256B, CU_TENSOR_MAP_FLOAT_OOB_FILL_NONE);
}

}

extern "C" void kernel_launch(void* const* d_in, const int* in_sizes, int n_in, void* d_out, int out_size) {
  (void)in_sizes; (void)n_in; (void)out_size;
  EncodeFn enc = nullptr;
  cudaDriverEntryPointQueryResult qres;
  cudaGetDriverEntryPoint("cuTensorMapEncodeTiled", (void**)&enc, cudaEnableDefault, &qres);
  void *p_x1, *p_qkv, *p_wf;
  cudaGetSymbolAddress(&p_wf, g_wf);
  cudaGetSymbolAddress(&p_x1, g_x1);
  cudaGetSymbolAddress(&p_qkv, g_qkv);
  cudaFuncSetAttribute(kernelA, cudaFuncAttributeMaxDynamicSharedMemorySize, A_SMEM);
  cudaFuncSetAttribute(kernelB, cudaFuncAttributeMaxDynamicSharedMemorySize, B_SMEM);

  CUtensorMap tm_x, tm_wqkvt, tm_wot, tm_wqkvs, tm_x1s, tm_qkvs, tm_q, tm_kv, tm_wos, tm_x1l, tm_out, tm_wf;
  const uint64_t d_act[3] = {192, 1296, 7}, d_qkv[3] = {576, 1296, 7}, d_w3[2] = {576, 192}, d_w1[2] = {192, 192}, d_wf[2] = {384, 384};
  const uint32_t b_a[3] = {64, 9, 7}, b_w[2] = {64, 192}, b_q[3] = {64, 128, 1}, b_kv[3] = {64, 144, 1}, b_o[3] = {64, 64, 1};
  make_map(enc, &tm_x, d_in[0], 3, d_act, b_a);
  make_map(enc, &tm_wqkvt, d_in[1], 2, d_w3, b_w);
  make_map(enc, &tm_wot, d_in[2], 2, d_w1, b_w);
  make_map(enc, &tm_wqkvs, d_in[3], 2, d_w3, b_w);
  make_map(enc, &tm_wos, d_in[4], 2, d_w1, b_w);
  make_map(enc, &tm_wf, p_wf, 2, d_wf, b_w);
  make_map(enc, &tm_x1s, p_x1, 3, d_act, b_a);
  make_map(enc, &tm_qkvs, p_qkv, 3, d_qkv, b_a);
  make_map(enc, &tm_q, p_qkv, 3, d_qkv, b_q);
  make_map(enc, &tm_kv, p_qkv, 3, d_qkv, b_kv);
  make_map(enc, &tm_x1l, p_x1, 3, d_act, b_q);
  make_map(enc, &tm_out, d_out, 3, d_act, b_o);

  kernelA<<<72 + A_FOLD, 384, A_SMEM>>>(tm_x, tm_wqkvt, tm_wot, tm_wqkvs, tm_wos, tm_wf, tm_x1s, tm_qkvs);
  kernelB<<<B_GRID, 384, B_SMEM>>>(tm_q, tm_kv, tm_x1l, tm_out);
}
```

```cpp
#include <cuda_runtime.h>
#include <cuda_bf16.h>
#include <cuda.h>
#include <stdint.h>

namespace {

constexpr int TT = 7, NL = 1296, CC = 192;

__device__ __align__(1024) __nv_bfloat16 g_x1[TT * NL * CC];
__device__ __align__(1024) __nv_bfloat16 g_qkv[TT * NL * 3 * CC];
__device__ __align__(1024) __nv_bfloat16 g_wf[2 * CC * 2 * CC];
__device__ __align__(1024) float4 g_part[110 * 2 * 25 * 128];
__device__ unsigned int g_flag[128];
__device__ unsigned int g_wflag[4];

#define TS(k, i)

__device__ __forceinline__ uint32_t smem_u32(const void* p) { return (uint32_t)__cvta_generic_to_shared(p); }
__device__ __forceinline__ void mbar_init(uint32_t bar, uint32_t cnt) {
  asm volatile("mbarrier.init.shared::cta.b64 [%0], %1;" ::"r"(bar), "r"(cnt));
}
__device__ __forceinline__ void mbar_expect_tx(uint32_t bar, uint32_t bytes) {
  asm volatile("mbarrier.arrive.expect_tx.shared::cta.b64 _, [%0], %1;" ::"r"(bar), "r"(bytes) : "memory");
}
__device__ __forceinline__ void mbar_arrive(uint32_t bar) {
  asm volatile("mbarrier.arrive.shared::cta.b64 _, [%0];" ::"r"(bar) : "memory");
}
__device__ __forceinline__ bool mbar_try(uint32_t bar, uint32_t parity) {
  uint32_t ok;
  asm volatile("{\n.reg .pred p;\nmbarrier.try_wait.parity.shared::cta.b64 p, [%1], %2;\nselp.u32 %0, 1, 0, p;\n}"
               : "=r"(ok) : "r"(bar), "r"(parity) : "memory");
  return ok != 0;
}
__device__ __forceinline__ void mbar_wait(uint32_t bar, uint32_t parity) {
  if (mbar_try(bar, parity)) return;
  uint32_t n = 0;
  while (!mbar_try(bar, parity)) {
    if (++n > (1u << 22)) break;
  }
}
__device__ __forceinline__ void tma_load_2d(uint32_t dst, const CUtensorMap* m, uint32_t bar, int c0, int c1) {
  asm volatile("cp.async.bulk.tensor.2d.shared::cluster.global.mbarrier::complete_tx::bytes [%0], [%1, {%3, %4}], [%2];"
               ::"r"(dst), "l"(m), "r"(bar), "r"(c0), "r"(c1) : "memory");
}
__device__ __forceinline__ void tma_load_3d(uint32_t dst, const CUtensorMap* m, uint32_t bar, int c0, int c1, int c2) {
  asm volatile("cp.async.bulk.tensor.3d.shared::cluster.global.mbarrier::complete_tx::bytes [%0], [%1, {%3, %4, %5}], [%2];"
               ::"r"(dst), "l"(m), "r"(bar), "r"(c0), "r"(c1), "r"(c2) : "memory");
}
__device__ __forceinline__ void tma_store_3d(const CUtensorMap* m, uint32_t src, int c0, int c1, int c2) {
  asm volatile("cp.async.bulk.tensor.3d.global.shared::cta.bulk_group [%0, {%2, %3, %4}], [%1];"
               ::"l"(m), "r"(src), "r"(c0), "r"(c1), "r"(c2) : "memory");
}
__device__ __forceinline__ void bulk_commit() { asm volatile("cp.async.bulk.commit_group;" ::: "memory"); }
__device__ __forceinline__ void bulk_wait_read0() { asm volatile("cp.async.bulk.wait_group.read 0;" ::: "memory"); }
__device__ __forceinline__ void bulk_wait0() { asm volatile("cp.async.bulk.wait_group 0;" ::: "memory"); }
__device__ __forceinline__ void fence_proxy_async() { asm volatile("fence.proxy.async.shared::cta;" ::: "memory"); }
__device__ __forceinline__ void prefetch_tmap(const CUtensorMap* m) {
  asm volatile("prefetch.tensormap [%0];" ::"l"(m) : "memory");
}
__device__ __forceinline__ void wg_fence() { asm volatile("wgmma.fence.sync.aligned;" ::: "memory"); }
__device__ __forceinline__ void wg_commit() { asm volatile("wgmma.commit_group.sync.aligned;" ::: "memory"); }
template <int N> __device__ __forceinline__ void wg_wait() { asm volatile("wgmma.wait_group.sync.aligned %0;" ::"n"(N) : "memory"); }
__device__ __forceinline__ void named_bar(int id, int nthreads) {
  asm volatile("bar.sync %0, %1;" ::"r"(id), "r"(nthreads) : "memory");
}
__device__ __forceinline__ void ldsm_x4(uint32_t (&r)[4], uint32_t addr) {
  asm volatile("ldmatrix.sync.aligned.m8n8.x4.shared.b16 {%0,%1,%2,%3}, [%4];"
               : "=r"(r[0]), "=r"(r[1]), "=r"(r[2]), "=r"(r[3]) : "r"(addr) : "memory");
}
__device__ __forceinline__ void stsm_x4(uint32_t addr, const uint32_t (&r)[4]) {
  asm volatile("stmatrix.sync.aligned.m8n8.x4.shared.b16 [%0], {%1,%2,%3,%4};"
               ::"r"(addr), "r"(r[0]), "r"(r[1]), "r"(r[2]), "r"(r[3]) : "memory");
}
__device__ __forceinline__ uint32_t pack_bf16(float lo, float hi) {
  uint32_t r;
  asm("cvt.rn.bf16x2.f32 %0, %1, %2;" : "=r"(r) : "f"(hi), "f"(lo));
  return r;
}
__device__ __forceinline__ float bf_lo(uint32_t v) { return __uint_as_float(v << 16); }
__device__ __forceinline__ float bf_hi(uint32_t v) { return __uint_as_float(v & 0xffff0000u); }
__device__ __forceinline__ float ex2(float x) {
  float y;
  asm("ex2.approx.ftz.f32 %0, %1;" : "=f"(y) : "f"(x));
  return y;
}
__device__ __forceinline__ uint64_t mk_desc(uint32_t addr, uint32_t lbo, uint32_t sbo) {
  return (uint64_t)((addr & 0x3FFFF) >> 4) | ((uint64_t)((lbo & 0x3FFFF) >> 4) << 16) |
         ((uint64_t)((sbo & 0x3FFFF) >> 4) << 32) | (1ull << 62);
}
__device__ __forceinline__ uint64_t mk_desc_o(uint32_t addr, uint32_t lbo, uint32_t sbo) {
  asm volatile("" : "+r"(addr));
  return mk_desc(addr, lbo, sbo);
}
template <int N> __device__ __forceinline__ void reg_fence(float (&d)[N]) {
#pragma unroll
  for (int i = 0; i < N; i++) asm volatile("" : "+f"(d[i])::"memory");
}

template<int TB> __device__ __forceinline__ void wgmma_n144_ss(float (&d)[72], uint64_t da, uint64_t db, int sc) {
  asm volatile("{\n.reg .pred p;\nsetp.ne.b32 p, %74, 0;\n"
    "wgmma.mma_async.sync.aligned.m64n144k16.f32.bf16.bf16 {%0, %1, %2, %3, %4, %5, %6, %7, %8, %9, %10, %11, %12, %13, %14, %15, %16, %17, %18, %19, %20, %21, %22, %23, %24, %25, %26, %27, %28, %29, %30, %31, %32, %33, %34, %35, %36, %37, %38, %39, %40, %41, %42, %43, %44, %45, %46, %47, %48, %49, %50, %51, %52, %53, %54, %55, %56, %57, %58, %59, %60, %61, %62, %63, %64, %65, %66, %67, %68, %69, %70, %71}, %72, %73, p, 1, 1, 0, %75;\n}\n"
    : "+f"(d[0]), "+f"(d[1]), "+f"(d[2]), "+f"(d[3]), "+f"(d[4]), "+f"(d[5]), "+f"(d[6]), "+f"(d[7]), "+f"(d[8]), "+f"(d[9]), "+f"(d[10]), "+f"(d[11]), "+f"(d[12]), "+f"(d[13]), "+f"(d[14]), "+f"(d[15]), "+f"(d[16]), "+f"(d[17]), "+f"(d[18]), "+f"(d[19]), "+f"(d[20]), "+f"(d[21]), "+f"(d[22]), "+f"(d[23]), "+f"(d[24]), "+f"(d[25]), "+f"(d[26]), "+f"(d[27]), "+f"(d[28]), "+f"(d[29]), "+f"(d[30]), "+f"(d[31]), "+f"(d[32]), "+f"(d[33]), "+f"(d[34]), "+f"(d[35]), "+f"(d[36]), "+f"(d[37]), "+f"(d[38]), "+f"(d[39]), "+f"(d[40]), "+f"(d[41]), "+f"(d[42]), "+f"(d[43]), "+f"(d[44]), "+f"(d[45]), "+f"(d[46]), "+f"(d[47]), "+f"(d[48]), "+f"(d[49]), "+f"(d[50]), "+f"(d[51]), "+f"(d[52]), "+f"(d[53]), "+f"(d[54]), "+f"(d[55]), "+f"(d[56]), "+f"(d[57]), "+f"(d[58]), "+f"(d[59]), "+f"(d[60]), "+f"(d[61]), "+f"(d[62]), "+f"(d[63]), "+f"(d[64]), "+f"(d[65]), "+f"(d[66]), "+f"(d[67]), "+f"(d[68]), "+f"(d[69]), "+f"(d[70]), "+f"(d[71])
    : "l"(da), "l"(db), "r"(sc), "n"(TB));
}
template<int TB> __device__ __forceinline__ void wgmma_n192_rs(float (&d)[96], const uint32_t (&a)[4], uint64_t db, int sc) {
  asm volatile("{\n.reg .pred p;\nsetp.ne.b32 p, %101, 0;\n"
    "wgmma.mma_async.sync.aligned.m64n192k16.f32.bf16.bf16 {%0, %1, %2, %3, %4, %5, %6, %7, %8, %9, %10, %11, %12, %13, %14, %15, %16, %17, %18, %19, %20, %21, %22, %23, %24, %25, %26, %27, %28, %29, %30, %31, %32, %33, %34, %35, %36, %37, %38, %39, %40, %41, %42, %43, %44, %45, %46, %47, %48, %49, %50, %51, %52, %53, %54, %55, %56, %57, %58, %59, %60, %61, %62, %63, %64, %65, %66, %67, %68, %69, %70, %71, %72, %73, %74, %75, %76, %77, %78, %79, %80, %81, %82, %83, %84, %85, %86, %87, %88, %89, %90, %91, %92, %93, %94, %95}, {%96, %97, %98, %99}, %100, p, 1, 1, %102;\n}\n"
    : "+f"(d[0]), "+f"(d[1]), "+f"(d[2]), "+f"(d[3]), "+f"(d[4]), "+f"(d[5]), "+f"(d[6]), "+f"(d[7]), "+f"(d[8]), "+f"(d[9]), "+f"(d[10]), "+f"(d[11]), "+f"(d[12]), "+f"(d[13]), "+f"(d[14]), "+f"(d[15]), "+f"(d[16]), "+f"(d[17]), "+f"(d[18]), "+f"(d[19]), "+f"(d[20]), "+f"(d[21]), "+f"(d[22]), "+f"(d[23]), "+f"(d[24]), "+f"(d[25]), "+f"(d[26]), "+f"(d[27]), "+f"(d[28]), "+f"(d[29]), "+f"(d[30]), "+f"(d[31]), "+f"(d[32]), "+f"(d[33]), "+f"(d[34]), "+f"(d[35]), "+f"(d[36]), "+f"(d[37]), "+f"(d[38]), "+f"(d[39]), "+f"(d[40]), "+f"(d[41]), "+f"(d[42]), "+f"(d[43]), "+f"(d[44]), "+f"(d[45]), "+f"(d[46]), "+f"(d[47]), "+f"(d[48]), "+f"(d[49]), "+f"(d[50]), "+f"(d[51]), "+f"(d[52]), "+f"(d[53]), "+f"(d[54]), "+f"(d[55]), "+f"(d[56]), "+f"(d[57]), "+f"(d[58]), "+f"(d[59]), "+f"(d[60]), "+f"(d[61]), "+f"(d[62]), "+f"(d[63]), "+f"(d[64]), "+f"(d[65]), "+f"(d[66]), "+f"(d[67]), "+f"(d[68]), "+f"(d[69]), "+f"(d[70]), "+f"(d[71]), "+f"(d[72]), "+f"(d[73]), "+f"(d[74]), "+f"(d[75]), "+f"(d[76]), "+f"(d[77]), "+f"(d[78]), "+f"(d[79]), "+f"(d[80]), "+f"(d[81]), "+f"(d[82]), "+f"(d[83]), "+f"(d[84]), "+f"(d[85]), "+f"(d[86]), "+f"(d[87]), "+f"(d[88]), "+f"(d[89]), "+f"(d[90]), "+f"(d[91]), "+f"(d[92]), "+f"(d[93]), "+f"(d[94]), "+f"(d[95])
    : "r"(a[0]), "r"(a[1]), "r"(a[2]), "r"(a[3]), "l"(db), "r"(sc), "n"(TB));
}
template<int TB> __device__ __forceinline__ void wgmma_n64_rs(float (&d)[32], const uint32_t (&a)[4], uint64_t db, int sc) {
  asm volatile("{\n.reg .pred p;\nsetp.ne.b32 p, %37, 0;\n"
    "wgmma.mma_async.sync.aligned.m64n64k16.f32.bf16.bf16 {%0, %1, %2, %3, %4, %5, %6, %7, %8, %9, %10, %11, %12, %13, %14, %15, %16, %17, %18, %19, %20, %21, %22, %23, %24, %25, %26, %27, %28, %29, %30, %31}, {%32, %33, %34, %35}, %36, p, 1, 1, %38;\n}\n"
    : "+f"(d[0]), "+f"(d[1]), "+f"(d[2]), "+f"(d[3]), "+f"(d[4]), "+f"(d[5]), "+f"(d[6]), "+f"(d[7]), "+f"(d[8]), "+f"(d[9]), "+f"(d[10]), "+f"(d[11]), "+f"(d[12]), "+f"(d[13]), "+f"(d[14]), "+f"(d[15]), "+f"(d[16]), "+f"(d[17]), "+f"(d[18]), "+f"(d[19]), "+f"(d[20]), "+f"(d[21]), "+f"(d[22]), "+f"(d[23]), "+f"(d[24]), "+f"(d[25]), "+f"(d[26]), "+f"(d[27]), "+f"(d[28]), "+f"(d[29]), "+f"(d[30]), "+f"(d[31])
    : "r"(a[0]), "r"(a[1]), "r"(a[2]), "r"(a[3]), "l"(db), "r"(sc), "n"(TB));
}
template<int TB> __device__ __forceinline__ void wgmma_n64_ss(float (&d)[32], uint64_t da, uint64_t db, int sc) {
  asm volatile("{\n.reg .pred p;\nsetp.ne.b32 p, %34, 0;\n"
    "wgmma.mma_async.sync.aligned.m64n64k16.f32.bf16.bf16 {%0, %1, %2, %3, %4, %5, %6, %7, %8, %9, %10, %11, %12, %13, %14, %15, %16, %17, %18, %19, %20, %21, %22, %23, %24, %25, %26, %27, %28, %29, %30, %31}, %32, %33, p, 1, 1, 0, %35;\n}\n"
    : "+f"(d[0]), "+f"(d[1]), "+f"(d[2]), "+f"(d[3]), "+f"(d[4]), "+f"(d[5]), "+f"(d[6]), "+f"(d[7]), "+f"(d[8]), "+f"(d[9]), "+f"(d[10]), "+f"(d[11]), "+f"(d[12]), "+f"(d[13]), "+f"(d[14]), "+f"(d[15]), "+f"(d[16]), "+f"(d[17]), "+f"(d[18]), "+f"(d[19]), "+f"(d[20]), "+f"(d[21]), "+f"(d[22]), "+f"(d[23]), "+f"(d[24]), "+f"(d[25]), "+f"(d[26]), "+f"(d[27]), "+f"(d[28]), "+f"(d[29]), "+f"(d[30]), "+f"(d[31])
    : "l"(da), "l"(db), "r"(sc), "n"(TB));
}

struct FragAddr {
  uint32_t rowoff;
  uint32_t rx;
  uint32_t hi;
  __device__ __forceinline__ FragAddr(int warp_in_wg, int lane) {
    int row = 16 * warp_in_wg + (lane & 7) + ((lane >> 3) & 1) * 8;
    rowoff = row * 128;
    rx = row & 7;
    hi = lane >> 4;
  }
  __device__ __forceinline__ uint32_t at(uint32_t chunk_base, int kk4) const {
    return chunk_base + rowoff + ((((uint32_t)kk4 * 2 + hi) ^ rx) << 4);
  }
};

__device__ __forceinline__ void layernorm_frags(uint32_t (&f)[12][4]) {
  float s0 = 0.f, s1 = 0.f;
#pragma unroll
  for (int k = 0; k < 12; k++) {
    s0 += bf_lo(f[k][0]) + bf_hi(f[k][0]) + bf_lo(f[k][2]) + bf_hi(f[k][2]);
    s1 += bf_lo(f[k][1]) + bf_hi(f[k][1]) + bf_lo(f[k][3]) + bf_hi(f[k][3]);
  }
  s0 += __shfl_xor_sync(0xffffffffu, s0, 1); s0 += __shfl_xor_sync(0xffffffffu, s0, 2);
  s1 += __shfl_xor_sync(0xffffffffu, s1, 1); s1 += __shfl_xor_sync(0xffffffffu, s1, 2);
  const float m0 = s0 * (1.f / 192.f), m1 = s1 * (1.f / 192.f);
  float v0 = 0.f, v1 = 0.f;
#pragma unroll
  for (int k = 0; k < 12; k++) {
    float a;
    a = bf_lo(f[k][0]) - m0; v0 += a * a; a = bf_hi(f[k][0]) - m0; v0 += a * a;
    a = bf_lo(f[k][2]) - m0; v0 += a * a; a = bf_hi(f[k][2]) - m0; v0 += a * a;
    a = bf_lo(f[k][1]) - m1; v1 += a * a; a = bf_hi(f[k][1]) - m1; v1 += a * a;
    a = bf_lo(f[k][3]) - m1; v1 += a * a; a = bf_hi(f[k][3]) - m1; v1 += a * a;
  }
  v0 += __shfl_xor_sync(0xffffffffu, v0, 1); v0 += __shfl_xor_sync(0xffffffffu, v0, 2);
  v1 += __shfl_xor_sync(0xffffffffu, v1, 1); v1 += __shfl_xor_sync(0xffffffffu, v1, 2);
  const float r0 = rsqrtf(v0 * (1.f / 192.f) + 1e-5f), r1 = rsqrtf(v1 * (1.f / 192.f) + 1e-5f);
#pragma unroll
  for (int k = 0; k < 12; k++) {
    f[k][0] = pack_bf16((bf_lo(f[k][0]) - m0) * r0, (bf_hi(f[k][0]) - m0) * r0);
    f[k][2] = pack_bf16((bf_lo(f[k][2]) - m0) * r0, (bf_hi(f[k][2]) - m0) * r0);
    f[k][1] = pack_bf16((bf_lo(f[k][1]) - m1) * r1, (bf_hi(f[k][1]) - m1) * r1);
    f[k][3] = pack_bf16((bf_lo(f[k][3]) - m1) * r1, (bf_hi(f[k][3]) - m1) * r1);
  }
}

constexpr int A_NST = 5;
constexpr int A_XS = 0;
constexpr int A_VB = 49152;
constexpr int A_W = 98304;
constexpr int A_BAR = A_W + A_NST * 24576;
constexpr int A_SMEM = A_BAR + 256 + 1024;
constexpr int A_FOLD = 36;

__device__ __forceinline__ void a_issue(float (&acc)[32], const uint32_t (&af)[12][4], uint32_t sb, int s) {
  const int st = s % A_NST;
  mbar_wait(sb + A_BAR + st * 8, (s / A_NST) & 1);
  const uint64_t wd = mk_desc_o(sb + A_W + st * 24576, 8192, 1024);
  wg_fence();
#pragma unroll
  for (int kk = 0; kk < 12; kk++) wgmma_n64_rs<1>(acc, af[kk], wd + kk * 128, kk > 0);
  wg_commit();
}
__device__ __forceinline__ void a_release(uint32_t sb, int s, int lane) {
  if (lane == 0) mbar_arrive(sb + A_BAR + 64 + (s % A_NST) * 8);
}
__device__ __forceinline__ void cvt_frags(uint32_t (*dst)[4], const float (&acc)[32]) {
#pragma unroll
  for (int k = 0; k < 4; k++) {
    dst[k][0] = pack_bf16(acc[8 * k + 0], acc[8 * k + 1]);
    dst[k][1] = pack_bf16(acc[8 * k + 2], acc[8 * k + 3]);
    dst[k][2] = pack_bf16(acc[8 * k + 4], acc[8 * k + 5]);
    dst[k][3] = pack_bf16(acc[8 * k + 6], acc[8 * k + 7]);
  }
}
__device__ __forceinline__ void store_chunk(const float (&acc)[32], uint32_t chunk_base, const FragAddr& fa) {
  uint32_t t[4][4];
  cvt_frags(t, acc);
#pragma unroll
  for (int k = 0; k < 4; k++) stsm_x4(fa.at(chunk_base, k), t[k]);
}
__device__ __forceinline__ void resid_chunk(uint32_t (*dst)[4], const float* acc, float s0, float s1, uint32_t chunk_base,
                                            const FragAddr& fa) {
#pragma unroll
  for (int k = 0; k < 4; k++) {
    uint32_t x[4];
    ldsm_x4(x, fa.at(chunk_base, k));
    uint32_t o[4];
    o[0] = pack_bf16(fmaf(acc[8 * k + 0], s0, bf_lo(x[0])), fmaf(acc[8 * k + 1], s0, bf_hi(x[0])));
    o[1] = pack_bf16(fmaf(acc[8 * k + 2], s1, bf_lo(x[1])), fmaf(acc[8 * k + 3], s1, bf_hi(x[1])));
    o[2] = pack_bf16(fmaf(acc[8 * k + 4], s0, bf_lo(x[2])), fmaf(acc[8 * k + 5], s0, bf_hi(x[2])));
    o[3] = pack_bf16(fmaf(acc[8 * k + 6], s1, bf_lo(x[3])), fmaf(acc[8 * k + 7], s1, bf_hi(x[3])));
    stsm_x4(fa.at(chunk_base, k), o);
    if (dst) { dst[k][0] = o[0]; dst[k][1] = o[1]; dst[k][2] = o[2]; dst[k][3] = o[3]; }
  }
}

__global__ void __launch_bounds__(384, 1)
kernelA(const __grid_constant__ CUtensorMap tm_x, const __grid_constant__ CUtensorMap tm_wq64t,
        const __grid_constant__ CUtensorMap tm_wot, const __grid_constant__ CUtensorMap tm_wq64s,
        const __grid_constant__ CUtensorMap tm_wos, const __grid_constant__ CUtensorMap tm_wf,
        const __grid_constant__ CUtensorMap tm_x1, const __grid_constant__ CUtensorMap tm_qkv) {
  extern __shared__ uint8_t smem_raw[];
  const uint32_t sb = (smem_u32(smem_raw) + 1023) & ~1023u;
  const int tid = threadIdx.x, warp = tid >> 5, lane = tid & 31;
  const bool is_fold = blockIdx.x < A_FOLD;
  const int blk = blockIdx.x - A_FOLD;
  if (tid == 256) {
    for (int i = 0; i < A_NST; i++) { mbar_init(sb + A_BAR + i * 8, 1); mbar_init(sb + A_BAR + 64 + i * 8, 8); }
    mbar_init(sb + A_BAR + 128, 1); mbar_init(sb + A_BAR + 136, 1);
    asm volatile("fence.mbarrier_init.release.cluster;" ::: "memory");
    if (!is_fold) {
      for (int w = 0; w < 2; w++) {
        const uint32_t bar = sb + A_BAR + 128 + w * 8;
        mbar_expect_tx(bar, 3 * 63 * 128);
        for (int c = 0; c < 3; c++)
          tma_load_3d(sb + A_XS + w * 24576 + c * 8192, &tm_x, bar, c * 64, (blk * 2 + w) * 9, 0);
      }
    } else {
      const int mat = blockIdx.x / 9, rs = (blockIdx.x % 9) / 3, cs = blockIdx.x % 3;
      const CUtensorMap* mq = (mat < 2) ? &tm_wq64t : &tm_wq64s;
      const CUtensorMap* mo = (mat < 2) ? &tm_wot : &tm_wos;
      const uint32_t bar = sb + A_BAR + 128;
      mbar_expect_tx(bar, 2 * 24576);
      for (int c = 0; c < 3; c++) tma_load_2d(sb + c * 8192, mq, bar, ((mat & 1) ? 384 : 0) + c * 64, rs * 64);
      if (mat & 1) tma_load_2d(sb + 24576, mo, bar, cs * 64, 0);
      else for (int c = 0; c < 3; c++) tma_load_2d(sb + 24576 + c * 8192, mq, bar, 192 + c * 64, cs * 64);
    }
  }
  if (blockIdx.x == 0 && tid < 128) g_flag[tid] = 0;
  if (!is_fold && tid < 48) {
    uint32_t a = sb + A_XS + (tid >> 3) * 8192 + 63 * 128 + (tid & 7) * 16;
    asm volatile("st.shared.v4.b32 [%0], {%1,%1,%1,%1};" ::"r"(a), "r"(0) : "memory");
  }
  __syncthreads();

  if (warp >= 8) {
    asm volatile("setmaxnreg.dec.sync.aligned.u32 24;");
    if (warp == 8 && lane == 0 && !is_fold) {
      for (int s = 0; s < 12; s++) {
        const int st = s % A_NST;
        const int g = s / 3;
        const int mat = (g == 0) ? 1 : (g == 1) ? 0 : g;
        if (s % 3 == 0) {
          uint32_t n = 0, v;
          do {
            asm volatile("ld.acquire.gpu.global.u32 %0, [%1];" : "=r"(v) : "l"(&g_wflag[mat]) : "memory");
          } while (v < 9u && ++n < (1u << 22));
          asm volatile("fence.proxy.async;" ::: "memory");
        }
        if (s >= A_NST) mbar_wait(sb + A_BAR + 64 + st * 8, ((s / A_NST) - 1) & 1);
        mbar_expect_tx(sb + A_BAR + st * 8, 24576);
        tma_load_2d(sb + A_W + st * 24576, &tm_wf, sb + A_BAR + st * 8, (mat & 1) * 192 + (s % 3) * 64, (mat >> 1) * 192);
      }
    }
    return;
  }

  asm volatile("setmaxnreg.inc.sync.aligned.u32 240;");
  const int wg = warp >> 2, wq = warp & 3;

  if (is_fold) {
    if (wg == 0) {
      const int mat = blockIdx.x / 9, rs = (blockIdx.x % 9) / 3, cs = blockIdx.x % 3;
      float d[32];
      mbar_wait(sb + A_BAR + 128, 0);
      const uint64_t ad = mk_desc_o(sb, 16, 1024);
      if (mat & 1) {
        const uint64_t bd = mk_desc_o(sb + 24576, 8192, 1024);
        wg_fence();
#pragma unroll
        for (int kk = 0; kk < 12; kk++) wgmma_n64_ss<1>(d, ad + (kk >> 2) * 512 + (kk & 3) * 2, bd + kk * 128, kk > 0);
        wg_commit();
      } else {
        const uint64_t bd = mk_desc_o(sb + 24576, 16, 1024);
        wg_fence();
#pragma unroll
        for (int kk = 0; kk < 12; kk++)
          wgmma_n64_ss<0>(d, ad + (kk >> 2) * 512 + (kk & 3) * 2, bd + (kk >> 2) * 512 + (kk & 3) * 2, kk > 0);
        wg_commit();
      }
      wg_wait<0>(); reg_fence(d);
      const int r0 = rs * 64 + wq * 16 + (lane >> 2);
      uint32_t* dst = reinterpret_cast<uint32_t*>(g_wf + ((size_t)(mat >> 1) * 192 + r0) * 384 + (mat & 1) * 192 + cs * 64 + (lane & 3) * 2);
#pragma unroll
      for (int j = 0; j < 8; j++) {
        dst[j * 4] = pack_bf16(d[4 * j], d[4 * j + 1]);
        dst[8 * 192 + j * 4] = pack_bf16(d[4 * j + 2], d[4 * j + 3]);
      }
      asm volatile("fence.proxy.async;" ::: "memory");
      __threadfence();
      named_bar(1, 128);
      if (tid == 0) atomicAdd(&g_wflag[mat], 1u);
    }
    return;
  }

  const int n0 = (blk * 2 + wg) * 9;
  const FragAddr fa(wq, lane);
  const uint32_t xs = sb + A_XS + wg * 24576, vb = sb + A_VB + wg * 24576;
  const int barid = 1 + wg;
  const bool elected = (tid & 127) == 0;

  uint32_t h[12][4];
  TS(0, 0);
  mbar_wait(sb + A_BAR + 128 + wg * 8, 0);
  TS(0, 1);
#pragma unroll
  for (int k = 0; k < 12; k++) ldsm_x4(h[k], fa.at(xs + (k >> 2) * 8192, k & 3));
  layernorm_frags(h);
#pragma unroll
  for (int k = 0; k < 12; k++) stsm_x4(fa.at(xs + (k >> 2) * 8192, k & 3), h[k]);

  float acc0[32], acc1[32];
  uint32_t qf[12][4];
  TS(0, 2);
  a_issue(acc0, h, sb, 0);
  TS(0, 3);
  a_issue(acc1, h, sb, 1); wg_wait<1>(); reg_fence(acc0); a_release(sb, 0, lane); store_chunk(acc0, vb, fa);
  a_issue(acc0, h, sb, 2); wg_wait<1>(); reg_fence(acc1); a_release(sb, 1, lane); store_chunk(acc1, vb + 8192, fa);
  a_issue(acc1, h, sb, 3); wg_wait<1>(); reg_fence(acc0); a_release(sb, 2, lane); store_chunk(acc0, vb + 16384, fa);
  fence_proxy_async();
  named_bar(barid, 128);
  a_issue(acc0, h, sb, 4); wg_wait<1>(); reg_fence(acc1); a_release(sb, 3, lane); cvt_frags(&qf[0], acc1);
  a_issue(acc1, h, sb, 5); wg_wait<1>(); reg_fence(acc0); a_release(sb, 4, lane); cvt_frags(&qf[4], acc0);
  wg_wait<0>(); reg_fence(acc1); a_release(sb, 5, lane); cvt_frags(&qf[8], acc1);
  TS(0, 4);
  {
    const uint64_t kd = mk_desc_o(xs, 16, 1024);
    wg_fence();
#pragma unroll
    for (int kk = 0; kk < 12; kk++) wgmma_n64_rs<0>(acc0, qf[kk], kd + (kk >> 2) * 512 + (kk & 3) * 2, kk > 0);
    wg_commit();
    wg_wait<0>(); reg_fence(acc0);
  }
  named_bar(barid, 128);
  if (elected) {
    const uint32_t bar = sb + A_BAR + 128 + wg * 8;
    mbar_expect_tx(bar, 3 * 63 * 128);
    for (int c = 0; c < 3; c++) tma_load_3d(xs + c * 8192, &tm_x, bar, c * 64, n0, 0);
  }
  uint32_t pf[4][4];
  {
    const int r0 = 16 * wq + (lane >> 2), r1 = r0 + 8;
    const unsigned long long MB = 0x0040201008040201ull;
    const unsigned long long mk0 = (MB << (r0 % 9)) >> (2 * (lane & 3));
    const unsigned long long mk1 = (MB << (r1 % 9)) >> (2 * (lane & 3));
    const float cs = 0.07216878364870322f * 1.4426950408889634f;
    float mx0 = -INFINITY, mx1 = -INFINITY;
#pragma unroll
    for (int j = 0; j < 8; j++) {
#pragma unroll
      for (int e = 0; e < 2; e++) {
        bool v0 = (mk0 >> (8 * j + e)) & 1, v1 = (mk1 >> (8 * j + e)) & 1;
        acc0[4 * j + e] = v0 ? acc0[4 * j + e] * cs : -INFINITY;
        acc0[4 * j + 2 + e] = v1 ? acc0[4 * j + 2 + e] * cs : -INFINITY;
        mx0 = fmaxf(mx0, acc0[4 * j + e]);
        mx1 = fmaxf(mx1, acc0[4 * j + 2 + e]);
      }
    }
    mx0 = fmaxf(mx0, __shfl_xor_sync(0xffffffffu, mx0, 1)); mx0 = fmaxf(mx0, __shfl_xor_sync(0xffffffffu, mx0, 2));
    mx1 = fmaxf(mx1, __shfl_xor_sync(0xffffffffu, mx1, 1)); mx1 = fmaxf(mx1, __shfl_xor_sync(0xffffffffu, mx1, 2));
    float l0 = 0.f, l1 = 0.f;
#pragma unroll
    for (int j = 0; j < 8; j++) {
#pragma unroll
      for (int e = 0; e < 2; e++) {
        acc0[4 * j + e] = ex2(acc0[4 * j + e] - mx0); l0 += acc0[4 * j + e];
        acc0[4 * j + 2 + e] = ex2(acc0[4 * j + 2 + e] - mx1); l1 += acc0[4 * j + 2 + e];
      }
    }
    l0 += __shfl_xor_sync(0xffffffffu, l0, 1); l0 += __shfl_xor_sync(0xffffffffu, l0, 2);
    l1 += __shfl_xor_sync(0xffffffffu, l1, 1); l1 += __shfl_xor_sync(0xffffffffu, l1, 2);
    const float i0 = 1.f / l0, i1 = 1.f / l1;
#pragma unroll
    for (int j = 0; j < 8; j++) {
      acc0[4 * j] *= i0; acc0[4 * j + 1] *= i0; acc0[4 * j + 2] *= i1; acc0[4 * j + 3] *= i1;
    }
    cvt_frags(pf, acc0);
  }
  TS(0, 5);
  {
    float oacc[96];
    const uint64_t vd = mk_desc_o(vb, 8192, 1024);
    wg_fence();
#pragma unroll
    for (int kk = 0; kk < 4; kk++) wgmma_n192_rs<1>(oacc, pf[kk], vd + kk * 128, kk > 0);
    wg_commit();
    wg_wait<0>(); reg_fence(oacc);
    TS(0, 6);
    mbar_wait(sb + A_BAR + 128 + wg * 8, 1);
#pragma unroll
    for (int c = 0; c < 3; c++) resid_chunk(&h[4 * c], &oacc[32 * c], 1.f, 1.f, xs + c * 8192, fa);
  }
  TS(0, 7);
  layernorm_frags(h);
  named_bar(barid, 128);
#pragma unroll
  for (int k = 0; k < 12; k++) stsm_x4(fa.at(vb + (k >> 2) * 8192, k & 3), h[k]);
  TS(0, 8);
  a_issue(acc0, h, sb, 6);
  fence_proxy_async();
  named_bar(barid, 128);
  if (elected) {
    for (int c = 0; c < 3; c++) tma_store_3d(&tm_x1, xs + c * 8192, c * 64, n0, 0);
    for (int c = 0; c < 3; c++) tma_store_3d(&tm_qkv, vb + c * 8192, 192 + c * 64, n0, 0);
    bulk_commit();
  }
  a_issue(acc1, h, sb, 7); wg_wait<1>(); reg_fence(acc0); a_release(sb, 6, lane);
  if (elected) bulk_wait_read0();
  named_bar(barid, 128);
  store_chunk(acc0, xs, fa);
  a_issue(acc0, h, sb, 8); wg_wait<1>(); reg_fence(acc1); store_chunk(acc1, xs + 8192, fa);
  a_issue(acc1, h, sb, 9); wg_wait<1>(); reg_fence(acc0); store_chunk(acc0, xs + 16384, fa);
  fence_proxy_async();
  named_bar(barid, 128);
  if (elected) {
    for (int c = 0; c < 3; c++) tma_store_3d(&tm_qkv, xs + c * 8192, c * 64, n0, 0);
    bulk_commit();
  }
  a_issue(acc0, h, sb, 10); wg_wait<1>(); reg_fence(acc1); store_chunk(acc1, vb, fa);
  a_issue(acc1, h, sb, 11); wg_wait<1>(); reg_fence(acc0); store_chunk(acc0, vb + 8192, fa);
  wg_wait<0>(); reg_fence(acc1); store_chunk(acc1, vb + 16384, fa);
  fence_proxy_async();
  named_bar(barid, 128);
  TS(0, 9);
  if (elected) {
    for (int c = 0; c < 3; c++) tma_store_3d(&tm_qkv, vb + c * 8192, 384 + c * 64, n0, 0);
    bulk_commit();
    bulk_wait0();
  }
  TS(0, 10);
}

constexpr int B_GRID = 132;
constexpr int B_SLOT = 55296;
constexpr int B_Q = 0;
constexpr int B_KV = 49152;
constexpr int B_BAR = B_KV + 3 * B_SLOT;
constexpr int B_SMEM = B_BAR + 256 + 1024;

__device__ __forceinline__ void bar_arrive(int id, int nthreads) {
  asm volatile("bar.arrive %0, %1;" ::"r"(id), "r"(nthreads) : "memory");
}

__global__ void __launch_bounds__(384, 1)
kernelB(const __grid_constant__ CUtensorMap tm_q, const __grid_constant__ CUtensorMap tm_kv,
        const __grid_constant__ CUtensorMap tm_x1, const __grid_constant__ CUtensorMap tm_out) {
  extern __shared__ uint8_t smem_raw[];
  const uint32_t sb = (smem_u32(smem_raw) + 1023) & ~1023u;
  const int tid = threadIdx.x, warp = tid >> 5, lane = tid & 31;
  const uint32_t bF = sb + B_BAR, bE = sb + B_BAR + 32, bQF = sb + B_BAR + 64, bQE = sb + B_BAR + 72;
  if (tid == 0) {
    for (int i = 0; i < 3; i++) { mbar_init(bF + i * 8, 1); mbar_init(bE + i * 8, 8); }
    mbar_init(bQF, 1); mbar_init(bQE, 8);
    asm volatile("fence.mbarrier_init.release.cluster;" ::: "memory");
  }
  __syncthreads();
  const int grp = blockIdx.x / 12, ci = blockIdx.x - grp * 12;
  const bool owner = ci < 7;
  int nseg, seg_tile[2], seg_k0[2], seg_k1[2];
  if (owner) {
    nseg = 1; seg_tile[0] = grp * 7 + ci; seg_k0[0] = 3; seg_k1[0] = 9;
    seg_tile[1] = 0; seg_k0[1] = 0; seg_k1[1] = 0;
  } else {
    const int hh = ci - 7;
    nseg = 2;
    seg_tile[0] = grp * 7 + ((0x54210 >> (4 * hh)) & 15); seg_k0[0] = (0x10210 >> (4 * hh)) & 15; seg_k1[0] = 3;
    seg_tile[1] = seg_tile[0] + 1; seg_k0[1] = 0; seg_k1[1] = (0x31321 >> (4 * hh)) & 15;
  }

  if (warp >= 8) {
    asm volatile("setmaxnreg.dec.sync.aligned.u32 24;");
    if (warp == 8 && lane == 0) {
      if (blockIdx.x == 0) { g_wflag[0] = 0; g_wflag[1] = 0; g_wflag[2] = 0; g_wflag[3] = 0; }
      int it = 0;
      for (int sg = 0; sg < nseg; sg++) {
        const int tile = sg ? seg_tile[1] : seg_tile[0];
        const int k0 = sg ? seg_k0[1] : seg_k0[0], k1 = sg ? seg_k1[1] : seg_k1[0];
        const int t = tile / 11, qt = tile - t * 11;
        if (sg > 0) mbar_wait(bQE, 0);
        mbar_expect_tx(bQF, 49152);
        for (int c = 0; c < 3; c++) tma_load_3d(sb + B_Q + c * 16384, &tm_q, bQF, c * 64, qt * 128, t);
        const int n = k1 - k0;
        for (int e = 0; e < 2 * n; e++) {
          int isv, kbi;
          if (e == 0) { isv = 0; kbi = 0; }
          else if (e == 2 * n - 1) { isv = 1; kbi = n - 1; }
          else { isv = (e & 1) ^ 1; kbi = isv ? (e >> 1) - 1 : (e + 1) >> 1; }
          const int sl = it % 3;
          if (it >= 3) mbar_wait(bE + sl * 8, ((it / 3) - 1) & 1);
          mbar_expect_tx(bF + sl * 8, B_SLOT);
          for (int c = 0; c < 3; c++)
            tma_load_3d(sb + B_KV + sl * B_SLOT + c * 18432, &tm_kv, bF + sl * 8, 192 + isv * 192 + c * 64, (k0 + kbi) * 144, t);
          it++;
        }
      }
      if (owner) {
        const int t = seg_tile[0] / 11, qt = seg_tile[0] - t * 11;
        mbar_wait(bQE, 0);
        mbar_expect_tx(bQF, 49152);
        for (int c = 0; c < 3; c++) tma_load_3d(sb + B_Q + c * 16384, &tm_x1, bQF, c * 64, qt * 128, t);
      }
    }
    return;
  }

  asm volatile("setmaxnreg.inc.sync.aligned.u32 240;");
  const int wg = warp >> 2, wq = warp & 3;
  const int wtid = tid & 127;
  const float cs = 0.07216878364870322f * 1.4426950408889634f;
  float oacc[96], sacc[72];
  uint32_t pf[9][4];
  float m0, m1, l0, l1;
  int it = 0;
  const uint32_t qb = sb + B_Q + wg * 8192;
  if (wg == 1) bar_arrive(3, 256);
  TS(1, 0);
  int tsi = 1;

  auto issue_qk = [&](int slot) {
    const uint64_t kd = mk_desc_o(sb + B_KV + slot * B_SLOT, 16, 1024);
    const uint64_t qd = mk_desc_o(qb, 16, 1024);
#pragma unroll
    for (int kk = 0; kk < 12; kk++)
      wgmma_n144_ss<0>(sacc, qd + (kk >> 2) * 1024 + (kk & 3) * 2, kd + (kk >> 2) * 1152 + (kk & 3) * 2, kk > 0);
    wg_commit();
  };
  auto issue_pv = [&](int slot, int accum) {
    const uint64_t vd = mk_desc_o(sb + B_KV + slot * B_SLOT, 18432, 1024);
#pragma unroll
    for (int kk = 0; kk < 9; kk++) wgmma_n192_rs<1>(oacc, pf[kk], vd + kk * 128, kk > 0 ? 1 : accum);
    wg_commit();
  };
  auto softmax1 = [&](float& a0, float& a1) {
    float mx0 = m0, mx1 = m1;
#pragma unroll
    for (int j = 0; j < 18; j++) {
      mx0 = fmaxf(mx0, fmaxf(sacc[4 * j], sacc[4 * j + 1]));
      mx1 = fmaxf(mx1, fmaxf(sacc[4 * j + 2], sacc[4 * j + 3]));
    }
    mx0 = fmaxf(mx0, __shfl_xor_sync(0xffffffffu, mx0, 1)); mx0 = fmaxf(mx0, __shfl_xor_sync(0xffffffffu, mx0, 2));
    mx1 = fmaxf(mx1, __shfl_xor_sync(0xffffffffu, mx1, 1)); mx1 = fmaxf(mx1, __shfl_xor_sync(0xffffffffu, mx1, 2));
    a0 = ex2((m0 - mx0) * cs); a1 = ex2((m1 - mx1) * cs);
    m0 = mx0; m1 = mx1;
    const float mc0 = mx0 * cs, mc1 = mx1 * cs;
    float rs0 = 0.f, rs1 = 0.f;
#pragma unroll
    for (int j = 0; j < 18; j++) {
      sacc[4 * j] = ex2(fmaf(sacc[4 * j], cs, -mc0)); sacc[4 * j + 1] = ex2(fmaf(sacc[4 * j + 1], cs, -mc0));
      sacc[4 * j + 2] = ex2(fmaf(sacc[4 * j + 2], cs, -mc1)); sacc[4 * j + 3] = ex2(fmaf(sacc[4 * j + 3], cs, -mc1));
      rs0 += sacc[4 * j] + sacc[4 * j + 1];
      rs1 += sacc[4 * j + 2] + sacc[4 * j + 3];
    }
    l0 = l0 * a0 + rs0; l1 = l1 * a1 + rs1;
  };
  auto cvt_p = [&]() {
#pragma unroll
    for (int k = 0; k < 9; k++) {
      pf[k][0] = pack_bf16(sacc[8 * k + 0], sacc[8 * k + 1]); pf[k][1] = pack_bf16(sacc[8 * k + 2], sacc[8 * k + 3]);
      pf[k][2] = pack_bf16(sacc[8 * k + 4], sacc[8 * k + 5]); pf[k][3] = pack_bf16(sacc[8 * k + 6], sacc[8 * k + 7]);
    }
  };

  for (int sg = 0; sg < nseg; sg++) {
    const int n = sg ? (seg_k1[1] - seg_k0[1]) : (seg_k1[0] - seg_k0[0]);
    m0 = m1 = -INFINITY; l0 = l1 = 0.f;
    mbar_wait(bQF, sg & 1);
    {
      const int sl = it % 3;
      mbar_wait(bF + sl * 8, (it / 3) & 1);
      named_bar(3 + wg, 256);
      wg_fence();
      issue_qk(sl);
      bar_arrive(3 + (wg ^ 1), 256);
      wg_wait<0>(); reg_fence(sacc);
      if (lane == 0) { mbar_arrive(bE + sl * 8); if (n == 1) mbar_arrive(bQE); }
      it++;
      float a0, a1;
      softmax1(a0, a1);
      cvt_p();
    }
    TS(1, tsi); tsi++;
    for (int j = 1; j < n; j++) {
      const int slk = it % 3, slv = (it + 1) % 3;
      mbar_wait(bF + slk * 8, (it / 3) & 1);
      named_bar(3 + wg, 256);
      wg_fence();
      issue_qk(slk);
      mbar_wait(bF + slv * 8, ((it + 1) / 3) & 1);
      issue_pv(slv, j > 1);
      bar_arrive(3 + (wg ^ 1), 256);
      wg_wait<1>(); reg_fence(sacc);
      if (lane == 0) { mbar_arrive(bE + slk * 8); if (j == n - 1) mbar_arrive(bQE); }
      float a0, a1;
      softmax1(a0, a1);
      wg_wait<0>(); reg_fence(oacc);
      if (lane == 0) mbar_arrive(bE + slv * 8);
      it += 2;
#pragma unroll
      for (int i = 0; i < 24; i++) {
        oacc[4 * i] *= a0; oacc[4 * i + 1] *= a0; oacc[4 * i + 2] *= a1; oacc[4 * i + 3] *= a1;
      }
      cvt_p();
      TS(1, tsi); tsi++;
    }
    {
      const int sl = it % 3;
      mbar_wait(bF + sl * 8, (it / 3) & 1);
      named_bar(3 + wg, 256);
      wg_fence();
      issue_pv(sl, n > 1);
      if (!(wg == 1 && sg == nseg - 1)) bar_arrive(3 + (wg ^ 1), 256);
      wg_wait<0>(); reg_fence(oacc);
      if (lane == 0) mbar_arrive(bE + sl * 8);
      it++;
    }
    TS(1, tsi); tsi++;
    if (!owner) {
      const int slot = (grp * 5 + (ci - 7)) * 2 + sg;
      float4* dst = g_part + (size_t)(slot * 2 + wg) * 25 * 128 + wtid;
#pragma unroll
      for (int i = 0; i < 24; i++) dst[i * 128] = make_float4(oacc[4 * i], oacc[4 * i + 1], oacc[4 * i + 2], oacc[4 * i + 3]);
      dst[24 * 128] = make_float4(m0, m1, l0, l1);
      __threadfence();
      named_bar(1 + wg, 128);
      if (wtid == 0) atomicAdd(&g_flag[slot], 1u);
      TS(1, tsi); tsi++;
    }
  }
  if (!owner) return;

  {
    const int first = (0x9765310 >> (4 * ci)) & 15, cnt = (0x1211221 >> (4 * ci)) & 15;
    for (int q = 0; q < cnt; q++) {
      const int slot = grp * 10 + first + q;
      if (wtid == 0) {
        uint32_t n = 0, v;
        do {
          asm volatile("ld.acquire.gpu.global.u32 %0, [%1];" : "=r"(v) : "l"(&g_flag[slot]) : "memory");
        } while (v < 2u && ++n < (1u << 22));
      }
      named_bar(1 + wg, 128);
      const float4* src = g_part + (size_t)(slot * 2 + wg) * 25 * 128 + wtid;
      const float4 ml = __ldcg(src + 24 * 128);
      const float mx0 = fmaxf(m0, ml.x), mx1 = fmaxf(m1, ml.y);
      const float a0 = ex2((m0 - mx0) * cs), a1 = ex2((m1 - mx1) * cs);
      const float b0 = ex2((ml.x - mx0) * cs), b1 = ex2((ml.y - mx1) * cs);
      m0 = mx0; m1 = mx1;
      l0 = l0 * a0 + ml.z * b0; l1 = l1 * a1 + ml.w * b1;
#pragma unroll
      for (int i = 0; i < 24; i++) {
        const float4 v = __ldcg(src + i * 128);
        oacc[4 * i] = oacc[4 * i] * a0 + v.x * b0; oacc[4 * i + 1] = oacc[4 * i + 1] * a0 + v.y * b0;
        oacc[4 * i + 2] = oacc[4 * i + 2] * a1 + v.z * b1; oacc[4 * i + 3] = oacc[4 * i + 3] * a1 + v.w * b1;
      }
    }
  }
  TS(1, 21);
  l0 += __shfl_xor_sync(0xffffffffu, l0, 1); l0 += __shfl_xor_sync(0xffffffffu, l0, 2);
  l1 += __shfl_xor_sync(0xffffffffu, l1, 1); l1 += __shfl_xor_sync(0xffffffffu, l1, 2);
  const float i0 = 1.f / l0, i1 = 1.f / l1;
  mbar_wait(bQF, 1);
  const FragAddr fa(wq, lane);
#pragma unroll
  for (int c = 0; c < 3; c++) resid_chunk(nullptr, &oacc[32 * c], i0, i1, qb + c * 16384, fa);
  fence_proxy_async();
  named_bar(1 + wg, 128);
  TS(1, 22);
  if (wtid == 0) {
    const int t = seg_tile[0] / 11, qt = seg_tile[0] - t * 11;
    if (qt * 128 + wg * 64 < NL) {
      for (int c = 0; c < 3; c++) tma_store_3d(&tm_out, qb + c * 16384, c * 64, qt * 128 + wg * 64, t);
      bulk_commit();
      bulk_wait0();
    }
  }
  TS(1, 23);
}

typedef CUresult (*EncodeFn)(CUtensorMap*, CUtensorMapDataType, cuuint32_t, void*, const cuuint64_t*, const cuuint64_t*,
                             const cuuint32_t*, const cuuint32_t*, CUtensorMapInterleave, CUtensorMapSwizzle,
                             CUtensorMapL2promotion, CUtensorMapFloatOOBfill);

void make_map(EncodeFn enc, CUtensorMap* m, const void* ptr, int rank, const uint64_t* dims, const uint32_t* box) {
  cuuint64_t gd[3], gs[2];
  cuuint32_t bx[3], es[3] = {1, 1, 1};
  uint64_t stride = 2;
  for (int i = 0; i < rank; i++) {
    gd[i] = dims[i]; bx[i] = box[i];
    stride *= dims[i];
    if (i < rank - 1) gs[i] = stride;
  }
  enc(m, CU_TENSOR_MAP_DATA_TYPE_BFLOAT16, rank, const_cast<void*>(ptr), gd, gs, bx, es, CU_TENSOR_MAP_INTERLEAVE_NONE,
      CU_TENSOR_MAP_SWIZZLE_128B, CU_TENSOR_MAP_L2_PROMOTION_L2_256B, CU_TENSOR_MAP_FLOAT_OOB_FILL_NONE);
}

}

extern "C" void kernel_launch(void* const* d_in, const int* in_sizes, int n_in, void* d_out, int out_size) {
  (void)in_sizes; (void)n_in; (void)out_size;
  EncodeFn enc = nullptr;
  cudaDriverEntryPointQueryResult qres;
  cudaGetDriverEntryPoint("cuTensorMapEncodeTiled", (void**)&enc, cudaEnableDefault, &qres);
  void *p_x1, *p_qkv, *p_wf;
  cudaGetSymbolAddress(&p_wf, g_wf);
  cudaGetSymbolAddress(&p_x1, g_x1);
  cudaGetSymbolAddress(&p_qkv, g_qkv);
  cudaFuncSetAttribute(kernelA, cudaFuncAttributeMaxDynamicSharedMemorySize, A_SMEM);
  cudaFuncSetAttribute(kernelB, cudaFuncAttributeMaxDynamicSharedMemorySize, B_SMEM);

  CUtensorMap tm_x, tm_wqkvt, tm_wot, tm_wqkvs, tm_x1s, tm_qkvs, tm_q, tm_kv, tm_wos, tm_x1l, tm_out, tm_wf;
  const uint64_t d_act[3] = {192, 1296, 7}, d_qkv[3] = {576, 1296, 7}, d_w3[2] = {576, 192}, d_w1[2] = {192, 192}, d_wf[2] = {384, 384};
  const uint32_t b_a[3] = {64, 9, 7}, b_w[2] = {64, 192}, b_q[3] = {64, 128, 1}, b_kv[3] = {64, 144, 1}, b_o[3] = {64, 64, 1}, b_w64[2] = {64, 64};
  make_map(enc, &tm_x, d_in[0], 3, d_act, b_a);
  make_map(enc, &tm_wqkvt, d_in[1], 2, d_w3, b_w64);
  make_map(enc, &tm_wot, d_in[2], 2, d_w1, b_w);
  make_map(enc, &tm_wqkvs, d_in[3], 2, d_w3, b_w64);
  make_map(enc, &tm_wos, d_in[4], 2, d_w1, b_w);
  make_map(enc, &tm_wf, p_wf, 2, d_wf, b_w);
  make_map(enc, &tm_x1s, p_x1, 3, d_act, b_a);
  make_map(enc, &tm_qkvs, p_qkv, 3, d_qkv, b_a);
  make_map(enc, &tm_q, p_qkv, 3, d_qkv, b_q);
  make_map(enc, &tm_kv, p_qkv, 3, d_qkv, b_kv);
  make_map(enc, &tm_x1l, p_x1, 3, d_act, b_q);
  make_map(enc, &tm_out, d_out, 3, d_act, b_o);

  kernelA<<<72 + A_FOLD, 384, A_SMEM>>>(tm_x, tm_wqkvt, tm_wot, tm_wqkvs, tm_wos, tm_wf, tm_x1s, tm_qkvs);
  kernelB<<<B_GRID, 384, B_SMEM>>>(tm_q, tm_kv, tm_x1l, tm_out);
}
```

```cpp
#include <cuda_runtime.h>
#include <cuda_bf16.h>
#include <cuda.h>
#include <stdint.h>

namespace {

constexpr int TT = 7, NL = 1296, CC = 192;

__device__ __align__(1024) __nv_bfloat16 g_x1[TT * NL * CC];
__device__ __align__(1024) __nv_bfloat16 g_qkv[TT * NL * 3 * CC];
__device__ __align__(1024) __nv_bfloat16 g_wf[2 * CC * 2 * CC];
__device__ __align__(1024) float4 g_part[110 * 2 * 25 * 128];
__device__ unsigned int g_flag[128];
__device__ unsigned int g_wflag[4];

#define TS(k, i)

__device__ __forceinline__ uint32_t smem_u32(const void* p) { return (uint32_t)__cvta_generic_to_shared(p); }
__device__ __forceinline__ void mbar_init(uint32_t bar, uint32_t cnt) {
  asm volatile("mbarrier.init.shared::cta.b64 [%0], %1;" ::"r"(bar), "r"(cnt));
}
__device__ __forceinline__ void mbar_expect_tx(uint32_t bar, uint32_t bytes) {
  asm volatile("mbarrier.arrive.expect_tx.shared::cta.b64 _, [%0], %1;" ::"r"(bar), "r"(bytes) : "memory");
}
__device__ __forceinline__ void mbar_arrive(uint32_t bar) {
  asm volatile("mbarrier.arrive.shared::cta.b64 _, [%0];" ::"r"(bar) : "memory");
}
__device__ __forceinline__ bool mbar_try(uint32_t bar, uint32_t parity) {
  uint32_t ok;
  asm volatile("{\n.reg .pred p;\nmbarrier.try_wait.parity.shared::cta.b64 p, [%1], %2;\nselp.u32 %0, 1, 0, p;\n}"
               : "=r"(ok) : "r"(bar), "r"(parity) : "memory");
  return ok != 0;
}
__device__ __forceinline__ void mbar_wait(uint32_t bar, uint32_t parity) {
  if (mbar_try(bar, parity)) return;
  uint32_t n = 0;
  while (!mbar_try(bar, parity)) {
    if (++n > (1u << 22)) break;
  }
}
__device__ __forceinline__ void tma_load_2d(uint32_t dst, const CUtensorMap* m, uint32_t bar, int c0, int c1) {
  asm volatile("cp.async.bulk.tensor.2d.shared::cluster.global.mbarrier::complete_tx::bytes [%0], [%1, {%3, %4}], [%2];"
               ::"r"(dst), "l"(m), "r"(bar), "r"(c0), "r"(c1) : "memory");
}
__device__ __forceinline__ void tma_load_3d(uint32_t dst, const CUtensorMap* m, uint32_t bar, int c0, int c1, int c2) {
  asm volatile("cp.async.bulk.tensor.3d.shared::cluster.global.mbarrier::complete_tx::bytes [%0], [%1, {%3, %4, %5}], [%2];"
               ::"r"(dst), "l"(m), "r"(bar), "r"(c0), "r"(c1), "r"(c2) : "memory");
}
__device__ __forceinline__ void tma_store_3d(const CUtensorMap* m, uint32_t src, int c0, int c1, int c2) {
  asm volatile("cp.async.bulk.tensor.3d.global.shared::cta.bulk_group [%0, {%2, %3, %4}], [%1];"
               ::"l"(m), "r"(src), "r"(c0), "r"(c1), "r"(c2) : "memory");
}
__device__ __forceinline__ void bulk_commit() { asm volatile("cp.async.bulk.commit_group;" ::: "memory"); }
__device__ __forceinline__ void bulk_wait_read0() { asm volatile("cp.async.bulk.wait_group.read 0;" ::: "memory"); }
__device__ __forceinline__ void bulk_wait0() { asm volatile("cp.async.bulk.wait_group 0;" ::: "memory"); }
__device__ __forceinline__ void fence_proxy_async() { asm volatile("fence.proxy.async.shared::cta;" ::: "memory"); }
__device__ __forceinline__ void prefetch_tmap(const CUtensorMap* m) {
  asm volatile("prefetch.tensormap [%0];" ::"l"(m) : "memory");
}
__device__ __forceinline__ void wg_fence() { asm volatile("wgmma.fence.sync.aligned;" ::: "memory"); }
__device__ __forceinline__ void wg_commit() { asm volatile("wgmma.commit_group.sync.aligned;" ::: "memory"); }
template <int N> __device__ __forceinline__ void wg_wait() { asm volatile("wgmma.wait_group.sync.aligned %0;" ::"n"(N) : "memory"); }
__device__ __forceinline__ void named_bar(int id, int nthreads) {
  asm volatile("bar.sync %0, %1;" ::"r"(id), "r"(nthreads) : "memory");
}
__device__ __forceinline__ void ldsm_x4(uint32_t (&r)[4], uint32_t addr) {
  asm volatile("ldmatrix.sync.aligned.m8n8.x4.shared.b16 {%0,%1,%2,%3}, [%4];"
               : "=r"(r[0]), "=r"(r[1]), "=r"(r[2]), "=r"(r[3]) : "r"(addr) : "memory");
}
__device__ __forceinline__ void stsm_x4(uint32_t addr, const uint32_t (&r)[4]) {
  asm volatile("stmatrix.sync.aligned.m8n8.x4.shared.b16 [%0], {%1,%2,%3,%4};"
               ::"r"(addr), "r"(r[0]), "r"(r[1]), "r"(r[2]), "r"(r[3]) : "memory");
}
__device__ __forceinline__ uint32_t pack_bf16(float lo, float hi) {
  uint32_t r;
  asm("cvt.rn.bf16x2.f32 %0, %1, %2;" : "=r"(r) : "f"(hi), "f"(lo));
  return r;
}
__device__ __forceinline__ float bf_lo(uint32_t v) { return __uint_as_float(v << 16); }
__device__ __forceinline__ float bf_hi(uint32_t v) { return __uint_as_float(v & 0xffff0000u); }
__device__ __forceinline__ float ex2(float x) {
  float y;
  asm("ex2.approx.ftz.f32 %0, %1;" : "=f"(y) : "f"(x));
  return y;
}
__device__ __forceinline__ uint64_t mk_desc(uint32_t addr, uint32_t lbo, uint32_t sbo) {
  return (uint64_t)((addr & 0x3FFFF) >> 4) | ((uint64_t)((lbo & 0x3FFFF) >> 4) << 16) |
         ((uint64_t)((sbo & 0x3FFFF) >> 4) << 32) | (1ull << 62);
}
__device__ __forceinline__ uint64_t mk_desc_o(uint32_t addr, uint32_t lbo, uint32_t sbo) {
  asm volatile("" : "+r"(addr));
  return mk_desc(addr, lbo, sbo);
}
template <int N> __device__ __forceinline__ void reg_fence(float (&d)[N]) {
#pragma unroll
  for (int i = 0; i < N; i++) asm volatile("" : "+f"(d[i])::"memory");
}

template<int TB> __device__ __forceinline__ void wgmma_n144_ss(float (&d)[72], uint64_t da, uint64_t db, int sc) {
  asm volatile("{\n.reg .pred p;\nsetp.ne.b32 p, %74, 0;\n"
    "wgmma.mma_async.sync.aligned.m64n144k16.f32.bf16.bf16 {%0, %1, %2, %3, %4, %5, %6, %7, %8, %9, %10, %11, %12, %13, %14, %15, %16, %17, %18, %19, %20, %21, %22, %23, %24, %25, %26, %27, %28, %29, %30, %31, %32, %33, %34, %35, %36, %37, %38, %39, %40, %41, %42, %43, %44, %45, %46, %47, %48, %49, %50, %51, %52, %53, %54, %55, %56, %57, %58, %59, %60, %61, %62, %63, %64, %65, %66, %67, %68, %69, %70, %71}, %72, %73, p, 1, 1, 0, %75;\n}\n"
    : "+f"(d[0]), "+f"(d[1]), "+f"(d[2]), "+f"(d[3]), "+f"(d[4]), "+f"(d[5]), "+f"(d[6]), "+f"(d[7]), "+f"(d[8]), "+f"(d[9]), "+f"(d[10]), "+f"(d[11]), "+f"(d[12]), "+f"(d[13]), "+f"(d[14]), "+f"(d[15]), "+f"(d[16]), "+f"(d[17]), "+f"(d[18]), "+f"(d[19]), "+f"(d[20]), "+f"(d[21]), "+f"(d[22]), "+f"(d[23]), "+f"(d[24]), "+f"(d[25]), "+f"(d[26]), "+f"(d[27]), "+f"(d[28]), "+f"(d[29]), "+f"(d[30]), "+f"(d[31]), "+f"(d[32]), "+f"(d[33]), "+f"(d[34]), "+f"(d[35]), "+f"(d[36]), "+f"(d[37]), "+f"(d[38]), "+f"(d[39]), "+f"(d[40]), "+f"(d[41]), "+f"(d[42]), "+f"(d[43]), "+f"(d[44]), "+f"(d[45]), "+f"(d[46]), "+f"(d[47]), "+f"(d[48]), "+f"(d[49]), "+f"(d[50]), "+f"(d[51]), "+f"(d[52]), "+f"(d[53]), "+f"(d[54]), "+f"(d[55]), "+f"(d[56]), "+f"(d[57]), "+f"(d[58]), "+f"(d[59]), "+f"(d[60]), "+f"(d[61]), "+f"(d[62]), "+f"(d[63]), "+f"(d[64]), "+f"(d[65]), "+f"(d[66]), "+f"(d[67]), "+f"(d[68]), "+f"(d[69]), "+f"(d[70]), "+f"(d[71])
    : "l"(da), "l"(db), "r"(sc), "n"(TB));
}
template<int TB> __device__ __forceinline__ void wgmma_n192_rs(float (&d)[96], const uint32_t (&a)[4], uint64_t db, int sc) {
  asm volatile("{\n.reg .pred p;\nsetp.ne.b32 p, %101, 0;\n"
    "wgmma.mma_async.sync.aligned.m64n192k16.f32.bf16.bf16 {%0, %1, %2, %3, %4, %5, %6, %7, %8, %9, %10, %11, %12, %13, %14, %15, %16, %17, %18, %19, %20, %21, %22, %23, %24, %25, %26, %27, %28, %29, %30, %31, %32, %33, %34, %35, %36, %37, %38, %39, %40, %41, %42, %43, %44, %45, %46, %47, %48, %49, %50, %51, %52, %53, %54, %55, %56, %57, %58, %59, %60, %61, %62, %63, %64, %65, %66, %67, %68, %69, %70, %71, %72, %73, %74, %75, %76, %77, %78, %79, %80, %81, %82, %83, %84, %85, %86, %87, %88, %89, %90, %91, %92, %93, %94, %95}, {%96, %97, %98, %99}, %100, p, 1, 1, %102;\n}\n"
    : "+f"(d[0]), "+f"(d[1]), "+f"(d[2]), "+f"(d[3]), "+f"(d[4]), "+f"(d[5]), "+f"(d[6]), "+f"(d[7]), "+f"(d[8]), "+f"(d[9]), "+f"(d[10]), "+f"(d[11]), "+f"(d[12]), "+f"(d[13]), "+f"(d[14]), "+f"(d[15]), "+f"(d[16]), "+f"(d[17]), "+f"(d[18]), "+f"(d[19]), "+f"(d[20]), "+f"(d[21]), "+f"(d[22]), "+f"(d[23]), "+f"(d[24]), "+f"(d[25]), "+f"(d[26]), "+f"(d[27]), "+f"(d[28]), "+f"(d[29]), "+f"(d[30]), "+f"(d[31]), "+f"(d[32]), "+f"(d[33]), "+f"(d[34]), "+f"(d[35]), "+f"(d[36]), "+f"(d[37]), "+f"(d[38]), "+f"(d[39]), "+f"(d[40]), "+f"(d[41]), "+f"(d[42]), "+f"(d[43]), "+f"(d[44]), "+f"(d[45]), "+f"(d[46]), "+f"(d[47]), "+f"(d[48]), "+f"(d[49]), "+f"(d[50]), "+f"(d[51]), "+f"(d[52]), "+f"(d[53]), "+f"(d[54]), "+f"(d[55]), "+f"(d[56]), "+f"(d[57]), "+f"(d[58]), "+f"(d[59]), "+f"(d[60]), "+f"(d[61]), "+f"(d[62]), "+f"(d[63]), "+f"(d[64]), "+f"(d[65]), "+f"(d[66]), "+f"(d[67]), "+f"(d[68]), "+f"(d[69]), "+f"(d[70]), "+f"(d[71]), "+f"(d[72]), "+f"(d[73]), "+f"(d[74]), "+f"(d[75]), "+f"(d[76]), "+f"(d[77]), "+f"(d[78]), "+f"(d[79]), "+f"(d[80]), "+f"(d[81]), "+f"(d[82]), "+f"(d[83]), "+f"(d[84]), "+f"(d[85]), "+f"(d[86]), "+f"(d[87]), "+f"(d[88]), "+f"(d[89]), "+f"(d[90]), "+f"(d[91]), "+f"(d[92]), "+f"(d[93]), "+f"(d[94]), "+f"(d[95])
    : "r"(a[0]), "r"(a[1]), "r"(a[2]), "r"(a[3]), "l"(db), "r"(sc), "n"(TB));
}
template<int TB> __device__ __forceinline__ void wgmma_n64_rs(float (&d)[32], const uint32_t (&a)[4], uint64_t db, int sc) {
  asm volatile("{\n.reg .pred p;\nsetp.ne.b32 p, %37, 0;\n"
    "wgmma.mma_async.sync.aligned.m64n64k16.f32.bf16.bf16 {%0, %1, %2, %3, %4, %5, %6, %7, %8, %9, %10, %11, %12, %13, %14, %15, %16, %17, %18, %19, %20, %21, %22, %23, %24, %25, %26, %27, %28, %29, %30, %31}, {%32, %33, %34, %35}, %36, p, 1, 1, %38;\n}\n"
    : "+f"(d[0]), "+f"(d[1]), "+f"(d[2]), "+f"(d[3]), "+f"(d[4]), "+f"(d[5]), "+f"(d[6]), "+f"(d[7]), "+f"(d[8]), "+f"(d[9]), "+f"(d[10]), "+f"(d[11]), "+f"(d[12]), "+f"(d[13]), "+f"(d[14]), "+f"(d[15]), "+f"(d[16]), "+f"(d[17]), "+f"(d[18]), "+f"(d[19]), "+f"(d[20]), "+f"(d[21]), "+f"(d[22]), "+f"(d[23]), "+f"(d[24]), "+f"(d[25]), "+f"(d[26]), "+f"(d[27]), "+f"(d[28]), "+f"(d[29]), "+f"(d[30]), "+f"(d[31])
    : "r"(a[0]), "r"(a[1]), "r"(a[2]), "r"(a[3]), "l"(db), "r"(sc), "n"(TB));
}
template<int TB> __device__ __forceinline__ void wgmma_n64_ss(float (&d)[32], uint64_t da, uint64_t db, int sc) {
  asm volatile("{\n.reg .pred p;\nsetp.ne.b32 p, %34, 0;\n"
    "wgmma.mma_async.sync.aligned.m64n64k16.f32.bf16.bf16 {%0, %1, %2, %3, %4, %5, %6, %7, %8, %9, %10, %11, %12, %13, %14, %15, %16, %17, %18, %19, %20, %21, %22, %23, %24, %25, %26, %27, %28, %29, %30, %31}, %32, %33, p, 1, 1, 0, %35;\n}\n"
    : "+f"(d[0]), "+f"(d[1]), "+f"(d[2]), "+f"(d[3]), "+f"(d[4]), "+f"(d[5]), "+f"(d[6]), "+f"(d[7]), "+f"(d[8]), "+f"(d[9]), "+f"(d[10]), "+f"(d[11]), "+f"(d[12]), "+f"(d[13]), "+f"(d[14]), "+f"(d[15]), "+f"(d[16]), "+f"(d[17]), "+f"(d[18]), "+f"(d[19]), "+f"(d[20]), "+f"(d[21]), "+f"(d[22]), "+f"(d[23]), "+f"(d[24]), "+f"(d[25]), "+f"(d[26]), "+f"(d[27]), "+f"(d[28]), "+f"(d[29]), "+f"(d[30]), "+f"(d[31])
    : "l"(da), "l"(db), "r"(sc), "n"(TB));
}

struct FragAddr {
  uint32_t rowoff;
  uint32_t rx;
  uint32_t hi;
  __device__ __forceinline__ FragAddr(int warp_in_wg, int lane) {
    int row = 16 * warp_in_wg + (lane & 7) + ((lane >> 3) & 1) * 8;
    rowoff = row * 128;
    rx = row & 7;
    hi = lane >> 4;
  }
  __device__ __forceinline__ uint32_t at(uint32_t chunk_base, int kk4) const {
    return chunk_base + rowoff + ((((uint32_t)kk4 * 2 + hi) ^ rx) << 4);
  }
};

__device__ __forceinline__ void layernorm_frags(uint32_t (&f)[12][4]) {
  float s0 = 0.f, s1 = 0.f;
#pragma unroll
  for (int k = 0; k < 12; k++) {
    s0 += bf_lo(f[k][0]) + bf_hi(f[k][0]) + bf_lo(f[k][2]) + bf_hi(f[k][2]);
    s1 += bf_lo(f[k][1]) + bf_hi(f[k][1]) + bf_lo(f[k][3]) + bf_hi(f[k][3]);
  }
  s0 += __shfl_xor_sync(0xffffffffu, s0, 1); s0 += __shfl_xor_sync(0xffffffffu, s0, 2);
  s1 += __shfl_xor_sync(0xffffffffu, s1, 1); s1 += __shfl_xor_sync(0xffffffffu, s1, 2);
  const float m0 = s0 * (1.f / 192.f), m1 = s1 * (1.f / 192.f);
  float v0 = 0.f, v1 = 0.f;
#pragma unroll
  for (int k = 0; k < 12; k++) {
    float a;
    a = bf_lo(f[k][0]) - m0; v0 += a * a; a = bf_hi(f[k][0]) - m0; v0 += a * a;
    a = bf_lo(f[k][2]) - m0; v0 += a * a; a = bf_hi(f[k][2]) - m0; v0 += a * a;
    a = bf_lo(f[k][1]) - m1; v1 += a * a; a = bf_hi(f[k][1]) - m1; v1 += a * a;
    a = bf_lo(f[k][3]) - m1; v1 += a * a; a = bf_hi(f[k][3]) - m1; v1 += a * a;
  }
  v0 += __shfl_xor_sync(0xffffffffu, v0, 1); v0 += __shfl_xor_sync(0xffffffffu, v0, 2);
  v1 += __shfl_xor_sync(0xffffffffu, v1, 1); v1 += __shfl_xor_sync(0xffffffffu, v1, 2);
  const float r0 = rsqrtf(v0 * (1.f / 192.f) + 1e-5f), r1 = rsqrtf(v1 * (1.f / 192.f) + 1e-5f);
#pragma unroll
  for (int k = 0; k < 12; k++) {
    f[k][0] = pack_bf16((bf_lo(f[k][0]) - m0) * r0, (bf_hi(f[k][0]) - m0) * r0);
    f[k][2] = pack_bf16((bf_lo(f[k][2]) - m0) * r0, (bf_hi(f[k][2]) - m0) * r0);
    f[k][1] = pack_bf16((bf_lo(f[k][1]) - m1) * r1, (bf_hi(f[k][1]) - m1) * r1);
    f[k][3] = pack_bf16((bf_lo(f[k][3]) - m1) * r1, (bf_hi(f[k][3]) - m1) * r1);
  }
}

constexpr int A_NST = 5;
constexpr int A_XS = 0;
constexpr int A_VB = 49152;
constexpr int A_W = 98304;
constexpr int A_BAR = A_W + A_NST * 24576;
constexpr int A_SMEM = A_BAR + 256 + 1024;
constexpr int A_FOLD = 36;

__device__ __forceinline__ void a_issue(float (&acc)[32], const uint32_t (&af)[12][4], uint32_t sb, int s) {
  const int st = s % A_NST;
  mbar_wait(sb + A_BAR + st * 8, (s / A_NST) & 1);
  const uint64_t wd = mk_desc_o(sb + A_W + st * 24576, 8192, 1024);
  wg_fence();
#pragma unroll
  for (int kk = 0; kk < 12; kk++) wgmma_n64_rs<1>(acc, af[kk], wd + kk * 128, kk > 0);
  wg_commit();
}
__device__ __forceinline__ void a_release(uint32_t sb, int s, int lane) {
  if (lane == 0) mbar_arrive(sb + A_BAR + 64 + (s % A_NST) * 8);
}
__device__ __forceinline__ void cvt_frags(uint32_t (*dst)[4], const float (&acc)[32]) {
#pragma unroll
  for (int k = 0; k < 4; k++) {
    dst[k][0] = pack_bf16(acc[8 * k + 0], acc[8 * k + 1]);
    dst[k][1] = pack_bf16(acc[8 * k + 2], acc[8 * k + 3]);
    dst[k][2] = pack_bf16(acc[8 * k + 4], acc[8 * k + 5]);
    dst[k][3] = pack_bf16(acc[8 * k + 6], acc[8 * k + 7]);
  }
}
__device__ __forceinline__ void store_chunk(const float (&acc)[32], uint32_t chunk_base, const FragAddr& fa) {
  uint32_t t[4][4];
  cvt_frags(t, acc);
#pragma unroll
  for (int k = 0; k < 4; k++) stsm_x4(fa.at(chunk_base, k), t[k]);
}
__device__ __forceinline__ void resid_chunk(uint32_t (*dst)[4], const float* acc, float s0, float s1, uint32_t chunk_base,
                                            const FragAddr& fa) {
#pragma unroll
  for (int k = 0; k < 4; k++) {
    uint32_t x[4];
    ldsm_x4(x, fa.at(chunk_base, k));
    uint32_t o[4];
    o[0] = pack_bf16(fmaf(acc[8 * k + 0], s0, bf_lo(x[0])), fmaf(acc[8 * k + 1], s0, bf_hi(x[0])));
    o[1] = pack_bf16(fmaf(acc[8 * k + 2], s1, bf_lo(x[1])), fmaf(acc[8 * k + 3], s1, bf_hi(x[1])));
    o[2] = pack_bf16(fmaf(acc[8 * k + 4], s0, bf_lo(x[2])), fmaf(acc[8 * k + 5], s0, bf_hi(x[2])));
    o[3] = pack_bf16(fmaf(acc[8 * k + 6], s1, bf_lo(x[3])), fmaf(acc[8 * k + 7], s1, bf_hi(x[3])));
    stsm_x4(fa.at(chunk_base, k), o);
    if (dst) { dst[k][0] = o[0]; dst[k][1] = o[1]; dst[k][2] = o[2]; dst[k][3] = o[3]; }
  }
}

__global__ void __launch_bounds__(384, 1)
kernelA(const __grid_constant__ CUtensorMap tm_x, const __grid_constant__ CUtensorMap tm_wq64t,
        const __grid_constant__ CUtensorMap tm_wot, const __grid_constant__ CUtensorMap tm_wq64s,
        const __grid_constant__ CUtensorMap tm_wos, const __grid_constant__ CUtensorMap tm_wf,
        const __grid_constant__ CUtensorMap tm_x1, const __grid_constant__ CUtensorMap tm_qkv) {
  extern __shared__ uint8_t smem_raw[];
  const uint32_t sb = (smem_u32(smem_raw) + 1023) & ~1023u;
  const int tid = threadIdx.x, warp = tid >> 5, lane = tid & 31;
  const bool is_fold = blockIdx.x < A_FOLD;
  const int blk = blockIdx.x - A_FOLD;
  if (tid == 256) {
    for (int i = 0; i < A_NST; i++) { mbar_init(sb + A_BAR + i * 8, 1); mbar_init(sb + A_BAR + 64 + i * 8, 8); }
    mbar_init(sb + A_BAR + 128, 1); mbar_init(sb + A_BAR + 136, 1);
    asm volatile("fence.mbarrier_init.release.cluster;" ::: "memory");
    if (!is_fold) {
      for (int w = 0; w < 2; w++) {
        const uint32_t bar = sb + A_BAR + 128 + w * 8;
        mbar_expect_tx(bar, 3 * 63 * 128);
        for (int c = 0; c < 3; c++)
          tma_load_3d(sb + A_XS + w * 24576 + c * 8192, &tm_x, bar, c * 64, (blk * 2 + w) * 9, 0);
      }
    } else {
      const int mat = blockIdx.x / 9, rs = (blockIdx.x % 9) / 3, cs = blockIdx.x % 3;
      const CUtensorMap* mq = (mat < 2) ? &tm_wq64t : &tm_wq64s;
      const CUtensorMap* mo = (mat < 2) ? &tm_wot : &tm_wos;
      const uint32_t bar = sb + A_BAR + 128;
      mbar_expect_tx(bar, 2 * 24576);
      for (int c = 0; c < 3; c++) tma_load_2d(sb + c * 8192, mq, bar, ((mat & 1) ? 384 : 0) + c * 64, rs * 64);
      if (mat & 1) tma_load_2d(sb + 24576, mo, bar, cs * 64, 0);
      else for (int c = 0; c < 3; c++) tma_load_2d(sb + 24576 + c * 8192, mq, bar, 192 + c * 64, cs * 64);
    }
  }
  if (blockIdx.x == 0 && tid < 128) g_flag[tid] = 0;
  if (!is_fold && tid < 48) {
    uint32_t a = sb + A_XS + (tid >> 3) * 8192 + 63 * 128 + (tid & 7) * 16;
    asm volatile("st.shared.v4.b32 [%0], {%1,%1,%1,%1};" ::"r"(a), "r"(0) : "memory");
  }
  __syncthreads();

  if (warp >= 8) {
    asm volatile("setmaxnreg.dec.sync.aligned.u32 24;");
    if (warp == 8 && lane == 0 && !is_fold) {
      for (int s = 0; s < 12; s++) {
        const int st = s % A_NST;
        const int g = s / 3;
        const int mat = (g == 0) ? 1 : (g == 1) ? 0 : g;
        if (s % 3 == 0) {
          uint32_t n = 0, v;
          do {
            asm volatile("ld.acquire.gpu.global.u32 %0, [%1];" : "=r"(v) : "l"(&g_wflag[mat]) : "memory");
          } while (v < 9u && ++n < (1u << 22));
          asm volatile("fence.proxy.async;" ::: "memory");
        }
        if (s >= A_NST) mbar_wait(sb + A_BAR + 64 + st * 8, ((s / A_NST) - 1) & 1);
        mbar_expect_tx(sb + A_BAR + st * 8, 24576);
        tma_load_2d(sb + A_W + st * 24576, &tm_wf, sb + A_BAR + st * 8, (mat & 1) * 192 + (s % 3) * 64, (mat >> 1) * 192);
      }
    }
    return;
  }

  asm volatile("setmaxnreg.inc.sync.aligned.u32 240;");
  const int wg = warp >> 2, wq = warp & 3;

  if (is_fold) {
    if (wg == 0) {
      const int mat = blockIdx.x / 9, rs = (blockIdx.x % 9) / 3, cs = blockIdx.x % 3;
      float d[32];
      mbar_wait(sb + A_BAR + 128, 0);
      const uint64_t ad = mk_desc_o(sb, 16, 1024);
      if (mat & 1) {
        const uint64_t bd = mk_desc_o(sb + 24576, 8192, 1024);
        wg_fence();
#pragma unroll
        for (int kk = 0; kk < 12; kk++) wgmma_n64_ss<1>(d, ad + (kk >> 2) * 512 + (kk & 3) * 2, bd + kk * 128, kk > 0);
        wg_commit();
      } else {
        const uint64_t bd = mk_desc_o(sb + 24576, 16, 1024);
        wg_fence();
#pragma unroll
        for (int kk = 0; kk < 12; kk++)
          wgmma_n64_ss<0>(d, ad + (kk >> 2) * 512 + (kk & 3) * 2, bd + (kk >> 2) * 512 + (kk & 3) * 2, kk > 0);
        wg_commit();
      }
      wg_wait<0>(); reg_fence(d);
      const int r0 = rs * 64 + wq * 16 + (lane >> 2);
      uint32_t* dst = reinterpret_cast<uint32_t*>(g_wf + ((size_t)(mat >> 1) * 192 + r0) * 384 + (mat & 1) * 192 + cs * 64 + (lane & 3) * 2);
#pragma unroll
      for (int j = 0; j < 8; j++) {
        dst[j * 4] = pack_bf16(d[4 * j], d[4 * j + 1]);
        dst[8 * 192 + j * 4] = pack_bf16(d[4 * j + 2], d[4 * j + 3]);
      }
      asm volatile("fence.proxy.async;" ::: "memory");
      __threadfence();
      named_bar(1, 128);
      if (tid == 0) atomicAdd(&g_wflag[mat], 1u);
    }
    return;
  }

  const int n0 = (blk * 2 + wg) * 9;
  const FragAddr fa(wq, lane);
  const uint32_t xs = sb + A_XS + wg * 24576, vb = sb + A_VB + wg * 24576;
  const int barid = 1 + wg;
  const bool elected = (tid & 127) == 0;

  uint32_t h[12][4];
  TS(0, 0);
  mbar_wait(sb + A_BAR + 128 + wg * 8, 0);
  TS(0, 1);
#pragma unroll
  for (int k = 0; k < 12; k++) ldsm_x4(h[k], fa.at(xs + (k >> 2) * 8192, k & 3));
  layernorm_frags(h);
#pragma unroll
  for (int k = 0; k < 12; k++) stsm_x4(fa.at(xs + (k >> 2) * 8192, k & 3), h[k]);

  float acc0[32], acc1[32];
  uint32_t qf[12][4];
  TS(0, 2);
  a_issue(acc0, h, sb, 0);
  TS(0, 3);
  a_issue(acc1, h, sb, 1); wg_wait<1>(); reg_fence(acc0); a_release(sb, 0, lane); store_chunk(acc0, vb, fa);
  a_issue(acc0, h, sb, 2); wg_wait<1>(); reg_fence(acc1); a_release(sb, 1, lane); store_chunk(acc1, vb + 8192, fa);
  a_issue(acc1, h, sb, 3); wg_wait<1>(); reg_fence(acc0); a_release(sb, 2, lane); store_chunk(acc0, vb + 16384, fa);
  fence_proxy_async();
  named_bar(barid, 128);
  a_issue(acc0, h, sb, 4); wg_wait<1>(); reg_fence(acc1); a_release(sb, 3, lane); cvt_frags(&qf[0], acc1);
  a_issue(acc1, h, sb, 5); wg_wait<1>(); reg_fence(acc0); a_release(sb, 4, lane); cvt_frags(&qf[4], acc0);
  wg_wait<0>(); reg_fence(acc1); a_release(sb, 5, lane); cvt_frags(&qf[8], acc1);
  TS(0, 4);
  {
    const uint64_t kd = mk_desc_o(xs, 16, 1024);
    wg_fence();
#pragma unroll
    for (int kk = 0; kk < 12; kk++) wgmma_n64_rs<0>(acc0, qf[kk], kd + (kk >> 2) * 512 + (kk & 3) * 2, kk > 0);
    wg_commit();
    wg_wait<0>(); reg_fence(acc0);
  }
  named_bar(barid, 128);
  if (elected) {
    const uint32_t bar = sb + A_BAR + 128 + wg * 8;
    mbar_expect_tx(bar, 3 * 63 * 128);
    for (int c = 0; c < 3; c++) tma_load_3d(xs + c * 8192, &tm_x, bar, c * 64, n0, 0);
  }
  uint32_t pf[4][4];
  {
    const int r0 = 16 * wq + (lane >> 2), r1 = r0 + 8;
    const unsigned long long MB = 0x0040201008040201ull;
    const unsigned long long mk0 = (MB << (r0 % 9)) >> (2 * (lane & 3));
    const unsigned long long mk1 = (MB << (r1 % 9)) >> (2 * (lane & 3));
    const float cs = 0.07216878364870322f * 1.4426950408889634f;
    float mx0 = -INFINITY, mx1 = -INFINITY;
#pragma unroll
    for (int j = 0; j < 8; j++) {
#pragma unroll
      for (int e = 0; e < 2; e++) {
        bool v0 = (mk0 >> (8 * j + e)) & 1, v1 = (mk1 >> (8 * j + e)) & 1;
        acc0[4 * j + e] = v0 ? acc0[4 * j + e] * cs : -INFINITY;
        acc0[4 * j + 2 + e] = v1 ? acc0[4 * j + 2 + e] * cs : -INFINITY;
        mx0 = fmaxf(mx0, acc0[4 * j + e]);
        mx1 = fmaxf(mx1, acc0[4 * j + 2 + e]);
      }
    }
    mx0 = fmaxf(mx0, __shfl_xor_sync(0xffffffffu, mx0, 1)); mx0 = fmaxf(mx0, __shfl_xor_sync(0xffffffffu, mx0, 2));
    mx1 = fmaxf(mx1, __shfl_xor_sync(0xffffffffu, mx1, 1)); mx1 = fmaxf(mx1, __shfl_xor_sync(0xffffffffu, mx1, 2));
    float l0 = 0.f, l1 = 0.f;
#pragma unroll
    for (int j = 0; j < 8; j++) {
#pragma unroll
      for (int e = 0; e < 2; e++) {
        acc0[4 * j + e] = ex2(acc0[4 * j + e] - mx0); l0 += acc0[4 * j + e];
        acc0[4 * j + 2 + e] = ex2(acc0[4 * j + 2 + e] - mx1); l1 += acc0[4 * j + 2 + e];
      }
    }
    l0 += __shfl_xor_sync(0xffffffffu, l0, 1); l0 += __shfl_xor_sync(0xffffffffu, l0, 2);
    l1 += __shfl_xor_sync(0xffffffffu, l1, 1); l1 += __shfl_xor_sync(0xffffffffu, l1, 2);
    const float i0 = 1.f / l0, i1 = 1.f / l1;
#pragma unroll
    for (int j = 0; j < 8; j++) {
      acc0[4 * j] *= i0; acc0[4 * j + 1] *= i0; acc0[4 * j + 2] *= i1; acc0[4 * j + 3] *= i1;
    }
    cvt_frags(pf, acc0);
  }
  TS(0, 5);
  {
    float oacc[96];
    const uint64_t vd = mk_desc_o(vb, 8192, 1024);
    wg_fence();
#pragma unroll
    for (int kk = 0; kk < 4; kk++) wgmma_n192_rs<1>(oacc, pf[kk], vd + kk * 128, kk > 0);
    wg_commit();
    wg_wait<0>(); reg_fence(oacc);
    TS(0, 6);
    mbar_wait(sb + A_BAR + 128 + wg * 8, 1);
#pragma unroll
    for (int c = 0; c < 3; c++) resid_chunk(&h[4 * c], &oacc[32 * c], 1.f, 1.f, xs + c * 8192, fa);
  }
  TS(0, 7);
  layernorm_frags(h);
  named_bar(barid, 128);
#pragma unroll
  for (int k = 0; k < 12; k++) stsm_x4(fa.at(vb + (k >> 2) * 8192, k & 3), h[k]);
  TS(0, 8);
  a_issue(acc0, h, sb, 6);
  fence_proxy_async();
  named_bar(barid, 128);
  if (elected) {
    for (int c = 0; c < 3; c++) tma_store_3d(&tm_x1, xs + c * 8192, c * 64, n0, 0);
    for (int c = 0; c < 3; c++) tma_store_3d(&tm_qkv, vb + c * 8192, 192 + c * 64, n0, 0);
    bulk_commit();
  }
  a_issue(acc1, h, sb, 7); wg_wait<1>(); reg_fence(acc0); a_release(sb, 6, lane);
  if (elected) bulk_wait_read0();
  named_bar(barid, 128);
  store_chunk(acc0, xs, fa);
  a_issue(acc0, h, sb, 8); wg_wait<1>(); reg_fence(acc1); store_chunk(acc1, xs + 8192, fa);
  a_issue(acc1, h, sb, 9); wg_wait<1>(); reg_fence(acc0); store_chunk(acc0, xs + 16384, fa);
  fence_proxy_async();
  named_bar(barid, 128);
  if (elected) {
    for (int c = 0; c < 3; c++) tma_store_3d(&tm_qkv, xs + c * 8192, c * 64, n0, 0);
    bulk_commit();
  }
  a_issue(acc0, h, sb, 10); wg_wait<1>(); reg_fence(acc1); store_chunk(acc1, vb, fa);
  a_issue(acc1, h, sb, 11); wg_wait<1>(); reg_fence(acc0); store_chunk(acc0, vb + 8192, fa);
  wg_wait<0>(); reg_fence(acc1); store_chunk(acc1, vb + 16384, fa);
  fence_proxy_async();
  named_bar(barid, 128);
  TS(0, 9);
  if (elected) {
    for (int c = 0; c < 3; c++) tma_store_3d(&tm_qkv, vb + c * 8192, 384 + c * 64, n0, 0);
    bulk_commit();
    bulk_wait0();
  }
  TS(0, 10);
}

constexpr int B_GRID = 132;
constexpr int B_SLOT = 55296;
constexpr int B_Q = 0;
constexpr int B_KV = 49152;
constexpr int B_BAR = B_KV + 3 * B_SLOT;
constexpr int B_SMEM = B_BAR + 256 + 1024;

__device__ __forceinline__ void bar_arrive(int id, int nthreads) {
  asm volatile("bar.arrive %0, %1;" ::"r"(id), "r"(nthreads) : "memory");
}

__global__ void __launch_bounds__(384, 1)
kernelB(const __grid_constant__ CUtensorMap tm_q, const __grid_constant__ CUtensorMap tm_kv,
        const __grid_constant__ CUtensorMap tm_x1, const __grid_constant__ CUtensorMap tm_out) {
  extern __shared__ uint8_t smem_raw[];
  const uint32_t sb = (smem_u32(smem_raw) + 1023) & ~1023u;
  const int tid = threadIdx.x, warp = tid >> 5, lane = tid & 31;
  const uint32_t bF = sb + B_BAR, bE = sb + B_BAR + 32, bQF = sb + B_BAR + 64, bQE = sb + B_BAR + 72;
  if (tid == 0) {
    for (int i = 0; i < 3; i++) { mbar_init(bF + i * 8, 1); mbar_init(bE + i * 8, 8); }
    mbar_init(bQF, 1); mbar_init(bQE, 8);
    asm volatile("fence.mbarrier_init.release.cluster;" ::: "memory");
  }
  __syncthreads();
  const int grp = blockIdx.x / 12, ci = blockIdx.x - grp * 12;
  const bool owner = ci < 7;
  int nseg, seg_tile[2], seg_k0[2], seg_k1[2];
  if (owner) {
    nseg = 1; seg_tile[0] = grp * 7 + ci; seg_k0[0] = 3; seg_k1[0] = 9;
    seg_tile[1] = 0; seg_k0[1] = 0; seg_k1[1] = 0;
  } else {
    const int hh = ci - 7;
    nseg = 2;
    seg_tile[0] = grp * 7 + ((0x54210 >> (4 * hh)) & 15); seg_k0[0] = (0x10210 >> (4 * hh)) & 15; seg_k1[0] = 3;
    seg_tile[1] = seg_tile[0] + 1; seg_k0[1] = 0; seg_k1[1] = (0x31321 >> (4 * hh)) & 15;
  }

  if (warp >= 8) {
    asm volatile("setmaxnreg.dec.sync.aligned.u32 24;");
    if (warp == 8 && lane == 0) {
      if (blockIdx.x == 0) { g_wflag[0] = 0; g_wflag[1] = 0; g_wflag[2] = 0; g_wflag[3] = 0; }
      int it = 0;
      for (int sg = 0; sg < nseg; sg++) {
        const int tile = sg ? seg_tile[1] : seg_tile[0];
        const int k0 = sg ? seg_k0[1] : seg_k0[0], k1 = sg ? seg_k1[1] : seg_k1[0];
        const int t = tile / 11, qt = tile - t * 11;
        if (sg > 0) mbar_wait(bQE, 0);
        mbar_expect_tx(bQF, 49152);
        for (int c = 0; c < 3; c++) tma_load_3d(sb + B_Q + c * 16384, &tm_q, bQF, c * 64, qt * 128, t);
        const int n = k1 - k0;
        for (int e = 0; e < 2 * n; e++) {
          int isv, kbi;
          if (e == 0) { isv = 0; kbi = 0; }
          else if (e == 2 * n - 1) { isv = 1; kbi = n - 1; }
          else { isv = (e & 1) ^ 1; kbi = isv ? (e >> 1) - 1 : (e + 1) >> 1; }
          const int sl = it % 3;
          if (it >= 3) mbar_wait(bE + sl * 8, ((it / 3) - 1) & 1);
          mbar_expect_tx(bF + sl * 8, B_SLOT);
          for (int c = 0; c < 3; c++)
            tma_load_3d(sb + B_KV + sl * B_SLOT + c * 18432, &tm_kv, bF + sl * 8, 192 + isv * 192 + c * 64, (k0 + kbi) * 144, t);
          it++;
        }
      }
      if (owner) {
        const int t = seg_tile[0] / 11, qt = seg_tile[0] - t * 11;
        mbar_wait(bQE, 0);
        mbar_expect_tx(bQF, 49152);
        for (int c = 0; c < 3; c++) tma_load_3d(sb + B_Q + c * 16384, &tm_x1, bQF, c * 64, qt * 128, t);
      }
    }
    return;
  }

  asm volatile("setmaxnreg.inc.sync.aligned.u32 240;");
  const int wg = warp >> 2, wq = warp & 3;
  const int wtid = tid & 127;
  const float cs = 0.07216878364870322f * 1.4426950408889634f;
  float oacc[96], sacc[72];
  uint32_t pf[9][4];
  float m0, m1, l0, l1;
  int it = 0;
  const uint32_t qb = sb + B_Q + wg * 8192;
  if (wg == 1) bar_arrive(3, 256);
  TS(1, 0);
  int tsi = 1;

  auto issue_qk = [&](int slot) {
    const uint64_t kd = mk_desc_o(sb + B_KV + slot * B_SLOT, 16, 1024);
    const uint64_t qd = mk_desc_o(qb, 16, 1024);
#pragma unroll
    for (int kk = 0; kk < 12; kk++)
      wgmma_n144_ss<0>(sacc, qd + (kk >> 2) * 1024 + (kk & 3) * 2, kd + (kk >> 2) * 1152 + (kk & 3) * 2, kk > 0);
    wg_commit();
  };
  auto issue_pv = [&](int slot, int accum) {
    const uint64_t vd = mk_desc_o(sb + B_KV + slot * B_SLOT, 18432, 1024);
#pragma unroll
    for (int kk = 0; kk < 9; kk++) wgmma_n192_rs<1>(oacc, pf[kk], vd + kk * 128, kk > 0 ? 1 : accum);
    wg_commit();
  };
  auto softmax1 = [&](float& a0, float& a1) {
    float mx0 = m0, mx1 = m1;
#pragma unroll
    for (int j = 0; j < 18; j++) {
      mx0 = fmaxf(mx0, fmaxf(sacc[4 * j], sacc[4 * j + 1]));
      mx1 = fmaxf(mx1, fmaxf(sacc[4 * j + 2], sacc[4 * j + 3]));
    }
    mx0 = fmaxf(mx0, __shfl_xor_sync(0xffffffffu, mx0, 1)); mx0 = fmaxf(mx0, __shfl_xor_sync(0xffffffffu, mx0, 2));
    mx1 = fmaxf(mx1, __shfl_xor_sync(0xffffffffu, mx1, 1)); mx1 = fmaxf(mx1, __shfl_xor_sync(0xffffffffu, mx1, 2));
    a0 = ex2((m0 - mx0) * cs); a1 = ex2((m1 - mx1) * cs);
    m0 = mx0; m1 = mx1;
    const float mc0 = mx0 * cs, mc1 = mx1 * cs;
    float rs0 = 0.f, rs1 = 0.f;
#pragma unroll
    for (int j = 0; j < 18; j++) {
      sacc[4 * j] = ex2(fmaf(sacc[4 * j], cs, -mc0)); sacc[4 * j + 1] = ex2(fmaf(sacc[4 * j + 1], cs, -mc0));
      sacc[4 * j + 2] = ex2(fmaf(sacc[4 * j + 2], cs, -mc1)); sacc[4 * j + 3] = ex2(fmaf(sacc[4 * j + 3], cs, -mc1));
      rs0 += sacc[4 * j] + sacc[4 * j + 1];
      rs1 += sacc[4 * j + 2] + sacc[4 * j + 3];
    }
    l0 = l0 * a0 + rs0; l1 = l1 * a1 + rs1;
  };
  auto cvt_p = [&]() {
#pragma unroll
    for (int k = 0; k < 9; k++) {
      pf[k][0] = pack_bf16(sacc[8 * k + 0], sacc[8 * k + 1]); pf[k][1] = pack_bf16(sacc[8 * k + 2], sacc[8 * k + 3]);
      pf[k][2] = pack_bf16(sacc[8 * k + 4], sacc[8 * k + 5]); pf[k][3] = pack_bf16(sacc[8 * k + 6], sacc[8 * k + 7]);
    }
  };

  for (int sg = 0; sg < nseg; sg++) {
    const int n = sg ? (seg_k1[1] - seg_k0[1]) : (seg_k1[0] - seg_k0[0]);
    m0 = m1 = -INFINITY; l0 = l1 = 0.f;
    mbar_wait(bQF, sg & 1);
    {
      const int sl = it % 3;
      mbar_wait(bF + sl * 8, (it / 3) & 1);
      named_bar(3 + wg, 256);
      wg_fence();
      issue_qk(sl);
      bar_arrive(3 + (wg ^ 1), 256);
      wg_wait<0>(); reg_fence(sacc);
      if (lane == 0) { mbar_arrive(bE + sl * 8); if (n == 1) mbar_arrive(bQE); }
      it++;
      float a0, a1;
      softmax1(a0, a1);
      cvt_p();
    }
    TS(1, tsi); tsi++;
    for (int j = 1; j < n; j++) {
      const int slk = it % 3, slv = (it + 1) % 3;
      mbar_wait(bF + slk * 8, (it / 3) & 1);
      if (j == 3) TS(1, 10);
      named_bar(3 + wg, 256);
      if (j == 3) TS(1, 11);
      wg_fence();
      issue_qk(slk);
      mbar_wait(bF + slv * 8, ((it + 1) / 3) & 1);
      if (j == 3) TS(1, 12);
      issue_pv(slv, j > 1);
      bar_arrive(3 + (wg ^ 1), 256);
      wg_wait<1>(); reg_fence(sacc);
      if (j == 3) TS(1, 13);
      if (lane == 0) { mbar_arrive(bE + slk * 8); if (j == n - 1) mbar_arrive(bQE); }
      float a0, a1;
      softmax1(a0, a1);
      reg_fence(sacc);
      if (j == 3) TS(1, 14);
      wg_wait<0>(); reg_fence(oacc);
      if (j == 3) TS(1, 15);
      if (lane == 0) mbar_arrive(bE + slv * 8);
      it += 2;
#pragma unroll
      for (int i = 0; i < 24; i++) {
        oacc[4 * i] *= a0; oacc[4 * i + 1] *= a0; oacc[4 * i + 2] *= a1; oacc[4 * i + 3] *= a1;
      }
      cvt_p();
      TS(1, tsi); tsi++;
    }
    {
      const int sl = it % 3;
      mbar_wait(bF + sl * 8, (it / 3) & 1);
      named_bar(3 + wg, 256);
      wg_fence();
      issue_pv(sl, n > 1);
      if (!(wg == 1 && sg == nseg - 1)) bar_arrive(3 + (wg ^ 1), 256);
      wg_wait<0>(); reg_fence(oacc);
      if (lane == 0) mbar_arrive(bE + sl * 8);
      it++;
    }
    TS(1, tsi); tsi++;
    if (!owner) {
      const int slot = (grp * 5 + (ci - 7)) * 2 + sg;
      float4* dst = g_part + (size_t)(slot * 2 + wg) * 25 * 128 + wtid;
#pragma unroll
      for (int i = 0; i < 24; i++) dst[i * 128] = make_float4(oacc[4 * i], oacc[4 * i + 1], oacc[4 * i + 2], oacc[4 * i + 3]);
      dst[24 * 128] = make_float4(m0, m1, l0, l1);
      __threadfence();
      named_bar(1 + wg, 128);
      if (wtid == 0) atomicAdd(&g_flag[slot], 1u);
      TS(1, tsi); tsi++;
    }
  }
  if (!owner) return;

  {
    const int first = (0x9765310 >> (4 * ci)) & 15, cnt = (0x1211221 >> (4 * ci)) & 15;
    for (int q = 0; q < cnt; q++) {
      const int slot = grp * 10 + first + q;
      if (wtid == 0) {
        uint32_t n = 0, v;
        do {
          asm volatile("ld.acquire.gpu.global.u32 %0, [%1];" : "=r"(v) : "l"(&g_flag[slot]) : "memory");
        } while (v < 2u && ++n < (1u << 22));
      }
      named_bar(1 + wg, 128);
      const float4* src = g_part + (size_t)(slot * 2 + wg) * 25 * 128 + wtid;
      const float4 ml = __ldcg(src + 24 * 128);
      const float mx0 = fmaxf(m0, ml.x), mx1 = fmaxf(m1, ml.y);
      const float a0 = ex2((m0 - mx0) * cs), a1 = ex2((m1 - mx1) * cs);
      const float b0 = ex2((ml.x - mx0) * cs), b1 = ex2((ml.y - mx1) * cs);
      m0 = mx0; m1 = mx1;
      l0 = l0 * a0 + ml.z * b0; l1 = l1 * a1 + ml.w * b1;
#pragma unroll
      for (int i = 0; i < 24; i++) {
        const float4 v = __ldcg(src + i * 128);
        oacc[4 * i] = oacc[4 * i] * a0 + v.x * b0; oacc[4 * i + 1] = oacc[4 * i + 1] * a0 + v.y * b0;
        oacc[4 * i + 2] = oacc[4 * i + 2] * a1 + v.z * b1; oacc[4 * i + 3] = oacc[4 * i + 3] * a1 + v.w * b1;
      }
    }
  }
  TS(1, 21);
  l0 += __shfl_xor_sync(0xffffffffu, l0, 1); l0 += __shfl_xor_sync(0xffffffffu, l0, 2);
  l1 += __shfl_xor_sync(0xffffffffu, l1, 1); l1 += __shfl_xor_sync(0xffffffffu, l1, 2);
  const float i0 = 1.f / l0, i1 = 1.f / l1;
  mbar_wait(bQF, 1);
  const FragAddr fa(wq, lane);
#pragma unroll
  for (int c = 0; c < 3; c++) resid_chunk(nullptr, &oacc[32 * c], i0, i1, qb + c * 16384, fa);
  fence_proxy_async();
  named_bar(1 + wg, 128);
  TS(1, 22);
  if (wtid == 0) {
    const int t = seg_tile[0] / 11, qt = seg_tile[0] - t * 11;
    if (qt * 128 + wg * 64 < NL) {
      for (int c = 0; c < 3; c++) tma_store_3d(&tm_out, qb + c * 16384, c * 64, qt * 128 + wg * 64, t);
      bulk_commit();
      bulk_wait0();
    }
  }
  TS(1, 23);
}

typedef CUresult (*EncodeFn)(CUtensorMap*, CUtensorMapDataType, cuuint32_t, void*, const cuuint64_t*, const cuuint64_t*,
                             const cuuint32_t*, const cuuint32_t*, CUtensorMapInterleave, CUtensorMapSwizzle,
                             CUtensorMapL2promotion, CUtensorMapFloatOOBfill);

void make_map(EncodeFn enc, CUtensorMap* m, const void* ptr, int rank, const uint64_t* dims, const uint32_t* box) {
  cuuint64_t gd[3], gs[2];
  cuuint32_t bx[3], es[3] = {1, 1, 1};
  uint64_t stride = 2;
  for (int i = 0; i < rank; i++) {
    gd[i] = dims[i]; bx[i] = box[i];
    stride *= dims[i];
    if (i < rank - 1) gs[i] = stride;
  }
  enc(m, CU_TENSOR_MAP_DATA_TYPE_BFLOAT16, rank, const_cast<void*>(ptr), gd, gs, bx, es, CU_TENSOR_MAP_INTERLEAVE_NONE,
      CU_TENSOR_MAP_SWIZZLE_128B, CU_TENSOR_MAP_L2_PROMOTION_L2_256B, CU_TENSOR_MAP_FLOAT_OOB_FILL_NONE);
}

}

extern "C" void kernel_launch(void* const* d_in, const int* in_sizes, int n_in, void* d_out, int out_size) {
  (void)in_sizes; (void)n_in; (void)out_size;
  EncodeFn enc = nullptr;
  cudaDriverEntryPointQueryResult qres;
  cudaGetDriverEntryPoint("cuTensorMapEncodeTiled", (void**)&enc, cudaEnableDefault, &qres);
  void *p_x1, *p_qkv, *p_wf;
  cudaGetSymbolAddress(&p_wf, g_wf);
  cudaGetSymbolAddress(&p_x1, g_x1);
  cudaGetSymbolAddress(&p_qkv, g_qkv);
  cudaFuncSetAttribute(kernelA, cudaFuncAttributeMaxDynamicSharedMemorySize, A_SMEM);
  cudaFuncSetAttribute(kernelB, cudaFuncAttributeMaxDynamicSharedMemorySize, B_SMEM);

  CUtensorMap tm_x, tm_wqkvt, tm_wot, tm_wqkvs, tm_x1s, tm_qkvs, tm_q, tm_kv, tm_wos, tm_x1l, tm_out, tm_wf;
  const uint64_t d_act[3] = {192, 1296, 7}, d_qkv[3] = {576, 1296, 7}, d_w3[2] = {576, 192}, d_w1[2] = {192, 192}, d_wf[2] = {384, 384};
  const uint32_t b_a[3] = {64, 9, 7}, b_w[2] = {64, 192}, b_q[3] = {64, 128, 1}, b_kv[3] = {64, 144, 1}, b_o[3] = {64, 64, 1}, b_w64[2] = {64, 64};
  make_map(enc, &tm_x, d_in[0], 3, d_act, b_a);
  make_map(enc, &tm_wqkvt, d_in[1], 2, d_w3, b_w64);
  make_map(enc, &tm_wot, d_in[2], 2, d_w1, b_w);
  make_map(enc, &tm_wqkvs, d_in[3], 2, d_w3, b_w64);
  make_map(enc, &tm_wos, d_in[4], 2, d_w1, b_w);
  make_map(enc, &tm_wf, p_wf, 2, d_wf, b_w);
  make_map(enc, &tm_x1s, p_x1, 3, d_act, b_a);
  make_map(enc, &tm_qkvs, p_qkv, 3, d_qkv, b_a);
  make_map(enc, &tm_q, p_qkv, 3, d_qkv, b_q);
  make_map(enc, &tm_kv, p_qkv, 3, d_qkv, b_kv);
  make_map(enc, &tm_x1l, p_x1, 3, d_act, b_q);
  make_map(enc, &tm_out, d_out, 3, d_act, b_o);

  kernelA<<<72 + A_FOLD, 384, A_SMEM>>>(tm_x, tm_wqkvt, tm_wot, tm_wqkvs, tm_wos, tm_wf, tm_x1s, tm_qkvs);
  kernelB<<<B_GRID, 384, B_SMEM>>>(tm_q, tm_kv, tm_x1l, tm_out);
}
```

```cpp
#include <cuda_runtime.h>
#include <cuda_bf16.h>
#include <cuda.h>
#include <stdint.h>

namespace {

constexpr int TT = 7, NL = 1296, CC = 192;

__device__ __align__(1024) __nv_bfloat16 g_x1[TT * NL * CC];
__device__ __align__(1024) __nv_bfloat16 g_qkv[TT * NL * 3 * CC];
__device__ __align__(1024) __nv_bfloat16 g_wf[2 * CC * 2 * CC];
__device__ __align__(1024) float4 g_part[110 * 2 * 25 * 128];
__device__ unsigned int g_flag[128];
__device__ unsigned int g_wflag[4];

#define TS(k, i)

__device__ __forceinline__ uint32_t smem_u32(const void* p) { return (uint32_t)__cvta_generic_to_shared(p); }
__device__ __forceinline__ void mbar_init(uint32_t bar, uint32_t cnt) {
  asm volatile("mbarrier.init.shared::cta.b64 [%0], %1;" ::"r"(bar), "r"(cnt));
}
__device__ __forceinline__ void mbar_expect_tx(uint32_t bar, uint32_t bytes) {
  asm volatile("mbarrier.arrive.expect_tx.shared::cta.b64 _, [%0], %1;" ::"r"(bar), "r"(bytes) : "memory");
}
__device__ __forceinline__ void mbar_arrive(uint32_t bar) {
  asm volatile("mbarrier.arrive.shared::cta.b64 _, [%0];" ::"r"(bar) : "memory");
}
__device__ __forceinline__ bool mbar_try(uint32_t bar, uint32_t parity) {
  uint32_t ok;
  asm volatile("{\n.reg .pred p;\nmbarrier.try_wait.parity.shared::cta.b64 p, [%1], %2;\nselp.u32 %0, 1, 0, p;\n}"
               : "=r"(ok) : "r"(bar), "r"(parity) : "memory");
  return ok != 0;
}
__device__ __forceinline__ void mbar_wait(uint32_t bar, uint32_t parity) {
  if (mbar_try(bar, parity)) return;
  uint32_t n = 0;
  while (!mbar_try(bar, parity)) {
    if (++n > (1u << 22)) break;
  }
}
__device__ __forceinline__ void tma_load_2d(uint32_t dst, const CUtensorMap* m, uint32_t bar, int c0, int c1) {
  asm volatile("cp.async.bulk.tensor.2d.shared::cluster.global.mbarrier::complete_tx::bytes [%0], [%1, {%3, %4}], [%2];"
               ::"r"(dst), "l"(m), "r"(bar), "r"(c0), "r"(c1) : "memory");
}
__device__ __forceinline__ void tma_load_3d(uint32_t dst, const CUtensorMap* m, uint32_t bar, int c0, int c1, int c2) {
  asm volatile("cp.async.bulk.tensor.3d.shared::cluster.global.mbarrier::complete_tx::bytes [%0], [%1, {%3, %4, %5}], [%2];"
               ::"r"(dst), "l"(m), "r"(bar), "r"(c0), "r"(c1), "r"(c2) : "memory");
}
__device__ __forceinline__ void tma_store_3d(const CUtensorMap* m, uint32_t src, int c0, int c1, int c2) {
  asm volatile("cp.async.bulk.tensor.3d.global.shared::cta.bulk_group [%0, {%2, %3, %4}], [%1];"
               ::"l"(m), "r"(src), "r"(c0), "r"(c1), "r"(c2) : "memory");
}
__device__ __forceinline__ void bulk_commit() { asm volatile("cp.async.bulk.commit_group;" ::: "memory"); }
__device__ __forceinline__ void bulk_wait_read0() { asm volatile("cp.async.bulk.wait_group.read 0;" ::: "memory"); }
__device__ __forceinline__ void bulk_wait0() { asm volatile("cp.async.bulk.wait_group 0;" ::: "memory"); }
__device__ __forceinline__ void fence_proxy_async() { asm volatile("fence.proxy.async.shared::cta;" ::: "memory"); }
__device__ __forceinline__ void prefetch_tmap(const CUtensorMap* m) {
  asm volatile("prefetch.tensormap [%0];" ::"l"(m) : "memory");
}
__device__ __forceinline__ void wg_fence() { asm volatile("wgmma.fence.sync.aligned;" ::: "memory"); }
__device__ __forceinline__ void wg_commit() { asm volatile("wgmma.commit_group.sync.aligned;" ::: "memory"); }
template <int N> __device__ __forceinline__ void wg_wait() { asm volatile("wgmma.wait_group.sync.aligned %0;" ::"n"(N) : "memory"); }
__device__ __forceinline__ void named_bar(int id, int nthreads) {
  asm volatile("bar.sync %0, %1;" ::"r"(id), "r"(nthreads) : "memory");
}
__device__ __forceinline__ void ldsm_x4(uint32_t (&r)[4], uint32_t addr) {
  asm volatile("ldmatrix.sync.aligned.m8n8.x4.shared.b16 {%0,%1,%2,%3}, [%4];"
               : "=r"(r[0]), "=r"(r[1]), "=r"(r[2]), "=r"(r[3]) : "r"(addr) : "memory");
}
__device__ __forceinline__ void stsm_x4(uint32_t addr, const uint32_t (&r)[4]) {
  asm volatile("stmatrix.sync.aligned.m8n8.x4.shared.b16 [%0], {%1,%2,%3,%4};"
               ::"r"(addr), "r"(r[0]), "r"(r[1]), "r"(r[2]), "r"(r[3]) : "memory");
}
__device__ __forceinline__ uint32_t pack_bf16(float lo, float hi) {
  uint32_t r;
  asm("cvt.rn.bf16x2.f32 %0, %1, %2;" : "=r"(r) : "f"(hi), "f"(lo));
  return r;
}
__device__ __forceinline__ float bf_lo(uint32_t v) { return __uint_as_float(v << 16); }
__device__ __forceinline__ float bf_hi(uint32_t v) { return __uint_as_float(v & 0xffff0000u); }
__device__ __forceinline__ float ex2(float x) {
  float y;
  asm("ex2.approx.ftz.f32 %0, %1;" : "=f"(y) : "f"(x));
  return y;
}
__device__ __forceinline__ uint64_t mk_desc(uint32_t addr, uint32_t lbo, uint32_t sbo) {
  return (uint64_t)((addr & 0x3FFFF) >> 4) | ((uint64_t)((lbo & 0x3FFFF) >> 4) << 16) |
         ((uint64_t)((sbo & 0x3FFFF) >> 4) << 32) | (1ull << 62);
}
__device__ __forceinline__ uint64_t mk_desc_o(uint32_t addr, uint32_t lbo, uint32_t sbo) {
  asm volatile("" : "+r"(addr));
  return mk_desc(addr, lbo, sbo);
}
template <int N> __device__ __forceinline__ void reg_fence(float (&d)[N]) {
#pragma unroll
  for (int i = 0; i < N; i++) asm volatile("" : "+f"(d[i])::"memory");
}

template<int TB> __device__ __forceinline__ void wgmma_n144_ss(float (&d)[72], uint64_t da, uint64_t db, int sc) {
  asm volatile("{\n.reg .pred p;\nsetp.ne.b32 p, %74, 0;\n"
    "wgmma.mma_async.sync.aligned.m64n144k16.f32.bf16.bf16 {%0, %1, %2, %3, %4, %5, %6, %7, %8, %9, %10, %11, %12, %13, %14, %15, %16, %17, %18, %19, %20, %21, %22, %23, %24, %25, %26, %27, %28, %29, %30, %31, %32, %33, %34, %35, %36, %37, %38, %39, %40, %41, %42, %43, %44, %45, %46, %47, %48, %49, %50, %51, %52, %53, %54, %55, %56, %57, %58, %59, %60, %61, %62, %63, %64, %65, %66, %67, %68, %69, %70, %71}, %72, %73, p, 1, 1, 0, %75;\n}\n"
    : "+f"(d[0]), "+f"(d[1]), "+f"(d[2]), "+f"(d[3]), "+f"(d[4]), "+f"(d[5]), "+f"(d[6]), "+f"(d[7]), "+f"(d[8]), "+f"(d[9]), "+f"(d[10]), "+f"(d[11]), "+f"(d[12]), "+f"(d[13]), "+f"(d[14]), "+f"(d[15]), "+f"(d[16]), "+f"(d[17]), "+f"(d[18]), "+f"(d[19]), "+f"(d[20]), "+f"(d[21]), "+f"(d[22]), "+f"(d[23]), "+f"(d[24]), "+f"(d[25]), "+f"(d[26]), "+f"(d[27]), "+f"(d[28]), "+f"(d[29]), "+f"(d[30]), "+f"(d[31]), "+f"(d[32]), "+f"(d[33]), "+f"(d[34]), "+f"(d[35]), "+f"(d[36]), "+f"(d[37]), "+f"(d[38]), "+f"(d[39]), "+f"(d[40]), "+f"(d[41]), "+f"(d[42]), "+f"(d[43]), "+f"(d[44]), "+f"(d[45]), "+f"(d[46]), "+f"(d[47]), "+f"(d[48]), "+f"(d[49]), "+f"(d[50]), "+f"(d[51]), "+f"(d[52]), "+f"(d[53]), "+f"(d[54]), "+f"(d[55]), "+f"(d[56]), "+f"(d[57]), "+f"(d[58]), "+f"(d[59]), "+f"(d[60]), "+f"(d[61]), "+f"(d[62]), "+f"(d[63]), "+f"(d[64]), "+f"(d[65]), "+f"(d[66]), "+f"(d[67]), "+f"(d[68]), "+f"(d[69]), "+f"(d[70]), "+f"(d[71])
    : "l"(da), "l"(db), "r"(sc), "n"(TB));
}
template<int TB> __device__ __forceinline__ void wgmma_n192_rs(float (&d)[96], const uint32_t (&a)[4], uint64_t db, int sc) {
  asm volatile("{\n.reg .pred p;\nsetp.ne.b32 p, %101, 0;\n"
    "wgmma.mma_async.sync.aligned.m64n192k16.f32.bf16.bf16 {%0, %1, %2, %3, %4, %5, %6, %7, %8, %9, %10, %11, %12, %13, %14, %15, %16, %17, %18, %19, %20, %21, %22, %23, %24, %25, %26, %27, %28, %29, %30, %31, %32, %33, %34, %35, %36, %37, %38, %39, %40, %41, %42, %43, %44, %45, %46, %47, %48, %49, %50, %51, %52, %53, %54, %55, %56, %57, %58, %59, %60, %61, %62, %63, %64, %65, %66, %67, %68, %69, %70, %71, %72, %73, %74, %75, %76, %77, %78, %79, %80, %81, %82, %83, %84, %85, %86, %87, %88, %89, %90, %91, %92, %93, %94, %95}, {%96, %97, %98, %99}, %100, p, 1, 1, %102;\n}\n"
    : "+f"(d[0]), "+f"(d[1]), "+f"(d[2]), "+f"(d[3]), "+f"(d[4]), "+f"(d[5]), "+f"(d[6]), "+f"(d[7]), "+f"(d[8]), "+f"(d[9]), "+f"(d[10]), "+f"(d[11]), "+f"(d[12]), "+f"(d[13]), "+f"(d[14]), "+f"(d[15]), "+f"(d[16]), "+f"(d[17]), "+f"(d[18]), "+f"(d[19]), "+f"(d[20]), "+f"(d[21]), "+f"(d[22]), "+f"(d[23]), "+f"(d[24]), "+f"(d[25]), "+f"(d[26]), "+f"(d[27]), "+f"(d[28]), "+f"(d[29]), "+f"(d[30]), "+f"(d[31]), "+f"(d[32]), "+f"(d[33]), "+f"(d[34]), "+f"(d[35]), "+f"(d[36]), "+f"(d[37]), "+f"(d[38]), "+f"(d[39]), "+f"(d[40]), "+f"(d[41]), "+f"(d[42]), "+f"(d[43]), "+f"(d[44]), "+f"(d[45]), "+f"(d[46]), "+f"(d[47]), "+f"(d[48]), "+f"(d[49]), "+f"(d[50]), "+f"(d[51]), "+f"(d[52]), "+f"(d[53]), "+f"(d[54]), "+f"(d[55]), "+f"(d[56]), "+f"(d[57]), "+f"(d[58]), "+f"(d[59]), "+f"(d[60]), "+f"(d[61]), "+f"(d[62]), "+f"(d[63]), "+f"(d[64]), "+f"(d[65]), "+f"(d[66]), "+f"(d[67]), "+f"(d[68]), "+f"(d[69]), "+f"(d[70]), "+f"(d[71]), "+f"(d[72]), "+f"(d[73]), "+f"(d[74]), "+f"(d[75]), "+f"(d[76]), "+f"(d[77]), "+f"(d[78]), "+f"(d[79]), "+f"(d[80]), "+f"(d[81]), "+f"(d[82]), "+f"(d[83]), "+f"(d[84]), "+f"(d[85]), "+f"(d[86]), "+f"(d[87]), "+f"(d[88]), "+f"(d[89]), "+f"(d[90]), "+f"(d[91]), "+f"(d[92]), "+f"(d[93]), "+f"(d[94]), "+f"(d[95])
    : "r"(a[0]), "r"(a[1]), "r"(a[2]), "r"(a[3]), "l"(db), "r"(sc), "n"(TB));
}
template<int TB> __device__ __forceinline__ void wgmma_n64_rs(float (&d)[32], const uint32_t (&a)[4], uint64_t db, int sc) {
  asm volatile("{\n.reg .pred p;\nsetp.ne.b32 p, %37, 0;\n"
    "wgmma.mma_async.sync.aligned.m64n64k16.f32.bf16.bf16 {%0, %1, %2, %3, %4, %5, %6, %7, %8, %9, %10, %11, %12, %13, %14, %15, %16, %17, %18, %19, %20, %21, %22, %23, %24, %25, %26, %27, %28, %29, %30, %31}, {%32, %33, %34, %35}, %36, p, 1, 1, %38;\n}\n"
    : "+f"(d[0]), "+f"(d[1]), "+f"(d[2]), "+f"(d[3]), "+f"(d[4]), "+f"(d[5]), "+f"(d[6]), "+f"(d[7]), "+f"(d[8]), "+f"(d[9]), "+f"(d[10]), "+f"(d[11]), "+f"(d[12]), "+f"(d[13]), "+f"(d[14]), "+f"(d[15]), "+f"(d[16]), "+f"(d[17]), "+f"(d[18]), "+f"(d[19]), "+f"(d[20]), "+f"(d[21]), "+f"(d[22]), "+f"(d[23]), "+f"(d[24]), "+f"(d[25]), "+f"(d[26]), "+f"(d[27]), "+f"(d[28]), "+f"(d[29]), "+f"(d[30]), "+f"(d[31])
    : "r"(a[0]), "r"(a[1]), "r"(a[2]), "r"(a[3]), "l"(db), "r"(sc), "n"(TB));
}
template<int TB> __device__ __forceinline__ void wgmma_n64_ss(float (&d)[32], uint64_t da, uint64_t db, int sc) {
  asm volatile("{\n.reg .pred p;\nsetp.ne.b32 p, %34, 0;\n"
    "wgmma.mma_async.sync.aligned.m64n64k16.f32.bf16.bf16 {%0, %1, %2, %3, %4, %5, %6, %7, %8, %9, %10, %11, %12, %13, %14, %15, %16, %17, %18, %19, %20, %21, %22, %23, %24, %25, %26, %27, %28, %29, %30, %31}, %32, %33, p, 1, 1, 0, %35;\n}\n"
    : "+f"(d[0]), "+f"(d[1]), "+f"(d[2]), "+f"(d[3]), "+f"(d[4]), "+f"(d[5]), "+f"(d[6]), "+f"(d[7]), "+f"(d[8]), "+f"(d[9]), "+f"(d[10]), "+f"(d[11]), "+f"(d[12]), "+f"(d[13]), "+f"(d[14]), "+f"(d[15]), "+f"(d[16]), "+f"(d[17]), "+f"(d[18]), "+f"(d[19]), "+f"(d[20]), "+f"(d[21]), "+f"(d[22]), "+f"(d[23]), "+f"(d[24]), "+f"(d[25]), "+f"(d[26]), "+f"(d[27]), "+f"(d[28]), "+f"(d[29]), "+f"(d[30]), "+f"(d[31])
    : "l"(da), "l"(db), "r"(sc), "n"(TB));
}

struct FragAddr {
  uint32_t rowoff;
  uint32_t rx;
  uint32_t hi;
  __device__ __forceinline__ FragAddr(int warp_in_wg, int lane) {
    int row = 16 * warp_in_wg + (lane & 7) + ((lane >> 3) & 1) * 8;
    rowoff = row * 128;
    rx = row & 7;
    hi = lane >> 4;
  }
  __device__ __forceinline__ uint32_t at(uint32_t chunk_base, int kk4) const {
    return chunk_base + rowoff + ((((uint32_t)kk4 * 2 + hi) ^ rx) << 4);
  }
};

__device__ __forceinline__ void layernorm_frags(uint32_t (&f)[12][4]) {
  float s0 = 0.f, s1 = 0.f;
#pragma unroll
  for (int k = 0; k < 12; k++) {
    s0 += bf_lo(f[k][0]) + bf_hi(f[k][0]) + bf_lo(f[k][2]) + bf_hi(f[k][2]);
    s1 += bf_lo(f[k][1]) + bf_hi(f[k][1]) + bf_lo(f[k][3]) + bf_hi(f[k][3]);
  }
  s0 += __shfl_xor_sync(0xffffffffu, s0, 1); s0 += __shfl_xor_sync(0xffffffffu, s0, 2);
  s1 += __shfl_xor_sync(0xffffffffu, s1, 1); s1 += __shfl_xor_sync(0xffffffffu, s1, 2);
  const float m0 = s0 * (1.f / 192.f), m1 = s1 * (1.f / 192.f);
  float v0 = 0.f, v1 = 0.f;
#pragma unroll
  for (int k = 0; k < 12; k++) {
    float a;
    a = bf_lo(f[k][0]) - m0; v0 += a * a; a = bf_hi(f[k][0]) - m0; v0 += a * a;
    a = bf_lo(f[k][2]) - m0; v0 += a * a; a = bf_hi(f[k][2]) - m0; v0 += a * a;
    a = bf_lo(f[k][1]) - m1; v1 += a * a; a = bf_hi(f[k][1]) - m1; v1 += a * a;
    a = bf_lo(f[k][3]) - m1; v1 += a * a; a = bf_hi(f[k][3]) - m1; v1 += a * a;
  }
  v0 += __shfl_xor_sync(0xffffffffu, v0, 1); v0 += __shfl_xor_sync(0xffffffffu, v0, 2);
  v1 += __shfl_xor_sync(0xffffffffu, v1, 1); v1 += __shfl_xor_sync(0xffffffffu, v1, 2);
  const float r0 = rsqrtf(v0 * (1.f / 192.f) + 1e-5f), r1 = rsqrtf(v1 * (1.f / 192.f) + 1e-5f);
#pragma unroll
  for (int k = 0; k < 12; k++) {
    f[k][0] = pack_bf16((bf_lo(f[k][0]) - m0) * r0, (bf_hi(f[k][0]) - m0) * r0);
    f[k][2] = pack_bf16((bf_lo(f[k][2]) - m0) * r0, (bf_hi(f[k][2]) - m0) * r0);
    f[k][1] = pack_bf16((bf_lo(f[k][1]) - m1) * r1, (bf_hi(f[k][1]) - m1) * r1);
    f[k][3] = pack_bf16((bf_lo(f[k][3]) - m1) * r1, (bf_hi(f[k][3]) - m1) * r1);
  }
}

constexpr int A_NST = 5;
constexpr int A_XS = 0;
constexpr int A_VB = 49152;
constexpr int A_W = 98304;
constexpr int A_BAR = A_W + A_NST * 24576;
constexpr int A_SMEM = A_BAR + 256 + 1024;
constexpr int A_FOLD = 36;

__device__ __forceinline__ void a_issue(float (&acc)[32], const uint32_t (&af)[12][4], uint32_t sb, int s) {
  const int st = s % A_NST;
  mbar_wait(sb + A_BAR + st * 8, (s / A_NST) & 1);
  const uint64_t wd = mk_desc_o(sb + A_W + st * 24576, 8192, 1024);
  wg_fence();
#pragma unroll
  for (int kk = 0; kk < 12; kk++) wgmma_n64_rs<1>(acc, af[kk], wd + kk * 128, kk > 0);
  wg_commit();
}
__device__ __forceinline__ void a_release(uint32_t sb, int s, int lane) {
  if (lane == 0) mbar_arrive(sb + A_BAR + 64 + (s % A_NST) * 8);
}
__device__ __forceinline__ void cvt_frags(uint32_t (*dst)[4], const float (&acc)[32]) {
#pragma unroll
  for (int k = 0; k < 4; k++) {
    dst[k][0] = pack_bf16(acc[8 * k + 0], acc[8 * k + 1]);
    dst[k][1] = pack_bf16(acc[8 * k + 2], acc[8 * k + 3]);
    dst[k][2] = pack_bf16(acc[8 * k + 4], acc[8 * k + 5]);
    dst[k][3] = pack_bf16(acc[8 * k + 6], acc[8 * k + 7]);
  }
}
__device__ __forceinline__ void store_chunk(const float (&acc)[32], uint32_t chunk_base, const FragAddr& fa) {
  uint32_t t[4][4];
  cvt_frags(t, acc);
#pragma unroll
  for (int k = 0; k < 4; k++) stsm_x4(fa.at(chunk_base, k), t[k]);
}
__device__ __forceinline__ void resid_chunk(uint32_t (*dst)[4], const float* acc, float s0, float s1, uint32_t chunk_base,
                                            const FragAddr& fa) {
#pragma unroll
  for (int k = 0; k < 4; k++) {
    uint32_t x[4];
    ldsm_x4(x, fa.at(chunk_base, k));
    uint32_t o[4];
    o[0] = pack_bf16(fmaf(acc[8 * k + 0], s0, bf_lo(x[0])), fmaf(acc[8 * k + 1], s0, bf_hi(x[0])));
    o[1] = pack_bf16(fmaf(acc[8 * k + 2], s1, bf_lo(x[1])), fmaf(acc[8 * k + 3], s1, bf_hi(x[1])));
    o[2] = pack_bf16(fmaf(acc[8 * k + 4], s0, bf_lo(x[2])), fmaf(acc[8 * k + 5], s0, bf_hi(x[2])));
    o[3] = pack_bf16(fmaf(acc[8 * k + 6], s1, bf_lo(x[3])), fmaf(acc[8 * k + 7], s1, bf_hi(x[3])));
    stsm_x4(fa.at(chunk_base, k), o);
    if (dst) { dst[k][0] = o[0]; dst[k][1] = o[1]; dst[k][2] = o[2]; dst[k][3] = o[3]; }
  }
}

__global__ void __launch_bounds__(384, 1)
kernelA(const __grid_constant__ CUtensorMap tm_x, const __grid_constant__ CUtensorMap tm_wq64t,
        const __grid_constant__ CUtensorMap tm_wot, const __grid_constant__ CUtensorMap tm_wq64s,
        const __grid_constant__ CUtensorMap tm_wos, const __grid_constant__ CUtensorMap tm_wf,
        const __grid_constant__ CUtensorMap tm_x1, const __grid_constant__ CUtensorMap tm_qkv) {
  extern __shared__ uint8_t smem_raw[];
  const uint32_t sb = (smem_u32(smem_raw) + 1023) & ~1023u;
  const int tid = threadIdx.x, warp = tid >> 5, lane = tid & 31;
  const bool is_fold = blockIdx.x < A_FOLD;
  const int blk = blockIdx.x - A_FOLD;
  if (tid == 256) {
    for (int i = 0; i < A_NST; i++) { mbar_init(sb + A_BAR + i * 8, 1); mbar_init(sb + A_BAR + 64 + i * 8, 8); }
    mbar_init(sb + A_BAR + 128, 1); mbar_init(sb + A_BAR + 136, 1);
    asm volatile("fence.mbarrier_init.release.cluster;" ::: "memory");
    if (!is_fold) {
      for (int w = 0; w < 2; w++) {
        const uint32_t bar = sb + A_BAR + 128 + w * 8;
        mbar_expect_tx(bar, 3 * 63 * 128);
        for (int c = 0; c < 3; c++)
          tma_load_3d(sb + A_XS + w * 24576 + c * 8192, &tm_x, bar, c * 64, (blk * 2 + w) * 9, 0);
      }
    } else {
      const int mat = blockIdx.x / 9, rs = (blockIdx.x % 9) / 3, cs = blockIdx.x % 3;
      const CUtensorMap* mq = (mat < 2) ? &tm_wq64t : &tm_wq64s;
      const CUtensorMap* mo = (mat < 2) ? &tm_wot : &tm_wos;
      const uint32_t bar = sb + A_BAR + 128;
      mbar_expect_tx(bar, 2 * 24576);
      for (int c = 0; c < 3; c++) tma_load_2d(sb + c * 8192, mq, bar, ((mat & 1) ? 384 : 0) + c * 64, rs * 64);
      if (mat & 1) tma_load_2d(sb + 24576, mo, bar, cs * 64, 0);
      else for (int c = 0; c < 3; c++) tma_load_2d(sb + 24576 + c * 8192, mq, bar, 192 + c * 64, cs * 64);
    }
  }
  if (blockIdx.x == 0 && tid < 128) g_flag[tid] = 0;
  if (!is_fold && tid < 48) {
    uint32_t a = sb + A_XS + (tid >> 3) * 8192 + 63 * 128 + (tid & 7) * 16;
    asm volatile("st.shared.v4.b32 [%0], {%1,%1,%1,%1};" ::"r"(a), "r"(0) : "memory");
  }
  __syncthreads();

  if (warp >= 8) {
    asm volatile("setmaxnreg.dec.sync.aligned.u32 24;");
    if (warp == 8 && lane == 0 && !is_fold) {
      for (int s = 0; s < 12; s++) {
        const int st = s % A_NST;
        const int g = s / 3;
        const int mat = (g == 0) ? 1 : (g == 1) ? 0 : g;
        if (s % 3 == 0) {
          uint32_t n = 0, v;
          do {
            asm volatile("ld.acquire.gpu.global.u32 %0, [%1];" : "=r"(v) : "l"(&g_wflag[mat]) : "memory");
          } while (v < 9u && ++n < (1u << 22));
          asm volatile("fence.proxy.async;" ::: "memory");
        }
        if (s >= A_NST) mbar_wait(sb + A_BAR + 64 + st * 8, ((s / A_NST) - 1) & 1);
        mbar_expect_tx(sb + A_BAR + st * 8, 24576);
        tma_load_2d(sb + A_W + st * 24576, &tm_wf, sb + A_BAR + st * 8, (mat & 1) * 192 + (s % 3) * 64, (mat >> 1) * 192);
      }
    }
    return;
  }

  asm volatile("setmaxnreg.inc.sync.aligned.u32 240;");
  const int wg = warp >> 2, wq = warp & 3;

  if (is_fold) {
    if (wg == 0) {
      const int mat = blockIdx.x / 9, rs = (blockIdx.x % 9) / 3, cs = blockIdx.x % 3;
      float d[32];
      mbar_wait(sb + A_BAR + 128, 0);
      const uint64_t ad = mk_desc_o(sb, 16, 1024);
      if (mat & 1) {
        const uint64_t bd = mk_desc_o(sb + 24576, 8192, 1024);
        wg_fence();
#pragma unroll
        for (int kk = 0; kk < 12; kk++) wgmma_n64_ss<1>(d, ad + (kk >> 2) * 512 + (kk & 3) * 2, bd + kk * 128, kk > 0);
        wg_commit();
      } else {
        const uint64_t bd = mk_desc_o(sb + 24576, 16, 1024);
        wg_fence();
#pragma unroll
        for (int kk = 0; kk < 12; kk++)
          wgmma_n64_ss<0>(d, ad + (kk >> 2) * 512 + (kk & 3) * 2, bd + (kk >> 2) * 512 + (kk & 3) * 2, kk > 0);
        wg_commit();
      }
      wg_wait<0>(); reg_fence(d);
      const int r0 = rs * 64 + wq * 16 + (lane >> 2);
      uint32_t* dst = reinterpret_cast<uint32_t*>(g_wf + ((size_t)(mat >> 1) * 192 + r0) * 384 + (mat & 1) * 192 + cs * 64 + (lane & 3) * 2);
#pragma unroll
      for (int j = 0; j < 8; j++) {
        dst[j * 4] = pack_bf16(d[4 * j], d[4 * j + 1]);
        dst[8 * 192 + j * 4] = pack_bf16(d[4 * j + 2], d[4 * j + 3]);
      }
      asm volatile("fence.proxy.async;" ::: "memory");
      __threadfence();
      named_bar(1, 128);
      if (tid == 0) atomicAdd(&g_wflag[mat], 1u);
    }
    return;
  }

  const int n0 = (blk * 2 + wg) * 9;
  const FragAddr fa(wq, lane);
  const uint32_t xs = sb + A_XS + wg * 24576, vb = sb + A_VB + wg * 24576;
  const int barid = 1 + wg;
  const bool elected = (tid & 127) == 0;

  uint32_t h[12][4];
  TS(0, 0);
  mbar_wait(sb + A_BAR + 128 + wg * 8, 0);
  TS(0, 1);
#pragma unroll
  for (int k = 0; k < 12; k++) ldsm_x4(h[k], fa.at(xs + (k >> 2) * 8192, k & 3));
  layernorm_frags(h);
#pragma unroll
  for (int k = 0; k < 12; k++) stsm_x4(fa.at(xs + (k >> 2) * 8192, k & 3), h[k]);

  float acc0[32], acc1[32];
  uint32_t qf[12][4];
  TS(0, 2);
  a_issue(acc0, h, sb, 0);
  TS(0, 3);
  a_issue(acc1, h, sb, 1); wg_wait<1>(); reg_fence(acc0); a_release(sb, 0, lane); store_chunk(acc0, vb, fa);
  a_issue(acc0, h, sb, 2); wg_wait<1>(); reg_fence(acc1); a_release(sb, 1, lane); store_chunk(acc1, vb + 8192, fa);
  a_issue(acc1, h, sb, 3); wg_wait<1>(); reg_fence(acc0); a_release(sb, 2, lane); store_chunk(acc0, vb + 16384, fa);
  fence_proxy_async();
  named_bar(barid, 128);
  a_issue(acc0, h, sb, 4); wg_wait<1>(); reg_fence(acc1); a_release(sb, 3, lane); cvt_frags(&qf[0], acc1);
  a_issue(acc1, h, sb, 5); wg_wait<1>(); reg_fence(acc0); a_release(sb, 4, lane); cvt_frags(&qf[4], acc0);
  wg_wait<0>(); reg_fence(acc1); a_release(sb, 5, lane); cvt_frags(&qf[8], acc1);
  TS(0, 4);
  {
    const uint64_t kd = mk_desc_o(xs, 16, 1024);
    wg_fence();
#pragma unroll
    for (int kk = 0; kk < 12; kk++) wgmma_n64_rs<0>(acc0, qf[kk], kd + (kk >> 2) * 512 + (kk & 3) * 2, kk > 0);
    wg_commit();
    wg_wait<0>(); reg_fence(acc0);
  }
  named_bar(barid, 128);
  if (elected) {
    const uint32_t bar = sb + A_BAR + 128 + wg * 8;
    mbar_expect_tx(bar, 3 * 63 * 128);
    for (int c = 0; c < 3; c++) tma_load_3d(xs + c * 8192, &tm_x, bar, c * 64, n0, 0);
  }
  uint32_t pf[4][4];
  {
    const int r0 = 16 * wq + (lane >> 2), r1 = r0 + 8;
    const unsigned long long MB = 0x0040201008040201ull;
    const unsigned long long mk0 = (MB << (r0 % 9)) >> (2 * (lane & 3));
    const unsigned long long mk1 = (MB << (r1 % 9)) >> (2 * (lane & 3));
    const float cs = 0.07216878364870322f * 1.4426950408889634f;
    float mx0 = -INFINITY, mx1 = -INFINITY;
#pragma unroll
    for (int j = 0; j < 8; j++) {
#pragma unroll
      for (int e = 0; e < 2; e++) {
        bool v0 = (mk0 >> (8 * j + e)) & 1, v1 = (mk1 >> (8 * j + e)) & 1;
        acc0[4 * j + e] = v0 ? acc0[4 * j + e] * cs : -INFINITY;
        acc0[4 * j + 2 + e] = v1 ? acc0[4 * j + 2 + e] * cs : -INFINITY;
        mx0 = fmaxf(mx0, acc0[4 * j + e]);
        mx1 = fmaxf(mx1, acc0[4 * j + 2 + e]);
      }
    }
    mx0 = fmaxf(mx0, __shfl_xor_sync(0xffffffffu, mx0, 1)); mx0 = fmaxf(mx0, __shfl_xor_sync(0xffffffffu, mx0, 2));
    mx1 = fmaxf(mx1, __shfl_xor_sync(0xffffffffu, mx1, 1)); mx1 = fmaxf(mx1, __shfl_xor_sync(0xffffffffu, mx1, 2));
    float l0 = 0.f, l1 = 0.f;
#pragma unroll
    for (int j = 0; j < 8; j++) {
#pragma unroll
      for (int e = 0; e < 2; e++) {
        acc0[4 * j + e] = ex2(acc0[4 * j + e] - mx0); l0 += acc0[4 * j + e];
        acc0[4 * j + 2 + e] = ex2(acc0[4 * j + 2 + e] - mx1); l1 += acc0[4 * j + 2 + e];
      }
    }
    l0 += __shfl_xor_sync(0xffffffffu, l0, 1); l0 += __shfl_xor_sync(0xffffffffu, l0, 2);
    l1 += __shfl_xor_sync(0xffffffffu, l1, 1); l1 += __shfl_xor_sync(0xffffffffu, l1, 2);
    const float i0 = 1.f / l0, i1 = 1.f / l1;
#pragma unroll
    for (int j = 0; j < 8; j++) {
      acc0[4 * j] *= i0; acc0[4 * j + 1] *= i0; acc0[4 * j + 2] *= i1; acc0[4 * j + 3] *= i1;
    }
    cvt_frags(pf, acc0);
  }
  TS(0, 5);
  {
    float oacc[96];
    const uint64_t vd = mk_desc_o(vb, 8192, 1024);
    wg_fence();
#pragma unroll
    for (int kk = 0; kk < 4; kk++) wgmma_n192_rs<1>(oacc, pf[kk], vd + kk * 128, kk > 0);
    wg_commit();
    wg_wait<0>(); reg_fence(oacc);
    TS(0, 6);
    mbar_wait(sb + A_BAR + 128 + wg * 8, 1);
#pragma unroll
    for (int c = 0; c < 3; c++) resid_chunk(&h[4 * c], &oacc[32 * c], 1.f, 1.f, xs + c * 8192, fa);
  }
  TS(0, 7);
  layernorm_frags(h);
  named_bar(barid, 128);
#pragma unroll
  for (int k = 0; k < 12; k++) stsm_x4(fa.at(vb + (k >> 2) * 8192, k & 3), h[k]);
  TS(0, 8);
  a_issue(acc0, h, sb, 6);
  fence_proxy_async();
  named_bar(barid, 128);
  if (elected) {
    for (int c = 0; c < 3; c++) tma_store_3d(&tm_x1, xs + c * 8192, c * 64, n0, 0);
    for (int c = 0; c < 3; c++) tma_store_3d(&tm_qkv, vb + c * 8192, 192 + c * 64, n0, 0);
    bulk_commit();
  }
  a_issue(acc1, h, sb, 7); wg_wait<1>(); reg_fence(acc0); a_release(sb, 6, lane);
  if (elected) bulk_wait_read0();
  named_bar(barid, 128);
  store_chunk(acc0, xs, fa);
  a_issue(acc0, h, sb, 8); wg_wait<1>(); reg_fence(acc1); store_chunk(acc1, xs + 8192, fa);
  a_issue(acc1, h, sb, 9); wg_wait<1>(); reg_fence(acc0); store_chunk(acc0, xs + 16384, fa);
  fence_proxy_async();
  named_bar(barid, 128);
  if (elected) {
    for (int c = 0; c < 3; c++) tma_store_3d(&tm_qkv, xs + c * 8192, c * 64, n0, 0);
    bulk_commit();
  }
  a_issue(acc0, h, sb, 10); wg_wait<1>(); reg_fence(acc1); store_chunk(acc1, vb, fa);
  a_issue(acc1, h, sb, 11); wg_wait<1>(); reg_fence(acc0); store_chunk(acc0, vb + 8192, fa);
  wg_wait<0>(); reg_fence(acc1); store_chunk(acc1, vb + 16384, fa);
  fence_proxy_async();
  named_bar(barid, 128);
  TS(0, 9);
  if (elected) {
    for (int c = 0; c < 3; c++) tma_store_3d(&tm_qkv, vb + c * 8192, 384 + c * 64, n0, 0);
    bulk_commit();
    bulk_wait0();
  }
  TS(0, 10);
}

constexpr int B_GRID = 132;
constexpr int B_SLOT = 55296;
constexpr int B_Q = 0;
constexpr int B_KV = 49152;
constexpr int B_BAR = B_KV + 3 * B_SLOT;
constexpr int B_SMEM = B_BAR + 256 + 1024;

__device__ __forceinline__ void bar_arrive(int id, int nthreads) {
  asm volatile("bar.arrive %0, %1;" ::"r"(id), "r"(nthreads) : "memory");
}

__global__ void __launch_bounds__(384, 1)
kernelB(const __grid_constant__ CUtensorMap tm_q, const __grid_constant__ CUtensorMap tm_kv,
        const __grid_constant__ CUtensorMap tm_x1, const __grid_constant__ CUtensorMap tm_out) {
  extern __shared__ uint8_t smem_raw[];
  const uint32_t sb = (smem_u32(smem_raw) + 1023) & ~1023u;
  const int tid = threadIdx.x, warp = tid >> 5, lane = tid & 31;
  const uint32_t bF = sb + B_BAR, bE = sb + B_BAR + 32, bQF = sb + B_BAR + 64, bQE = sb + B_BAR + 72;
  if (tid == 0) {
    for (int i = 0; i < 3; i++) { mbar_init(bF + i * 8, 1); mbar_init(bE + i * 8, 8); }
    mbar_init(bQF, 1); mbar_init(bQE, 8);
    asm volatile("fence.mbarrier_init.release.cluster;" ::: "memory");
  }
  __syncthreads();
  const int grp = blockIdx.x / 12, ci = blockIdx.x - grp * 12;
  const bool owner = ci < 7;
  int nseg, seg_tile[2], seg_k0[2], seg_k1[2];
  if (owner) {
    nseg = 1; seg_tile[0] = grp * 7 + ci; seg_k0[0] = 3; seg_k1[0] = 9;
    seg_tile[1] = 0; seg_k0[1] = 0; seg_k1[1] = 0;
  } else {
    const int hh = ci - 7;
    nseg = 2;
    seg_tile[0] = grp * 7 + ((0x54210 >> (4 * hh)) & 15); seg_k0[0] = (0x10210 >> (4 * hh)) & 15; seg_k1[0] = 3;
    seg_tile[1] = seg_tile[0] + 1; seg_k0[1] = 0; seg_k1[1] = (0x31321 >> (4 * hh)) & 15;
  }

  if (warp >= 8) {
    asm volatile("setmaxnreg.dec.sync.aligned.u32 24;");
    if (warp == 8 && lane == 0) {
      if (blockIdx.x == 0) { g_wflag[0] = 0; g_wflag[1] = 0; g_wflag[2] = 0; g_wflag[3] = 0; }
      int it = 0;
      for (int sg = 0; sg < nseg; sg++) {
        const int tile = sg ? seg_tile[1] : seg_tile[0];
        const int k0 = sg ? seg_k0[1] : seg_k0[0], k1 = sg ? seg_k1[1] : seg_k1[0];
        const int t = tile / 11, qt = tile - t * 11;
        if (sg > 0) mbar_wait(bQE, 0);
        mbar_expect_tx(bQF, 49152);
        for (int c = 0; c < 3; c++) tma_load_3d(sb + B_Q + c * 16384, &tm_q, bQF, c * 64, qt * 128, t);
        const int n = k1 - k0;
        for (int e = 0; e < 2 * n; e++) {
          const int isv = e & 1, kbi = e >> 1;
          const int sl = it % 3;
          if (it >= 3) mbar_wait(bE + sl * 8, ((it / 3) - 1) & 1);
          mbar_expect_tx(bF + sl * 8, B_SLOT);
          for (int c = 0; c < 3; c++)
            tma_load_3d(sb + B_KV + sl * B_SLOT + c * 18432, &tm_kv, bF + sl * 8, 192 + isv * 192 + c * 64, (k0 + kbi) * 144, t);
          it++;
        }
      }
      if (owner) {
        const int t = seg_tile[0] / 11, qt = seg_tile[0] - t * 11;
        mbar_wait(bQE, 0);
        mbar_expect_tx(bQF, 49152);
        for (int c = 0; c < 3; c++) tma_load_3d(sb + B_Q + c * 16384, &tm_x1, bQF, c * 64, qt * 128, t);
      }
    }
    return;
  }

  asm volatile("setmaxnreg.inc.sync.aligned.u32 240;");
  const int wg = warp >> 2, wq = warp & 3;
  const int wtid = tid & 127;
  const float cs = 0.07216878364870322f * 1.4426950408889634f;
  float oacc[96], sacc[72];
  uint32_t pf[9][4];
  float m0, m1, l0, l1;
  int it = 0;
  const uint32_t qb = sb + B_Q + wg * 8192;
  if (wg == 1) bar_arrive(3, 256);
  TS(1, 0);
  int tsi = 1;

  auto issue_qk = [&](int slot) {
    const uint64_t kd = mk_desc_o(sb + B_KV + slot * B_SLOT, 16, 1024);
    const uint64_t qd = mk_desc_o(qb, 16, 1024);
#pragma unroll
    for (int kk = 0; kk < 12; kk++)
      wgmma_n144_ss<0>(sacc, qd + (kk >> 2) * 1024 + (kk & 3) * 2, kd + (kk >> 2) * 1152 + (kk & 3) * 2, kk > 0);
    wg_commit();
  };
  auto issue_pv = [&](int slot, int accum) {
    const uint64_t vd = mk_desc_o(sb + B_KV + slot * B_SLOT, 18432, 1024);
#pragma unroll
    for (int kk = 0; kk < 9; kk++) wgmma_n192_rs<1>(oacc, pf[kk], vd + kk * 128, kk > 0 ? 1 : accum);
    wg_commit();
  };
  auto softmax1 = [&](float& a0, float& a1) {
    float t0[4], t1[4];
#pragma unroll
    for (int q = 0; q < 4; q++) {
      t0[q] = fmaxf(sacc[4 * q], sacc[4 * q + 1]);
      t1[q] = fmaxf(sacc[4 * q + 2], sacc[4 * q + 3]);
    }
#pragma unroll
    for (int j = 4; j < 18; j++) {
      t0[j & 3] = fmaxf(t0[j & 3], fmaxf(sacc[4 * j], sacc[4 * j + 1]));
      t1[j & 3] = fmaxf(t1[j & 3], fmaxf(sacc[4 * j + 2], sacc[4 * j + 3]));
    }
    float mx0 = fmaxf(fmaxf(t0[0], t0[1]), fmaxf(fmaxf(t0[2], t0[3]), m0));
    float mx1 = fmaxf(fmaxf(t1[0], t1[1]), fmaxf(fmaxf(t1[2], t1[3]), m1));
    mx0 = fmaxf(mx0, __shfl_xor_sync(0xffffffffu, mx0, 1)); mx1 = fmaxf(mx1, __shfl_xor_sync(0xffffffffu, mx1, 1));
    mx0 = fmaxf(mx0, __shfl_xor_sync(0xffffffffu, mx0, 2)); mx1 = fmaxf(mx1, __shfl_xor_sync(0xffffffffu, mx1, 2));
    a0 = ex2((m0 - mx0) * cs); a1 = ex2((m1 - mx1) * cs);
    m0 = mx0; m1 = mx1;
    const float mc0 = mx0 * cs, mc1 = mx1 * cs;
#pragma unroll
    for (int q = 0; q < 4; q++) { t0[q] = 0.f; t1[q] = 0.f; }
#pragma unroll
    for (int j = 0; j < 18; j++) {
      sacc[4 * j] = ex2(fmaf(sacc[4 * j], cs, -mc0)); sacc[4 * j + 1] = ex2(fmaf(sacc[4 * j + 1], cs, -mc0));
      sacc[4 * j + 2] = ex2(fmaf(sacc[4 * j + 2], cs, -mc1)); sacc[4 * j + 3] = ex2(fmaf(sacc[4 * j + 3], cs, -mc1));
      t0[j & 1] += sacc[4 * j]; t0[2 + (j & 1)] += sacc[4 * j + 1];
      t1[j & 1] += sacc[4 * j + 2]; t1[2 + (j & 1)] += sacc[4 * j + 3];
    }
    l0 = l0 * a0 + ((t0[0] + t0[1]) + (t0[2] + t0[3]));
    l1 = l1 * a1 + ((t1[0] + t1[1]) + (t1[2] + t1[3]));
  };
  auto cvt_p = [&]() {
#pragma unroll
    for (int k = 0; k < 9; k++) {
      pf[k][0] = pack_bf16(sacc[8 * k + 0], sacc[8 * k + 1]); pf[k][1] = pack_bf16(sacc[8 * k + 2], sacc[8 * k + 3]);
      pf[k][2] = pack_bf16(sacc[8 * k + 4], sacc[8 * k + 5]); pf[k][3] = pack_bf16(sacc[8 * k + 6], sacc[8 * k + 7]);
    }
  };

  for (int sg = 0; sg < nseg; sg++) {
    const int n = sg ? (seg_k1[1] - seg_k0[1]) : (seg_k1[0] - seg_k0[0]);
    m0 = m1 = -INFINITY; l0 = l1 = 0.f;
    mbar_wait(bQF, sg & 1);
    {
      const int sl = it % 3;
      mbar_wait(bF + sl * 8, (it / 3) & 1);
      named_bar(3 + wg, 256);
      wg_fence();
      issue_qk(sl);
      bar_arrive(3 + (wg ^ 1), 256);
      wg_wait<0>(); reg_fence(sacc);
      if (lane == 0) { mbar_arrive(bE + sl * 8); if (n == 1) mbar_arrive(bQE); }
      it++;
      float a0, a1;
      softmax1(a0, a1);
      cvt_p();
    }
    TS(1, tsi); tsi++;
    for (int j = 1; j < n; j++) {
      const int slv = it % 3, slk = (it + 1) % 3;
      mbar_wait(bF + slv * 8, (it / 3) & 1);
      if (j == 3) TS(1, 10);
      named_bar(3 + wg, 256);
      if (j == 3) TS(1, 11);
      wg_fence();
      issue_pv(slv, j > 1);
      mbar_wait(bF + slk * 8, ((it + 1) / 3) & 1);
      if (j == 3) TS(1, 12);
      issue_qk(slk);
      bar_arrive(3 + (wg ^ 1), 256);
      wg_wait<1>(); reg_fence(oacc);
      if (lane == 0) mbar_arrive(bE + slv * 8);
      if (j == 3) TS(1, 13);
      wg_wait<0>(); reg_fence(sacc);
      if (lane == 0) { mbar_arrive(bE + slk * 8); if (j == n - 1) mbar_arrive(bQE); }
      if (j == 3) TS(1, 14);
      float a0, a1;
      softmax1(a0, a1);
      it += 2;
#pragma unroll
      for (int i = 0; i < 24; i++) {
        oacc[4 * i] *= a0; oacc[4 * i + 1] *= a0; oacc[4 * i + 2] *= a1; oacc[4 * i + 3] *= a1;
      }
      cvt_p();
      TS(1, tsi); tsi++;
    }
    {
      const int sl = it % 3;
      mbar_wait(bF + sl * 8, (it / 3) & 1);
      named_bar(3 + wg, 256);
      wg_fence();
      issue_pv(sl, n > 1);
      if (!(wg == 1 && sg == nseg - 1)) bar_arrive(3 + (wg ^ 1), 256);
      wg_wait<0>(); reg_fence(oacc);
      if (lane == 0) mbar_arrive(bE + sl * 8);
      it++;
    }
    TS(1, tsi); tsi++;
    if (!owner) {
      const int slot = (grp * 5 + (ci - 7)) * 2 + sg;
      float4* dst = g_part + (size_t)(slot * 2 + wg) * 25 * 128 + wtid;
#pragma unroll
      for (int i = 0; i < 24; i++) dst[i * 128] = make_float4(oacc[4 * i], oacc[4 * i + 1], oacc[4 * i + 2], oacc[4 * i + 3]);
      dst[24 * 128] = make_float4(m0, m1, l0, l1);
      __threadfence();
      named_bar(1 + wg, 128);
      if (wtid == 0) atomicAdd(&g_flag[slot], 1u);
      TS(1, tsi); tsi++;
    }
  }
  if (!owner) return;

  {
    const int first = (0x9765310 >> (4 * ci)) & 15, cnt = (0x1211221 >> (4 * ci)) & 15;
    for (int q = 0; q < cnt; q++) {
      const int slot = grp * 10 + first + q;
      if (wtid == 0) {
        uint32_t n = 0, v;
        do {
          asm volatile("ld.acquire.gpu.global.u32 %0, [%1];" : "=r"(v) : "l"(&g_flag[slot]) : "memory");
        } while (v < 2u && ++n < (1u << 22));
      }
      named_bar(1 + wg, 128);
      const float4* src = g_part + (size_t)(slot * 2 + wg) * 25 * 128 + wtid;
      const float4 ml = __ldcg(src + 24 * 128);
      const float mx0 = fmaxf(m0, ml.x), mx1 = fmaxf(m1, ml.y);
      const float a0 = ex2((m0 - mx0) * cs), a1 = ex2((m1 - mx1) * cs);
      const float b0 = ex2((ml.x - mx0) * cs), b1 = ex2((ml.y - mx1) * cs);
      m0 = mx0; m1 = mx1;
      l0 = l0 * a0 + ml.z * b0; l1 = l1 * a1 + ml.w * b1;
#pragma unroll
      for (int i = 0; i < 24; i++) {
        const float4 v = __ldcg(src + i * 128);
        oacc[4 * i] = oacc[4 * i] * a0 + v.x * b0; oacc[4 * i + 1] = oacc[4 * i + 1] * a0 + v.y * b0;
        oacc[4 * i + 2] = oacc[4 * i + 2] * a1 + v.z * b1; oacc[4 * i + 3] = oacc[4 * i + 3] * a1 + v.w * b1;
      }
    }
  }
  TS(1, 21);
  l0 += __shfl_xor_sync(0xffffffffu, l0, 1); l0 += __shfl_xor_sync(0xffffffffu, l0, 2);
  l1 += __shfl_xor_sync(0xffffffffu, l1, 1); l1 += __shfl_xor_sync(0xffffffffu, l1, 2);
  const float i0 = 1.f / l0, i1 = 1.f / l1;
  mbar_wait(bQF, 1);
  const FragAddr fa(wq, lane);
#pragma unroll
  for (int c = 0; c < 3; c++) resid_chunk(nullptr, &oacc[32 * c], i0, i1, qb + c * 16384, fa);
  fence_proxy_async();
  named_bar(1 + wg, 128);
  TS(1, 22);
  if (wtid == 0) {
    const int t = seg_tile[0] / 11, qt = seg_tile[0] - t * 11;
    if (qt * 128 + wg * 64 < NL) {
      for (int c = 0; c < 3; c++) tma_store_3d(&tm_out, qb + c * 16384, c * 64, qt * 128 + wg * 64, t);
      bulk_commit();
      bulk_wait0();
    }
  }
  TS(1, 23);
}

typedef CUresult (*EncodeFn)(CUtensorMap*, CUtensorMapDataType, cuuint32_t, void*, const cuuint64_t*, const cuuint64_t*,
                             const cuuint32_t*, const cuuint32_t*, CUtensorMapInterleave, CUtensorMapSwizzle,
                             CUtensorMapL2promotion, CUtensorMapFloatOOBfill);

void make_map(EncodeFn enc, CUtensorMap* m, const void* ptr, int rank, const uint64_t* dims, const uint32_t* box) {
  cuuint64_t gd[3], gs[2];
  cuuint32_t bx[3], es[3] = {1, 1, 1};
  uint64_t stride = 2;
  for (int i = 0; i < rank; i++) {
    gd[i] = dims[i]; bx[i] = box[i];
    stride *= dims[i];
    if (i < rank - 1) gs[i] = stride;
  }
  enc(m, CU_TENSOR_MAP_DATA_TYPE_BFLOAT16, rank, const_cast<void*>(ptr), gd, gs, bx, es, CU_TENSOR_MAP_INTERLEAVE_NONE,
      CU_TENSOR_MAP_SWIZZLE_128B, CU_TENSOR_MAP_L2_PROMOTION_L2_256B, CU_TENSOR_MAP_FLOAT_OOB_FILL_NONE);
}

}

extern "C" void kernel_launch(void* const* d_in, const int* in_sizes, int n_in, void* d_out, int out_size) {
  (void)in_sizes; (void)n_in; (void)out_size;
  EncodeFn enc = nullptr;
  cudaDriverEntryPointQueryResult qres;
  cudaGetDriverEntryPoint("cuTensorMapEncodeTiled", (void**)&enc, cudaEnableDefault, &qres);
  void *p_x1, *p_qkv, *p_wf;
  cudaGetSymbolAddress(&p_wf, g_wf);
  cudaGetSymbolAddress(&p_x1, g_x1);
  cudaGetSymbolAddress(&p_qkv, g_qkv);
  cudaFuncSetAttribute(kernelA, cudaFuncAttributeMaxDynamicSharedMemorySize, A_SMEM);
  cudaFuncSetAttribute(kernelB, cudaFuncAttributeMaxDynamicSharedMemorySize, B_SMEM);

  CUtensorMap tm_x, tm_wqkvt, tm_wot, tm_wqkvs, tm_x1s, tm_qkvs, tm_q, tm_kv, tm_wos, tm_x1l, tm_out, tm_wf;
  const uint64_t d_act[3] = {192, 1296, 7}, d_qkv[3] = {576, 1296, 7}, d_w3[2] = {576, 192}, d_w1[2] = {192, 192}, d_wf[2] = {384, 384};
  const uint32_t b_a[3] = {64, 9, 7}, b_w[2] = {64, 192}, b_q[3] = {64, 128, 1}, b_kv[3] = {64, 144, 1}, b_o[3] = {64, 64, 1}, b_w64[2] = {64, 64};
  make_map(enc, &tm_x, d_in[0], 3, d_act, b_a);
  make_map(enc, &tm_wqkvt, d_in[1], 2, d_w3, b_w64);
  make_map(enc, &tm_wot, d_in[2], 2, d_w1, b_w);
  make_map(enc, &tm_wqkvs, d_in[3], 2, d_w3, b_w64);
  make_map(enc, &tm_wos, d_in[4], 2, d_w1, b_w);
  make_map(enc, &tm_wf, p_wf, 2, d_wf, b_w);
  make_map(enc, &tm_x1s, p_x1, 3, d_act, b_a);
  make_map(enc, &tm_qkvs, p_qkv, 3, d_qkv, b_a);
  make_map(enc, &tm_q, p_qkv, 3, d_qkv, b_q);
  make_map(enc, &tm_kv, p_qkv, 3, d_qkv, b_kv);
  make_map(enc, &tm_x1l, p_x1, 3, d_act, b_q);
  make_map(enc, &tm_out, d_out, 3, d_act, b_o);

  kernelA<<<72 + A_FOLD, 384, A_SMEM>>>(tm_x, tm_wqkvt, tm_wot, tm_wqkvs, tm_wos, tm_wf, tm_x1s, tm_qkvs);
  kernelB<<<B_GRID, 384, B_SMEM>>>(tm_q, tm_kv, tm_x1l, tm_out);
}
```

```cpp
#include <cuda_runtime.h>
#include <cuda_bf16.h>
#include <cuda.h>
#include <stdint.h>

namespace {

constexpr int TT = 7, NL = 1296, CC = 192;

__device__ __align__(1024) __nv_bfloat16 g_x1[TT * NL * CC];
__device__ __align__(1024) __nv_bfloat16 g_qkv[TT * NL * 3 * CC];
__device__ __align__(1024) __nv_bfloat16 g_wf[2 * CC * 2 * CC];
__device__ __align__(1024) float4 g_part[110 * 2 * 25 * 128];
__device__ unsigned int g_flag[128];
__device__ unsigned int g_wflag[4];

#define TS(k, i)

__device__ __forceinline__ uint32_t smem_u32(const void* p) { return (uint32_t)__cvta_generic_to_shared(p); }
__device__ __forceinline__ void mbar_init(uint32_t bar, uint32_t cnt) {
  asm volatile("mbarrier.init.shared::cta.b64 [%0], %1;" ::"r"(bar), "r"(cnt));
}
__device__ __forceinline__ void mbar_expect_tx(uint32_t bar, uint32_t bytes) {
  asm volatile("mbarrier.arrive.expect_tx.shared::cta.b64 _, [%0], %1;" ::"r"(bar), "r"(bytes) : "memory");
}
__device__ __forceinline__ void mbar_arrive(uint32_t bar) {
  asm volatile("mbarrier.arrive.shared::cta.b64 _, [%0];" ::"r"(bar) : "memory");
}
__device__ __forceinline__ bool mbar_try(uint32_t bar, uint32_t parity) {
  uint32_t ok;
  asm volatile("{\n.reg .pred p;\nmbarrier.try_wait.parity.shared::cta.b64 p, [%1], %2;\nselp.u32 %0, 1, 0, p;\n}"
               : "=r"(ok) : "r"(bar), "r"(parity) : "memory");
  return ok != 0;
}
__device__ __forceinline__ void mbar_wait(uint32_t bar, uint32_t parity) {
  if (mbar_try(bar, parity)) return;
  uint32_t n = 0;
  while (!mbar_try(bar, parity)) {
    if (++n > (1u << 22)) break;
  }
}
__device__ __forceinline__ void tma_load_2d(uint32_t dst, const CUtensorMap* m, uint32_t bar, int c0, int c1) {
  asm volatile("cp.async.bulk.tensor.2d.shared::cluster.global.mbarrier::complete_tx::bytes [%0], [%1, {%3, %4}], [%2];"
               ::"r"(dst), "l"(m), "r"(bar), "r"(c0), "r"(c1) : "memory");
}
__device__ __forceinline__ void tma_load_3d(uint32_t dst, const CUtensorMap* m, uint32_t bar, int c0, int c1, int c2) {
  asm volatile("cp.async.bulk.tensor.3d.shared::cluster.global.mbarrier::complete_tx::bytes [%0], [%1, {%3, %4, %5}], [%2];"
               ::"r"(dst), "l"(m), "r"(bar), "r"(c0), "r"(c1), "r"(c2) : "memory");
}
__device__ __forceinline__ void tma_store_3d(const CUtensorMap* m, uint32_t src, int c0, int c1, int c2) {
  asm volatile("cp.async.bulk.tensor.3d.global.shared::cta.bulk_group [%0, {%2, %3, %4}], [%1];"
               ::"l"(m), "r"(src), "r"(c0), "r"(c1), "r"(c2) : "memory");
}
__device__ __forceinline__ void bulk_commit() { asm volatile("cp.async.bulk.commit_group;" ::: "memory"); }
__device__ __forceinline__ void bulk_wait_read0() { asm volatile("cp.async.bulk.wait_group.read 0;" ::: "memory"); }
__device__ __forceinline__ void bulk_wait0() { asm volatile("cp.async.bulk.wait_group 0;" ::: "memory"); }
__device__ __forceinline__ void fence_proxy_async() { asm volatile("fence.proxy.async.shared::cta;" ::: "memory"); }
__device__ __forceinline__ void prefetch_tmap(const CUtensorMap* m) {
  asm volatile("prefetch.tensormap [%0];" ::"l"(m) : "memory");
}
__device__ __forceinline__ void wg_fence() { asm volatile("wgmma.fence.sync.aligned;" ::: "memory"); }
__device__ __forceinline__ void wg_commit() { asm volatile("wgmma.commit_group.sync.aligned;" ::: "memory"); }
template <int N> __device__ __forceinline__ void wg_wait() { asm volatile("wgmma.wait_group.sync.aligned %0;" ::"n"(N) : "memory"); }
__device__ __forceinline__ void named_bar(int id, int nthreads) {
  asm volatile("bar.sync %0, %1;" ::"r"(id), "r"(nthreads) : "memory");
}
__device__ __forceinline__ void ldsm_x4(uint32_t (&r)[4], uint32_t addr) {
  asm volatile("ldmatrix.sync.aligned.m8n8.x4.shared.b16 {%0,%1,%2,%3}, [%4];"
               : "=r"(r[0]), "=r"(r[1]), "=r"(r[2]), "=r"(r[3]) : "r"(addr) : "memory");
}
__device__ __forceinline__ void stsm_x4(uint32_t addr, const uint32_t (&r)[4]) {
  asm volatile("stmatrix.sync.aligned.m8n8.x4.shared.b16 [%0], {%1,%2,%3,%4};"
               ::"r"(addr), "r"(r[0]), "r"(r[1]), "r"(r[2]), "r"(r[3]) : "memory");
}
__device__ __forceinline__ uint32_t pack_bf16(float lo, float hi) {
  uint32_t r;
  asm("cvt.rn.bf16x2.f32 %0, %1, %2;" : "=r"(r) : "f"(hi), "f"(lo));
  return r;
}
__device__ __forceinline__ float bf_lo(uint32_t v) { return __uint_as_float(v << 16); }
__device__ __forceinline__ float bf_hi(uint32_t v) { return __uint_as_float(v & 0xffff0000u); }
__device__ __forceinline__ float ex2(float x) {
  float y;
  asm("ex2.approx.ftz.f32 %0, %1;" : "=f"(y) : "f"(x));
  return y;
}
__device__ __forceinline__ uint64_t mk_desc(uint32_t addr, uint32_t lbo, uint32_t sbo) {
  return (uint64_t)((addr & 0x3FFFF) >> 4) | ((uint64_t)((lbo & 0x3FFFF) >> 4) << 16) |
         ((uint64_t)((sbo & 0x3FFFF) >> 4) << 32) | (1ull << 62);
}
__device__ __forceinline__ uint64_t mk_desc_o(uint32_t addr, uint32_t lbo, uint32_t sbo) {
  asm volatile("" : "+r"(addr));
  return mk_desc(addr, lbo, sbo);
}
template <int N> __device__ __forceinline__ void reg_fence(float (&d)[N]) {
#pragma unroll
  for (int i = 0; i < N; i++) asm volatile("" : "+f"(d[i])::"memory");
}

template<int TB> __device__ __forceinline__ void wgmma_n144_rs(float (&d)[72], const uint32_t (&a)[4], uint64_t db, int sc) {
  asm volatile("{\n.reg .pred p;\nsetp.ne.b32 p, %77, 0;\n"
    "wgmma.mma_async.sync.aligned.m64n144k16.f32.bf16.bf16 {%0, %1, %2, %3, %4, %5, %6, %7, %8, %9, %10, %11, %12, %13, %14, %15, %16, %17, %18, %19, %20, %21, %22, %23, %24, %25, %26, %27, %28, %29, %30, %31, %32, %33, %34, %35, %36, %37, %38, %39, %40, %41, %42, %43, %44, %45, %46, %47, %48, %49, %50, %51, %52, %53, %54, %55, %56, %57, %58, %59, %60, %61, %62, %63, %64, %65, %66, %67, %68, %69, %70, %71}, {%72, %73, %74, %75}, %76, p, 1, 1, %78;\n}\n"
    : "+f"(d[0]), "+f"(d[1]), "+f"(d[2]), "+f"(d[3]), "+f"(d[4]), "+f"(d[5]), "+f"(d[6]), "+f"(d[7]), "+f"(d[8]), "+f"(d[9]), "+f"(d[10]), "+f"(d[11]), "+f"(d[12]), "+f"(d[13]), "+f"(d[14]), "+f"(d[15]), "+f"(d[16]), "+f"(d[17]), "+f"(d[18]), "+f"(d[19]), "+f"(d[20]), "+f"(d[21]), "+f"(d[22]), "+f"(d[23]), "+f"(d[24]), "+f"(d[25]), "+f"(d[26]), "+f"(d[27]), "+f"(d[28]), "+f"(d[29]), "+f"(d[30]), "+f"(d[31]), "+f"(d[32]), "+f"(d[33]), "+f"(d[34]), "+f"(d[35]), "+f"(d[36]), "+f"(d[37]), "+f"(d[38]), "+f"(d[39]), "+f"(d[40]), "+f"(d[41]), "+f"(d[42]), "+f"(d[43]), "+f"(d[44]), "+f"(d[45]), "+f"(d[46]), "+f"(d[47]), "+f"(d[48]), "+f"(d[49]), "+f"(d[50]), "+f"(d[51]), "+f"(d[52]), "+f"(d[53]), "+f"(d[54]), "+f"(d[55]), "+f"(d[56]), "+f"(d[57]), "+f"(d[58]), "+f"(d[59]), "+f"(d[60]), "+f"(d[61]), "+f"(d[62]), "+f"(d[63]), "+f"(d[64]), "+f"(d[65]), "+f"(d[66]), "+f"(d[67]), "+f"(d[68]), "+f"(d[69]), "+f"(d[70]), "+f"(d[71])
    : "r"(a[0]), "r"(a[1]), "r"(a[2]), "r"(a[3]), "l"(db), "r"(sc), "n"(TB));
}
template<int TB> __device__ __forceinline__ void wgmma_n192_rs(float (&d)[96], const uint32_t (&a)[4], uint64_t db, int sc) {
  asm volatile("{\n.reg .pred p;\nsetp.ne.b32 p, %101, 0;\n"
    "wgmma.mma_async.sync.aligned.m64n192k16.f32.bf16.bf16 {%0, %1, %2, %3, %4, %5, %6, %7, %8, %9, %10, %11, %12, %13, %14, %15, %16, %17, %18, %19, %20, %21, %22, %23, %24, %25, %26, %27, %28, %29, %30, %31, %32, %33, %34, %35, %36, %37, %38, %39, %40, %41, %42, %43, %44, %45, %46, %47, %48, %49, %50, %51, %52, %53, %54, %55, %56, %57, %58, %59, %60, %61, %62, %63, %64, %65, %66, %67, %68, %69, %70, %71, %72, %73, %74, %75, %76, %77, %78, %79, %80, %81, %82, %83, %84, %85, %86, %87, %88, %89, %90, %91, %92, %93, %94, %95}, {%96, %97, %98, %99}, %100, p, 1, 1, %102;\n}\n"
    : "+f"(d[0]), "+f"(d[1]), "+f"(d[2]), "+f"(d[3]), "+f"(d[4]), "+f"(d[5]), "+f"(d[6]), "+f"(d[7]), "+f"(d[8]), "+f"(d[9]), "+f"(d[10]), "+f"(d[11]), "+f"(d[12]), "+f"(d[13]), "+f"(d[14]), "+f"(d[15]), "+f"(d[16]), "+f"(d[17]), "+f"(d[18]), "+f"(d[19]), "+f"(d[20]), "+f"(d[21]), "+f"(d[22]), "+f"(d[23]), "+f"(d[24]), "+f"(d[25]), "+f"(d[26]), "+f"(d[27]), "+f"(d[28]), "+f"(d[29]), "+f"(d[30]), "+f"(d[31]), "+f"(d[32]), "+f"(d[33]), "+f"(d[34]), "+f"(d[35]), "+f"(d[36]), "+f"(d[37]), "+f"(d[38]), "+f"(d[39]), "+f"(d[40]), "+f"(d[41]), "+f"(d[42]), "+f"(d[43]), "+f"(d[44]), "+f"(d[45]), "+f"(d[46]), "+f"(d[47]), "+f"(d[48]), "+f"(d[49]), "+f"(d[50]), "+f"(d[51]), "+f"(d[52]), "+f"(d[53]), "+f"(d[54]), "+f"(d[55]), "+f"(d[56]), "+f"(d[57]), "+f"(d[58]), "+f"(d[59]), "+f"(d[60]), "+f"(d[61]), "+f"(d[62]), "+f"(d[63]), "+f"(d[64]), "+f"(d[65]), "+f"(d[66]), "+f"(d[67]), "+f"(d[68]), "+f"(d[69]), "+f"(d[70]), "+f"(d[71]), "+f"(d[72]), "+f"(d[73]), "+f"(d[74]), "+f"(d[75]), "+f"(d[76]), "+f"(d[77]), "+f"(d[78]), "+f"(d[79]), "+f"(d[80]), "+f"(d[81]), "+f"(d[82]), "+f"(d[83]), "+f"(d[84]), "+f"(d[85]), "+f"(d[86]), "+f"(d[87]), "+f"(d[88]), "+f"(d[89]), "+f"(d[90]), "+f"(d[91]), "+f"(d[92]), "+f"(d[93]), "+f"(d[94]), "+f"(d[95])
    : "r"(a[0]), "r"(a[1]), "r"(a[2]), "r"(a[3]), "l"(db), "r"(sc), "n"(TB));
}
template<int TB> __device__ __forceinline__ void wgmma_n64_rs(float (&d)[32], const uint32_t (&a)[4], uint64_t db, int sc) {
  asm volatile("{\n.reg .pred p;\nsetp.ne.b32 p, %37, 0;\n"
    "wgmma.mma_async.sync.aligned.m64n64k16.f32.bf16.bf16 {%0, %1, %2, %3, %4, %5, %6, %7, %8, %9, %10, %11, %12, %13, %14, %15, %16, %17, %18, %19, %20, %21, %22, %23, %24, %25, %26, %27, %28, %29, %30, %31}, {%32, %33, %34, %35}, %36, p, 1, 1, %38;\n}\n"
    : "+f"(d[0]), "+f"(d[1]), "+f"(d[2]), "+f"(d[3]), "+f"(d[4]), "+f"(d[5]), "+f"(d[6]), "+f"(d[7]), "+f"(d[8]), "+f"(d[9]), "+f"(d[10]), "+f"(d[11]), "+f"(d[12]), "+f"(d[13]), "+f"(d[14]), "+f"(d[15]), "+f"(d[16]), "+f"(d[17]), "+f"(d[18]), "+f"(d[19]), "+f"(d[20]), "+f"(d[21]), "+f"(d[22]), "+f"(d[23]), "+f"(d[24]), "+f"(d[25]), "+f"(d[26]), "+f"(d[27]), "+f"(d[28]), "+f"(d[29]), "+f"(d[30]), "+f"(d[31])
    : "r"(a[0]), "r"(a[1]), "r"(a[2]), "r"(a[3]), "l"(db), "r"(sc), "n"(TB));
}
template<int TB> __device__ __forceinline__ void wgmma_n64_ss(float (&d)[32], uint64_t da, uint64_t db, int sc) {
  asm volatile("{\n.reg .pred p;\nsetp.ne.b32 p, %34, 0;\n"
    "wgmma.mma_async.sync.aligned.m64n64k16.f32.bf16.bf16 {%0, %1, %2, %3, %4, %5, %6, %7, %8, %9, %10, %11, %12, %13, %14, %15, %16, %17, %18, %19, %20, %21, %22, %23, %24, %25, %26, %27, %28, %29, %30, %31}, %32, %33, p, 1, 1, 0, %35;\n}\n"
    : "+f"(d[0]), "+f"(d[1]), "+f"(d[2]), "+f"(d[3]), "+f"(d[4]), "+f"(d[5]), "+f"(d[6]), "+f"(d[7]), "+f"(d[8]), "+f"(d[9]), "+f"(d[10]), "+f"(d[11]), "+f"(d[12]), "+f"(d[13]), "+f"(d[14]), "+f"(d[15]), "+f"(d[16]), "+f"(d[17]), "+f"(d[18]), "+f"(d[19]), "+f"(d[20]), "+f"(d[21]), "+f"(d[22]), "+f"(d[23]), "+f"(d[24]), "+f"(d[25]), "+f"(d[26]), "+f"(d[27]), "+f"(d[28]), "+f"(d[29]), "+f"(d[30]), "+f"(d[31])
    : "l"(da), "l"(db), "r"(sc), "n"(TB));
}

struct FragAddr {
  uint32_t rowoff;
  uint32_t rx;
  uint32_t hi;
  __device__ __forceinline__ FragAddr(int warp_in_wg, int lane) {
    int row = 16 * warp_in_wg + (lane & 7) + ((lane >> 3) & 1) * 8;
    rowoff = row * 128;
    rx = row & 7;
    hi = lane >> 4;
  }
  __device__ __forceinline__ uint32_t at(uint32_t chunk_base, int kk4) const {
    return chunk_base + rowoff + ((((uint32_t)kk4 * 2 + hi) ^ rx) << 4);
  }
};

__device__ __forceinline__ void layernorm_frags(uint32_t (&f)[12][4]) {
  float s0 = 0.f, s1 = 0.f;
#pragma unroll
  for (int k = 0; k < 12; k++) {
    s0 += bf_lo(f[k][0]) + bf_hi(f[k][0]) + bf_lo(f[k][2]) + bf_hi(f[k][2]);
    s1 += bf_lo(f[k][1]) + bf_hi(f[k][1]) + bf_lo(f[k][3]) + bf_hi(f[k][3]);
  }
  s0 += __shfl_xor_sync(0xffffffffu, s0, 1); s0 += __shfl_xor_sync(0xffffffffu, s0, 2);
  s1 += __shfl_xor_sync(0xffffffffu, s1, 1); s1 += __shfl_xor_sync(0xffffffffu, s1, 2);
  const float m0 = s0 * (1.f / 192.f), m1 = s1 * (1.f / 192.f);
  float v0 = 0.f, v1 = 0.f;
#pragma unroll
  for (int k = 0; k < 12; k++) {
    float a;
    a = bf_lo(f[k][0]) - m0; v0 += a * a; a = bf_hi(f[k][0]) - m0; v0 += a * a;
    a = bf_lo(f[k][2]) - m0; v0 += a * a; a = bf_hi(f[k][2]) - m0; v0 += a * a;
    a = bf_lo(f[k][1]) - m1; v1 += a * a; a = bf_hi(f[k][1]) - m1; v1 += a * a;
    a = bf_lo(f[k][3]) - m1; v1 += a * a; a = bf_hi(f[k][3]) - m1; v1 += a * a;
  }
  v0 += __shfl_xor_sync(0xffffffffu, v0, 1); v0 += __shfl_xor_sync(0xffffffffu, v0, 2);
  v1 += __shfl_xor_sync(0xffffffffu, v1, 1); v1 += __shfl_xor_sync(0xffffffffu, v1, 2);
  const float r0 = rsqrtf(v0 * (1.f / 192.f) + 1e-5f), r1 = rsqrtf(v1 * (1.f / 192.f) + 1e-5f);
#pragma unroll
  for (int k = 0; k < 12; k++) {
    f[k][0] = pack_bf16((bf_lo(f[k][0]) - m0) * r0, (bf_hi(f[k][0]) - m0) * r0);
    f[k][2] = pack_bf16((bf_lo(f[k][2]) - m0) * r0, (bf_hi(f[k][2]) - m0) * r0);
    f[k][1] = pack_bf16((bf_lo(f[k][1]) - m1) * r1, (bf_hi(f[k][1]) - m1) * r1);
    f[k][3] = pack_bf16((bf_lo(f[k][3]) - m1) * r1, (bf_hi(f[k][3]) - m1) * r1);
  }
}

constexpr int A_NST = 5;
constexpr int A_XS = 0;
constexpr int A_VB = 49152;
constexpr int A_W = 98304;
constexpr int A_BAR = A_W + A_NST * 24576;
constexpr int A_SMEM = A_BAR + 256 + 1024;
constexpr int A_FOLD = 36;

__device__ __forceinline__ void a_issue(float (&acc)[32], const uint32_t (&af)[12][4], uint32_t sb, int s) {
  const int st = s % A_NST;
  mbar_wait(sb + A_BAR + st * 8, (s / A_NST) & 1);
  const uint64_t wd = mk_desc_o(sb + A_W + st * 24576, 8192, 1024);
  wg_fence();
#pragma unroll
  for (int kk = 0; kk < 12; kk++) wgmma_n64_rs<1>(acc, af[kk], wd + kk * 128, kk > 0);
  wg_commit();
}
__device__ __forceinline__ void a_release(uint32_t sb, int s, int lane) {
  if (lane == 0) mbar_arrive(sb + A_BAR + 64 + (s % A_NST) * 8);
}
__device__ __forceinline__ void cvt_frags(uint32_t (*dst)[4], const float (&acc)[32]) {
#pragma unroll
  for (int k = 0; k < 4; k++) {
    dst[k][0] = pack_bf16(acc[8 * k + 0], acc[8 * k + 1]);
    dst[k][1] = pack_bf16(acc[8 * k + 2], acc[8 * k + 3]);
    dst[k][2] = pack_bf16(acc[8 * k + 4], acc[8 * k + 5]);
    dst[k][3] = pack_bf16(acc[8 * k + 6], acc[8 * k + 7]);
  }
}
__device__ __forceinline__ void store_chunk(const float (&acc)[32], uint32_t chunk_base, const FragAddr& fa) {
  uint32_t t[4][4];
  cvt_frags(t, acc);
#pragma unroll
  for (int k = 0; k < 4; k++) stsm_x4(fa.at(chunk_base, k), t[k]);
}
__device__ __forceinline__ void resid_chunk(uint32_t (*dst)[4], const float* acc, float s0, float s1, uint32_t chunk_base,
                                            const FragAddr& fa) {
#pragma unroll
  for (int k = 0; k < 4; k++) {
    uint32_t x[4];
    ldsm_x4(x, fa.at(chunk_base, k));
    uint32_t o[4];
    o[0] = pack_bf16(fmaf(acc[8 * k + 0], s0, bf_lo(x[0])), fmaf(acc[8 * k + 1], s0, bf_hi(x[0])));
    o[1] = pack_bf16(fmaf(acc[8 * k + 2], s1, bf_lo(x[1])), fmaf(acc[8 * k + 3], s1, bf_hi(x[1])));
    o[2] = pack_bf16(fmaf(acc[8 * k + 4], s0, bf_lo(x[2])), fmaf(acc[8 * k + 5], s0, bf_hi(x[2])));
    o[3] = pack_bf16(fmaf(acc[8 * k + 6], s1, bf_lo(x[3])), fmaf(acc[8 * k + 7], s1, bf_hi(x[3])));
    stsm_x4(fa.at(chunk_base, k), o);
    if (dst) { dst[k][0] = o[0]; dst[k][1] = o[1]; dst[k][2] = o[2]; dst[k][3] = o[3]; }
  }
}

__global__ void __launch_bounds__(384, 1)
kernelA(const __grid_constant__ CUtensorMap tm_x, const __grid_constant__ CUtensorMap tm_wq64t,
        const __grid_constant__ CUtensorMap tm_wot, const __grid_constant__ CUtensorMap tm_wq64s,
        const __grid_constant__ CUtensorMap tm_wos, const __grid_constant__ CUtensorMap tm_wf,
        const __grid_constant__ CUtensorMap tm_x1, const __grid_constant__ CUtensorMap tm_qkv) {
  extern __shared__ uint8_t smem_raw[];
  const uint32_t sb = (smem_u32(smem_raw) + 1023) & ~1023u;
  const int tid = threadIdx.x, warp = tid >> 5, lane = tid & 31;
  const bool is_fold = blockIdx.x < A_FOLD;
  const int blk = blockIdx.x - A_FOLD;
  if (tid == 256) {
    for (int i = 0; i < A_NST; i++) { mbar_init(sb + A_BAR + i * 8, 1); mbar_init(sb + A_BAR + 64 + i * 8, 8); }
    mbar_init(sb + A_BAR + 128, 1); mbar_init(sb + A_BAR + 136, 1);
    asm volatile("fence.mbarrier_init.release.cluster;" ::: "memory");
    if (!is_fold) {
      for (int w = 0; w < 2; w++) {
        const uint32_t bar = sb + A_BAR + 128 + w * 8;
        mbar_expect_tx(bar, 3 * 63 * 128);
        for (int c = 0; c < 3; c++)
          tma_load_3d(sb + A_XS + w * 24576 + c * 8192, &tm_x, bar, c * 64, (blk * 2 + w) * 9, 0);
      }
    } else {
      const int mat = blockIdx.x / 9, rs = (blockIdx.x % 9) / 3, cs = blockIdx.x % 3;
      const CUtensorMap* mq = (mat < 2) ? &tm_wq64t : &tm_wq64s;
      const CUtensorMap* mo = (mat < 2) ? &tm_wot : &tm_wos;
      const uint32_t bar = sb + A_BAR + 128;
      mbar_expect_tx(bar, 2 * 24576);
      for (int c = 0; c < 3; c++) tma_load_2d(sb + c * 8192, mq, bar, ((mat & 1) ? 384 : 0) + c * 64, rs * 64);
      if (mat & 1) tma_load_2d(sb + 24576, mo, bar, cs * 64, 0);
      else for (int c = 0; c < 3; c++) tma_load_2d(sb + 24576 + c * 8192, mq, bar, 192 + c * 64, cs * 64);
    }
  }
  if (blockIdx.x == 0 && tid < 128) g_flag[tid] = 0;
  if (!is_fold && tid < 48) {
    uint32_t a = sb + A_XS + (tid >> 3) * 8192 + 63 * 128 + (tid & 7) * 16;
    asm volatile("st.shared.v4.b32 [%0], {%1,%1,%1,%1};" ::"r"(a), "r"(0) : "memory");
  }
  __syncthreads();

  if (warp >= 8) {
    asm volatile("setmaxnreg.dec.sync.aligned.u32 24;");
    if (warp == 8 && lane == 0 && !is_fold) {
      for (int s = 0; s < 12; s++) {
        const int st = s % A_NST;
        const int g = s / 3;
        const int mat = (g == 0) ? 1 : (g == 1) ? 0 : g;
        if (s % 3 == 0) {
          uint32_t n = 0, v;
          do {
            asm volatile("ld.acquire.gpu.global.u32 %0, [%1];" : "=r"(v) : "l"(&g_wflag[mat]) : "memory");
          } while (v < 9u && ++n < (1u << 22));
          asm volatile("fence.proxy.async;" ::: "memory");
        }
        if (s >= A_NST) mbar_wait(sb + A_BAR + 64 + st * 8, ((s / A_NST) - 1) & 1);
        mbar_expect_tx(sb + A_BAR + st * 8, 24576);
        tma_load_2d(sb + A_W + st * 24576, &tm_wf, sb + A_BAR + st * 8, (mat & 1) * 192 + (s % 3) * 64, (mat >> 1) * 192);
      }
    }
    return;
  }

  asm volatile("setmaxnreg.inc.sync.aligned.u32 240;");
  const int wg = warp >> 2, wq = warp & 3;

  if (is_fold) {
    if (wg == 0) {
      const int mat = blockIdx.x / 9, rs = (blockIdx.x % 9) / 3, cs = blockIdx.x % 3;
      float d[32];
      mbar_wait(sb + A_BAR + 128, 0);
      const uint64_t ad = mk_desc_o(sb, 16, 1024);
      if (mat & 1) {
        const uint64_t bd = mk_desc_o(sb + 24576, 8192, 1024);
        wg_fence();
#pragma unroll
        for (int kk = 0; kk < 12; kk++) wgmma_n64_ss<1>(d, ad + (kk >> 2) * 512 + (kk & 3) * 2, bd + kk * 128, kk > 0);
        wg_commit();
      } else {
        const uint64_t bd = mk_desc_o(sb + 24576, 16, 1024);
        wg_fence();
#pragma unroll
        for (int kk = 0; kk < 12; kk++)
          wgmma_n64_ss<0>(d, ad + (kk >> 2) * 512 + (kk & 3) * 2, bd + (kk >> 2) * 512 + (kk & 3) * 2, kk > 0);
        wg_commit();
      }
      wg_wait<0>(); reg_fence(d);
      const int r0 = rs * 64 + wq * 16 + (lane >> 2);
      uint32_t* dst = reinterpret_cast<uint32_t*>(g_wf + ((size_t)(mat >> 1) * 192 + r0) * 384 + (mat & 1) * 192 + cs * 64 + (lane & 3) * 2);
#pragma unroll
      for (int j = 0; j < 8; j++) {
        dst[j * 4] = pack_bf16(d[4 * j], d[4 * j + 1]);
        dst[8 * 192 + j * 4] = pack_bf16(d[4 * j + 2], d[4 * j + 3]);
      }
      asm volatile("fence.proxy.async;" ::: "memory");
      __threadfence();
      named_bar(1, 128);
      if (tid == 0) atomicAdd(&g_wflag[mat], 1u);
    }
    return;
  }

  const int n0 = (blk * 2 + wg) * 9;
  const FragAddr fa(wq, lane);
  const uint32_t xs = sb + A_XS + wg * 24576, vb = sb + A_VB + wg * 24576;
  const int barid = 1 + wg;
  const bool elected = (tid & 127) == 0;

  uint32_t h[12][4];
  TS(0, 0);
  mbar_wait(sb + A_BAR + 128 + wg * 8, 0);
  TS(0, 1);
#pragma unroll
  for (int k = 0; k < 12; k++) ldsm_x4(h[k], fa.at(xs + (k >> 2) * 8192, k & 3));
  layernorm_frags(h);
#pragma unroll
  for (int k = 0; k < 12; k++) stsm_x4(fa.at(xs + (k >> 2) * 8192, k & 3), h[k]);

  float acc0[32], acc1[32];
  uint32_t qf[12][4];
  TS(0, 2);
  a_issue(acc0, h, sb, 0);
  TS(0, 3);
  a_issue(acc1, h, sb, 1); wg_wait<1>(); reg_fence(acc0); a_release(sb, 0, lane); store_chunk(acc0, vb, fa);
  a_issue(acc0, h, sb, 2); wg_wait<1>(); reg_fence(acc1); a_release(sb, 1, lane); store_chunk(acc1, vb + 8192, fa);
  a_issue(acc1, h, sb, 3); wg_wait<1>(); reg_fence(acc0); a_release(sb, 2, lane); store_chunk(acc0, vb + 16384, fa);
  fence_proxy_async();
  named_bar(barid, 128);
  a_issue(acc0, h, sb, 4); wg_wait<1>(); reg_fence(acc1); a_release(sb, 3, lane); cvt_frags(&qf[0], acc1);
  a_issue(acc1, h, sb, 5); wg_wait<1>(); reg_fence(acc0); a_release(sb, 4, lane); cvt_frags(&qf[4], acc0);
  wg_wait<0>(); reg_fence(acc1); a_release(sb, 5, lane); cvt_frags(&qf[8], acc1);
  TS(0, 4);
  {
    const uint64_t kd = mk_desc_o(xs, 16, 1024);
    wg_fence();
#pragma unroll
    for (int kk = 0; kk < 12; kk++) wgmma_n64_rs<0>(acc0, qf[kk], kd + (kk >> 2) * 512 + (kk & 3) * 2, kk > 0);
    wg_commit();
    wg_wait<0>(); reg_fence(acc0);
  }
  named_bar(barid, 128);
  if (elected) {
    const uint32_t bar = sb + A_BAR + 128 + wg * 8;
    mbar_expect_tx(bar, 3 * 63 * 128);
    for (int c = 0; c < 3; c++) tma_load_3d(xs + c * 8192, &tm_x, bar, c * 64, n0, 0);
  }
  uint32_t pf[4][4];
  {
    const int r0 = 16 * wq + (lane >> 2), r1 = r0 + 8;
    const unsigned long long MB = 0x0040201008040201ull;
    const unsigned long long mk0 = (MB << (r0 % 9)) >> (2 * (lane & 3));
    const unsigned long long mk1 = (MB << (r1 % 9)) >> (2 * (lane & 3));
    const float cs = 0.07216878364870322f * 1.4426950408889634f;
    float mx0 = -INFINITY, mx1 = -INFINITY;
#pragma unroll
    for (int j = 0; j < 8; j++) {
#pragma unroll
      for (int e = 0; e < 2; e++) {
        bool v0 = (mk0 >> (8 * j + e)) & 1, v1 = (mk1 >> (8 * j + e)) & 1;
        acc0[4 * j + e] = v0 ? acc0[4 * j + e] * cs : -INFINITY;
        acc0[4 * j + 2 + e] = v1 ? acc0[4 * j + 2 + e] * cs : -INFINITY;
        mx0 = fmaxf(mx0, acc0[4 * j + e]);
        mx1 = fmaxf(mx1, acc0[4 * j + 2 + e]);
      }
    }
    mx0 = fmaxf(mx0, __shfl_xor_sync(0xffffffffu, mx0, 1)); mx0 = fmaxf(mx0, __shfl_xor_sync(0xffffffffu, mx0, 2));
    mx1 = fmaxf(mx1, __shfl_xor_sync(0xffffffffu, mx1, 1)); mx1 = fmaxf(mx1, __shfl_xor_sync(0xffffffffu, mx1, 2));
    float l0 = 0.f, l1 = 0.f;
#pragma unroll
    for (int j = 0; j < 8; j++) {
#pragma unroll
      for (int e = 0; e < 2; e++) {
        acc0[4 * j + e] = ex2(acc0[4 * j + e] - mx0); l0 += acc0[4 * j + e];
        acc0[4 * j + 2 + e] = ex2(acc0[4 * j + 2 + e] - mx1); l1 += acc0[4 * j + 2 + e];
      }
    }
    l0 += __shfl_xor_sync(0xffffffffu, l0, 1); l0 += __shfl_xor_sync(0xffffffffu, l0, 2);
    l1 += __shfl_xor_sync(0xffffffffu, l1, 1); l1 += __shfl_xor_sync(0xffffffffu, l1, 2);
    const float i0 = 1.f / l0, i1 = 1.f / l1;
#pragma unroll
    for (int j = 0; j < 8; j++) {
      acc0[4 * j] *= i0; acc0[4 * j + 1] *= i0; acc0[4 * j + 2] *= i1; acc0[4 * j + 3] *= i1;
    }
    cvt_frags(pf, acc0);
  }
  TS(0, 5);
  {
    float oacc[96];
    const uint64_t vd = mk_desc_o(vb, 8192, 1024);
    wg_fence();
#pragma unroll
    for (int kk = 0; kk < 4; kk++) wgmma_n192_rs<1>(oacc, pf[kk], vd + kk * 128, kk > 0);
    wg_commit();
    wg_wait<0>(); reg_fence(oacc);
    TS(0, 6);
    mbar_wait(sb + A_BAR + 128 + wg * 8, 1);
#pragma unroll
    for (int c = 0; c < 3; c++) resid_chunk(&h[4 * c], &oacc[32 * c], 1.f, 1.f, xs + c * 8192, fa);
  }
  TS(0, 7);
  layernorm_frags(h);
  named_bar(barid, 128);
#pragma unroll
  for (int k = 0; k < 12; k++) stsm_x4(fa.at(vb + (k >> 2) * 8192, k & 3), h[k]);
  TS(0, 8);
  a_issue(acc0, h, sb, 6);
  fence_proxy_async();
  named_bar(barid, 128);
  if (elected) {
    for (int c = 0; c < 3; c++) tma_store_3d(&tm_x1, xs + c * 8192, c * 64, n0, 0);
    for (int c = 0; c < 3; c++) tma_store_3d(&tm_qkv, vb + c * 8192, 192 + c * 64, n0, 0);
    bulk_commit();
  }
  a_issue(acc1, h, sb, 7); wg_wait<1>(); reg_fence(acc0); a_release(sb, 6, lane);
  if (elected) bulk_wait_read0();
  named_bar(barid, 128);
  store_chunk(acc0, xs, fa);
  a_issue(acc0, h, sb, 8); wg_wait<1>(); reg_fence(acc1); store_chunk(acc1, xs + 8192, fa);
  a_issue(acc1, h, sb, 9); wg_wait<1>(); reg_fence(acc0); store_chunk(acc0, xs + 16384, fa);
  fence_proxy_async();
  named_bar(barid, 128);
  if (elected) {
    for (int c = 0; c < 3; c++) tma_store_3d(&tm_qkv, xs + c * 8192, c * 64, n0, 0);
    bulk_commit();
  }
  a_issue(acc0, h, sb, 10); wg_wait<1>(); reg_fence(acc1); store_chunk(acc1, vb, fa);
  a_issue(acc1, h, sb, 11); wg_wait<1>(); reg_fence(acc0); store_chunk(acc0, vb + 8192, fa);
  wg_wait<0>(); reg_fence(acc1); store_chunk(acc1, vb + 16384, fa);
  fence_proxy_async();
  named_bar(barid, 128);
  TS(0, 9);
  if (elected) {
    for (int c = 0; c < 3; c++) tma_store_3d(&tm_qkv, vb + c * 8192, 384 + c * 64, n0, 0);
    bulk_commit();
    bulk_wait0();
  }
  TS(0, 10);
}

constexpr int B_GRID = 132;
constexpr int B_NS = 4;
constexpr int B_SLOT = 55296;
constexpr int B_BAR = B_NS * B_SLOT;
constexpr int B_SMEM = B_BAR + 256 + 1024;
#define PINGPONG 1

__device__ __forceinline__ void bar_arrive(int id, int nthreads) {
  asm volatile("bar.arrive %0, %1;" ::"r"(id), "r"(nthreads) : "memory");
}

__global__ void __launch_bounds__(384, 1)
kernelB(const __grid_constant__ CUtensorMap tm_q, const __grid_constant__ CUtensorMap tm_kv,
        const __grid_constant__ CUtensorMap tm_x1, const __grid_constant__ CUtensorMap tm_out) {
  extern __shared__ uint8_t smem_raw[];
  const uint32_t sb = (smem_u32(smem_raw) + 1023) & ~1023u;
  const int tid = threadIdx.x, warp = tid >> 5, lane = tid & 31;
  const uint32_t bF = sb + B_BAR, bE = sb + B_BAR + 64;
  if (tid == 0) {
    for (int i = 0; i < B_NS; i++) { mbar_init(bF + i * 8, 1); mbar_init(bE + i * 8, 8); }
    asm volatile("fence.mbarrier_init.release.cluster;" ::: "memory");
  }
  __syncthreads();
  const int grp = blockIdx.x / 12, ci = blockIdx.x - grp * 12;
  const bool owner = ci < 7;
  int nseg, seg_tile[2], seg_k0[2], seg_k1[2];
  if (owner) {
    nseg = 1; seg_tile[0] = grp * 7 + ci; seg_k0[0] = 3; seg_k1[0] = 9;
    seg_tile[1] = 0; seg_k0[1] = 0; seg_k1[1] = 0;
  } else {
    const int hh = ci - 7;
    nseg = 2;
    seg_tile[0] = grp * 7 + ((0x54210 >> (4 * hh)) & 15); seg_k0[0] = (0x10210 >> (4 * hh)) & 15; seg_k1[0] = 3;
    seg_tile[1] = seg_tile[0] + 1; seg_k0[1] = 0; seg_k1[1] = (0x31321 >> (4 * hh)) & 15;
  }

  if (warp >= 8) {
    asm volatile("setmaxnreg.dec.sync.aligned.u32 24;");
    if (warp == 8 && lane == 0) {
      if (blockIdx.x == 0) { g_wflag[0] = 0; g_wflag[1] = 0; g_wflag[2] = 0; g_wflag[3] = 0; }
      int it = 0;
      for (int sg = 0; sg < nseg; sg++) {
        const int tile = sg ? seg_tile[1] : seg_tile[0];
        const int k0 = sg ? seg_k0[1] : seg_k0[0], k1 = sg ? seg_k1[1] : seg_k1[0];
        const int t = tile / 11, qt = tile - t * 11;
        const int n = k1 - k0;
        for (int e = -1; e < 2 * n; e++) {
          const int sl = it % B_NS;
          if (it >= B_NS) mbar_wait(bE + sl * 8, ((it / B_NS) - 1) & 1);
          if (e < 0) {
            mbar_expect_tx(bF + sl * 8, 49152);
            for (int c = 0; c < 3; c++) tma_load_3d(sb + sl * B_SLOT + c * 16384, &tm_q, bF + sl * 8, c * 64, qt * 128, t);
          } else {
            mbar_expect_tx(bF + sl * 8, B_SLOT);
            for (int c = 0; c < 3; c++)
              tma_load_3d(sb + sl * B_SLOT + c * 18432, &tm_kv, bF + sl * 8, 192 + (e & 1) * 192 + c * 64, (k0 + (e >> 1)) * 144, t);
          }
          it++;
        }
      }
      if (owner) {
        const int t = seg_tile[0] / 11, qt = seg_tile[0] - t * 11;
        const int sl = it % B_NS;
        mbar_wait(bE + sl * 8, ((it / B_NS) - 1) & 1);
        mbar_expect_tx(bF + sl * 8, 49152);
        for (int c = 0; c < 3; c++) tma_load_3d(sb + sl * B_SLOT + c * 16384, &tm_x1, bF + sl * 8, c * 64, qt * 128, t);
      }
    }
    return;
  }

  asm volatile("setmaxnreg.inc.sync.aligned.u32 240;");
  const int wg = warp >> 2, wq = warp & 3;
  const int wtid = tid & 127;
  const float cs = 0.07216878364870322f * 1.4426950408889634f;
  float oacc[96], sacc[72];
  uint32_t qf[12][4];
  float m0, m1, l0, l1;
  int it = 0;
  const FragAddr fa(wq, lane);
  if (wg == 1) bar_arrive(3, 256);
  TS(1, 0);
  int tsi = 1;

  auto issue_qk = [&](int slot) {
    const uint64_t kd = mk_desc_o(sb + slot * B_SLOT, 16, 1024);
    wg_fence();
#pragma unroll
    for (int kk = 0; kk < 12; kk++) wgmma_n144_rs<0>(sacc, qf[kk], kd + (kk >> 2) * 1152 + (kk & 3) * 2, kk > 0);
    wg_commit();
  };
  auto issue_pv = [&](int slot, int accum) {
    const uint64_t vd = mk_desc_o(sb + slot * B_SLOT, 18432, 1024);
    wg_fence();
#pragma unroll
    for (int kk = 0; kk < 9; kk++) {
      const uint32_t pa[4] = {__float_as_uint(sacc[8 * kk]), __float_as_uint(sacc[8 * kk + 1]),
                              __float_as_uint(sacc[8 * kk + 2]), __float_as_uint(sacc[8 * kk + 3])};
      wgmma_n192_rs<1>(oacc, pa, vd + kk * 128, kk > 0 ? 1 : accum);
    }
    wg_commit();
  };
  auto softmax = [&](bool rescale) {
    float t0[4], t1[4];
#pragma unroll
    for (int q = 0; q < 4; q++) {
      t0[q] = fmaxf(sacc[4 * q], sacc[4 * q + 1]);
      t1[q] = fmaxf(sacc[4 * q + 2], sacc[4 * q + 3]);
    }
#pragma unroll
    for (int j = 4; j < 18; j++) {
      t0[j & 3] = fmaxf(t0[j & 3], fmaxf(sacc[4 * j], sacc[4 * j + 1]));
      t1[j & 3] = fmaxf(t1[j & 3], fmaxf(sacc[4 * j + 2], sacc[4 * j + 3]));
    }
    float mx0 = fmaxf(fmaxf(t0[0], t0[1]), fmaxf(fmaxf(t0[2], t0[3]), m0));
    float mx1 = fmaxf(fmaxf(t1[0], t1[1]), fmaxf(fmaxf(t1[2], t1[3]), m1));
    mx0 = fmaxf(mx0, __shfl_xor_sync(0xffffffffu, mx0, 1)); mx1 = fmaxf(mx1, __shfl_xor_sync(0xffffffffu, mx1, 1));
    mx0 = fmaxf(mx0, __shfl_xor_sync(0xffffffffu, mx0, 2)); mx1 = fmaxf(mx1, __shfl_xor_sync(0xffffffffu, mx1, 2));
    const float a0 = ex2((m0 - mx0) * cs), a1 = ex2((m1 - mx1) * cs);
    m0 = mx0; m1 = mx1;
    const float mc0 = mx0 * cs, mc1 = mx1 * cs;
#pragma unroll
    for (int q = 0; q < 4; q++) { t0[q] = 0.f; t1[q] = 0.f; }
#pragma unroll
    for (int k = 0; k < 9; k++) {
      float p[8];
#pragma unroll
      for (int e = 0; e < 8; e++) p[e] = ex2(fmaf(sacc[8 * k + e], cs, (e & 2) ? -mc1 : -mc0));
      t0[0] += p[0]; t0[1] += p[1]; t0[2] += p[4]; t0[3] += p[5];
      t1[0] += p[2]; t1[1] += p[3]; t1[2] += p[6]; t1[3] += p[7];
      sacc[8 * k + 0] = __uint_as_float(pack_bf16(p[0], p[1]));
      sacc[8 * k + 1] = __uint_as_float(pack_bf16(p[2], p[3]));
      sacc[8 * k + 2] = __uint_as_float(pack_bf16(p[4], p[5]));
      sacc[8 * k + 3] = __uint_as_float(pack_bf16(p[6], p[7]));
    }
    l0 = l0 * a0 + ((t0[0] + t0[1]) + (t0[2] + t0[3]));
    l1 = l1 * a1 + ((t1[0] + t1[1]) + (t1[2] + t1[3]));
    if (rescale) {
#pragma unroll
      for (int i = 0; i < 24; i++) {
        oacc[4 * i] *= a0; oacc[4 * i + 1] *= a0; oacc[4 * i + 2] *= a1; oacc[4 * i + 3] *= a1;
      }
    }
  };

  for (int sg = 0; sg < nseg; sg++) {
    const int n = sg ? (seg_k1[1] - seg_k0[1]) : (seg_k1[0] - seg_k0[0]);
    m0 = m1 = -INFINITY; l0 = l1 = 0.f;
    {
      const int sl = it % B_NS;
      mbar_wait(bF + sl * 8, (it / B_NS) & 1);
      const uint32_t qb = sb + sl * B_SLOT + wg * 8192;
#pragma unroll
      for (int k = 0; k < 12; k++) ldsm_x4(qf[k], fa.at(qb + (k >> 2) * 16384, k & 3));
      __syncwarp();
      if (lane == 0) mbar_arrive(bE + sl * 8);
      it++;
    }
    {
      const int sl = it % B_NS;
      mbar_wait(bF + sl * 8, (it / B_NS) & 1);
      named_bar(3 + wg, 256);
      issue_qk(sl);
      bar_arrive(3 + (wg ^ 1), 256);
      wg_wait<0>(); reg_fence(sacc);
      if (lane == 0) mbar_arrive(bE + sl * 8);
      it++;
      softmax(false);
    }
    TS(1, tsi); tsi++;
    for (int j = 1; j < n; j++) {
      const int slv = it % B_NS, slk = (it + 1) % B_NS;
      mbar_wait(bF + slv * 8, (it / B_NS) & 1);
      mbar_wait(bF + slk * 8, ((it + 1) / B_NS) & 1);
      if (j == 3) TS(1, 10);
      named_bar(3 + wg, 256);
      if (j == 3) TS(1, 11);
      issue_pv(slv, j > 1);
      wg_wait<0>(); reg_fence(oacc); reg_fence(sacc);
      if (j == 3) TS(1, 12);
      issue_qk(slk);
      bar_arrive(3 + (wg ^ 1), 256);
      if (lane == 0) mbar_arrive(bE + slv * 8);
      wg_wait<0>(); reg_fence(sacc);
      if (lane == 0) mbar_arrive(bE + slk * 8);
      if (j == 3) TS(1, 13);
      it += 2;
      softmax(true);
      TS(1, tsi); tsi++;
    }
    {
      const int sl = it % B_NS;
      mbar_wait(bF + sl * 8, (it / B_NS) & 1);
      named_bar(3 + wg, 256);
      issue_pv(sl, n > 1);
      if (!(wg == 1 && sg == nseg - 1)) bar_arrive(3 + (wg ^ 1), 256);
      wg_wait<0>(); reg_fence(oacc);
      if (lane == 0) mbar_arrive(bE + sl * 8);
      it++;
    }
    TS(1, tsi); tsi++;
    if (!owner) {
      const int slot = (grp * 5 + (ci - 7)) * 2 + sg;
      float4* dst = g_part + (size_t)(slot * 2 + wg) * 25 * 128 + wtid;
#pragma unroll
      for (int i = 0; i < 24; i++) dst[i * 128] = make_float4(oacc[4 * i], oacc[4 * i + 1], oacc[4 * i + 2], oacc[4 * i + 3]);
      dst[24 * 128] = make_float4(m0, m1, l0, l1);
      __threadfence();
      named_bar(1 + wg, 128);
      if (wtid == 0) atomicAdd(&g_flag[slot], 1u);
      TS(1, tsi); tsi++;
    }
  }
  if (!owner) return;

  {
    const int first = (0x9765310 >> (4 * ci)) & 15, cnt = (0x1211221 >> (4 * ci)) & 15;
    for (int q = 0; q < cnt; q++) {
      const int slot = grp * 10 + first + q;
      if (wtid == 0) {
        uint32_t n = 0, v;
        do {
          asm volatile("ld.acquire.gpu.global.u32 %0, [%1];" : "=r"(v) : "l"(&g_flag[slot]) : "memory");
        } while (v < 2u && ++n < (1u << 22));
      }
      named_bar(1 + wg, 128);
      const float4* src = g_part + (size_t)(slot * 2 + wg) * 25 * 128 + wtid;
      const float4 ml = __ldcg(src + 24 * 128);
      const float mx0 = fmaxf(m0, ml.x), mx1 = fmaxf(m1, ml.y);
      const float a0 = ex2((m0 - mx0) * cs), a1 = ex2((m1 - mx1) * cs);
      const float b0 = ex2((ml.x - mx0) * cs), b1 = ex2((ml.y - mx1) * cs);
      m0 = mx0; m1 = mx1;
      l0 = l0 * a0 + ml.z * b0; l1 = l1 * a1 + ml.w * b1;
#pragma unroll
      for (int i = 0; i < 24; i++) {
        const float4 v = __ldcg(src + i * 128);
        oacc[4 * i] = oacc[4 * i] * a0 + v.x * b0; oacc[4 * i + 1] = oacc[4 * i + 1] * a0 + v.y * b0;
        oacc[4 * i + 2] = oacc[4 * i + 2] * a1 + v.z * b1; oacc[4 * i + 3] = oacc[4 * i + 3] * a1 + v.w * b1;
      }
    }
  }
  TS(1, 21);
  l0 += __shfl_xor_sync(0xffffffffu, l0, 1); l0 += __shfl_xor_sync(0xffffffffu, l0, 2);
  l1 += __shfl_xor_sync(0xffffffffu, l1, 1); l1 += __shfl_xor_sync(0xffffffffu, l1, 2);
  const float i0 = 1.f / l0, i1 = 1.f / l1;
  const int sl = it % B_NS;
  mbar_wait(bF + sl * 8, (it / B_NS) & 1);
  const uint32_t qb = sb + sl * B_SLOT + wg * 8192;
#pragma unroll
  for (int c = 0; c < 3; c++) resid_chunk(nullptr, &oacc[32 * c], i0, i1, qb + c * 16384, fa);
  fence_proxy_async();
  named_bar(1 + wg, 128);
  TS(1, 22);
  if (wtid == 0) {
    const int t = seg_tile[0] / 11, qt = seg_tile[0] - t * 11;
    if (qt * 128 + wg * 64 < NL) {
      for (int c = 0; c < 3; c++) tma_store_3d(&tm_out, qb + c * 16384, c * 64, qt * 128 + wg * 64, t);
      bulk_commit();
      bulk_wait0();
    }
  }
  TS(1, 23);
}

typedef CUresult (*EncodeFn)(CUtensorMap*, CUtensorMapDataType, cuuint32_t, void*, const cuuint64_t*, const cuuint64_t*,
                             const cuuint32_t*, const cuuint32_t*, CUtensorMapInterleave, CUtensorMapSwizzle,
                             CUtensorMapL2promotion, CUtensorMapFloatOOBfill);

void make_map(EncodeFn enc, CUtensorMap* m, const void* ptr, int rank, const uint64_t* dims, const uint32_t* box) {
  cuuint64_t gd[3], gs[2];
  cuuint32_t bx[3], es[3] = {1, 1, 1};
  uint64_t stride = 2;
  for (int i = 0; i < rank; i++) {
    gd[i] = dims[i]; bx[i] = box[i];
    stride *= dims[i];
    if (i < rank - 1) gs[i] = stride;
  }
  enc(m, CU_TENSOR_MAP_DATA_TYPE_BFLOAT16, rank, const_cast<void*>(ptr), gd, gs, bx, es, CU_TENSOR_MAP_INTERLEAVE_NONE,
      CU_TENSOR_MAP_SWIZZLE_128B, CU_TENSOR_MAP_L2_PROMOTION_L2_256B, CU_TENSOR_MAP_FLOAT_OOB_FILL_NONE);
}

}

extern "C" void kernel_launch(void* const* d_in, const int* in_sizes, int n_in, void* d_out, int out_size) {
  (void)in_sizes; (void)n_in; (void)out_size;
  EncodeFn enc = nullptr;
  cudaDriverEntryPointQueryResult qres;
  cudaGetDriverEntryPoint("cuTensorMapEncodeTiled", (void**)&enc, cudaEnableDefault, &qres);
  void *p_x1, *p_qkv, *p_wf;
  cudaGetSymbolAddress(&p_wf, g_wf);
  cudaGetSymbolAddress(&p_x1, g_x1);
  cudaGetSymbolAddress(&p_qkv, g_qkv);
  cudaFuncSetAttribute(kernelA, cudaFuncAttributeMaxDynamicSharedMemorySize, A_SMEM);
  cudaFuncSetAttribute(kernelB, cudaFuncAttributeMaxDynamicSharedMemorySize, B_SMEM);

  CUtensorMap tm_x, tm_wqkvt, tm_wot, tm_wqkvs, tm_x1s, tm_qkvs, tm_q, tm_kv, tm_wos, tm_x1l, tm_out, tm_wf;
  const uint64_t d_act[3] = {192, 1296, 7}, d_qkv[3] = {576, 1296, 7}, d_w3[2] = {576, 192}, d_w1[2] = {192, 192}, d_wf[2] = {384, 384};
  const uint32_t b_a[3] = {64, 9, 7}, b_w[2] = {64, 192}, b_q[3] = {64, 128, 1}, b_kv[3] = {64, 144, 1}, b_o[3] = {64, 64, 1}, b_w64[2] = {64, 64};
  make_map(enc, &tm_x, d_in[0], 3, d_act, b_a);
  make_map(enc, &tm_wqkvt, d_in[1], 2, d_w3, b_w64);
  make_map(enc, &tm_wot, d_in[2], 2, d_w1, b_w);
  make_map(enc, &tm_wqkvs, d_in[3], 2, d_w3, b_w64);
  make_map(enc, &tm_wos, d_in[4], 2, d_w1, b_w);
  make_map(enc, &tm_wf, p_wf, 2, d_wf, b_w);
  make_map(enc, &tm_x1s, p_x1, 3, d_act, b_a);
  make_map(enc, &tm_qkvs, p_qkv, 3, d_qkv, b_a);
  make_map(enc, &tm_q, p_qkv, 3, d_qkv, b_q);
  make_map(enc, &tm_kv, p_qkv, 3, d_qkv, b_kv);
  make_map(enc, &tm_x1l, p_x1, 3, d_act, b_q);
  make_map(enc, &tm_out, d_out, 3, d_act, b_o);

  kernelA<<<72 + A_FOLD, 384, A_SMEM>>>(tm_x, tm_wqkvt, tm_wot, tm_wqkvs, tm_wos, tm_wf, tm_x1s, tm_qkvs);
  kernelB<<<B_GRID, 384, B_SMEM>>>(tm_q, tm_kv, tm_x1l, tm_out);
}
```

```cpp
#include <cuda_runtime.h>
#include <cuda_bf16.h>
#include <cuda.h>
#include <stdint.h>

namespace {

constexpr int TT = 7, NL = 1296, CC = 192;

__device__ __align__(1024) __nv_bfloat16 g_x1[TT * NL * CC];
__device__ __align__(1024) __nv_bfloat16 g_qkv[TT * NL * 3 * CC];
__device__ __align__(1024) __nv_bfloat16 g_wf[2 * CC * 2 * CC];
__device__ __align__(1024) uint4 g_part[110 * 2 * 13 * 128];
__device__ unsigned int g_flag[128];
__device__ unsigned int g_wflag[4];

#define TS(k, i)

__device__ __forceinline__ uint32_t smem_u32(const void* p) { return (uint32_t)__cvta_generic_to_shared(p); }
__device__ __forceinline__ void mbar_init(uint32_t bar, uint32_t cnt) {
  asm volatile("mbarrier.init.shared::cta.b64 [%0], %1;" ::"r"(bar), "r"(cnt));
}
__device__ __forceinline__ void mbar_expect_tx(uint32_t bar, uint32_t bytes) {
  asm volatile("mbarrier.arrive.expect_tx.shared::cta.b64 _, [%0], %1;" ::"r"(bar), "r"(bytes) : "memory");
}
__device__ __forceinline__ void mbar_arrive(uint32_t bar) {
  asm volatile("mbarrier.arrive.shared::cta.b64 _, [%0];" ::"r"(bar) : "memory");
}
__device__ __forceinline__ bool mbar_try(uint32_t bar, uint32_t parity) {
  uint32_t ok;
  asm volatile("{\n.reg .pred p;\nmbarrier.try_wait.parity.shared::cta.b64 p, [%1], %2;\nselp.u32 %0, 1, 0, p;\n}"
               : "=r"(ok) : "r"(bar), "r"(parity) : "memory");
  return ok != 0;
}
__device__ __forceinline__ void mbar_wait(uint32_t bar, uint32_t parity) {
  if (mbar_try(bar, parity)) return;
  uint32_t n = 0;
  while (!mbar_try(bar, parity)) {
    if (++n > (1u << 22)) break;
  }
}
__device__ __forceinline__ void tma_load_2d(uint32_t dst, const CUtensorMap* m, uint32_t bar, int c0, int c1) {
  asm volatile("cp.async.bulk.tensor.2d.shared::cluster.global.mbarrier::complete_tx::bytes [%0], [%1, {%3, %4}], [%2];"
               ::"r"(dst), "l"(m), "r"(bar), "r"(c0), "r"(c1) : "memory");
}
__device__ __forceinline__ void tma_load_3d(uint32_t dst, const CUtensorMap* m, uint32_t bar, int c0, int c1, int c2) {
  asm volatile("cp.async.bulk.tensor.3d.shared::cluster.global.mbarrier::complete_tx::bytes [%0], [%1, {%3, %4, %5}], [%2];"
               ::"r"(dst), "l"(m), "r"(bar), "r"(c0), "r"(c1), "r"(c2) : "memory");
}
__device__ __forceinline__ void tma_store_3d(const CUtensorMap* m, uint32_t src, int c0, int c1, int c2) {
  asm volatile("cp.async.bulk.tensor.3d.global.shared::cta.bulk_group [%0, {%2, %3, %4}], [%1];"
               ::"l"(m), "r"(src), "r"(c0), "r"(c1), "r"(c2) : "memory");
}
__device__ __forceinline__ void bulk_commit() { asm volatile("cp.async.bulk.commit_group;" ::: "memory"); }
__device__ __forceinline__ void bulk_wait_read0() { asm volatile("cp.async.bulk.wait_group.read 0;" ::: "memory"); }
__device__ __forceinline__ void bulk_wait0() { asm volatile("cp.async.bulk.wait_group 0;" ::: "memory"); }
__device__ __forceinline__ void fence_proxy_async() { asm volatile("fence.proxy.async.shared::cta;" ::: "memory"); }
__device__ __forceinline__ void prefetch_tmap(const CUtensorMap* m) {
  asm volatile("prefetch.tensormap [%0];" ::"l"(m) : "memory");
}
__device__ __forceinline__ void wg_fence() { asm volatile("wgmma.fence.sync.aligned;" ::: "memory"); }
__device__ __forceinline__ void wg_commit() { asm volatile("wgmma.commit_group.sync.aligned;" ::: "memory"); }
template <int N> __device__ __forceinline__ void wg_wait() { asm volatile("wgmma.wait_group.sync.aligned %0;" ::"n"(N) : "memory"); }
__device__ __forceinline__ void named_bar(int id, int nthreads) {
  asm volatile("bar.sync %0, %1;" ::"r"(id), "r"(nthreads) : "memory");
}
__device__ __forceinline__ void ldsm_x4(uint32_t (&r)[4], uint32_t addr) {
  asm volatile("ldmatrix.sync.aligned.m8n8.x4.shared.b16 {%0,%1,%2,%3}, [%4];"
               : "=r"(r[0]), "=r"(r[1]), "=r"(r[2]), "=r"(r[3]) : "r"(addr) : "memory");
}
__device__ __forceinline__ void stsm_x4(uint32_t addr, const uint32_t (&r)[4]) {
  asm volatile("stmatrix.sync.aligned.m8n8.x4.shared.b16 [%0], {%1,%2,%3,%4};"
               ::"r"(addr), "r"(r[0]), "r"(r[1]), "r"(r[2]), "r"(r[3]) : "memory");
}
__device__ __forceinline__ uint32_t pack_bf16(float lo, float hi) {
  uint32_t r;
  asm("cvt.rn.bf16x2.f32 %0, %1, %2;" : "=r"(r) : "f"(hi), "f"(lo));
  return r;
}
__device__ __forceinline__ float bf_lo(uint32_t v) { return __uint_as_float(v << 16); }
__device__ __forceinline__ float bf_hi(uint32_t v) { return __uint_as_float(v & 0xffff0000u); }
__device__ __forceinline__ float ex2(float x) {
  float y;
  asm("ex2.approx.ftz.f32 %0, %1;" : "=f"(y) : "f"(x));
  return y;
}
__device__ __forceinline__ uint64_t mk_desc(uint32_t addr, uint32_t lbo, uint32_t sbo) {
  return (uint64_t)((addr & 0x3FFFF) >> 4) | ((uint64_t)((lbo & 0x3FFFF) >> 4) << 16) |
         ((uint64_t)((sbo & 0x3FFFF) >> 4) << 32) | (1ull << 62);
}
__device__ __forceinline__ uint64_t mk_desc_o(uint32_t addr, uint32_t lbo, uint32_t sbo) {
  asm volatile("" : "+r"(addr));
  return mk_desc(addr, lbo, sbo);
}
template <int N> __device__ __forceinline__ void reg_fence(uint32_t (&d)[N]) {
#pragma unroll
  for (int i = 0; i < N; i++) asm volatile("" : "+r"(d[i])::"memory");
}
template <int N> __device__ __forceinline__ void reg_fence(float (&d)[N]) {
#pragma unroll
  for (int i = 0; i < N; i++) asm volatile("" : "+f"(d[i])::"memory");
}

template<int TB> __device__ __forceinline__ void wgmma_n144_ss(float (&d)[72], uint64_t da, uint64_t db, int sc) {
  asm volatile("{\n.reg .pred p;\nsetp.ne.b32 p, %74, 0;\n"
    "wgmma.mma_async.sync.aligned.m64n144k16.f32.bf16.bf16 {%0, %1, %2, %3, %4, %5, %6, %7, %8, %9, %10, %11, %12, %13, %14, %15, %16, %17, %18, %19, %20, %21, %22, %23, %24, %25, %26, %27, %28, %29, %30, %31, %32, %33, %34, %35, %36, %37, %38, %39, %40, %41, %42, %43, %44, %45, %46, %47, %48, %49, %50, %51, %52, %53, %54, %55, %56, %57, %58, %59, %60, %61, %62, %63, %64, %65, %66, %67, %68, %69, %70, %71}, %72, %73, p, 1, 1, 0, %75;\n}\n"
    : "+f"(d[0]), "+f"(d[1]), "+f"(d[2]), "+f"(d[3]), "+f"(d[4]), "+f"(d[5]), "+f"(d[6]), "+f"(d[7]), "+f"(d[8]), "+f"(d[9]), "+f"(d[10]), "+f"(d[11]), "+f"(d[12]), "+f"(d[13]), "+f"(d[14]), "+f"(d[15]), "+f"(d[16]), "+f"(d[17]), "+f"(d[18]), "+f"(d[19]), "+f"(d[20]), "+f"(d[21]), "+f"(d[22]), "+f"(d[23]), "+f"(d[24]), "+f"(d[25]), "+f"(d[26]), "+f"(d[27]), "+f"(d[28]), "+f"(d[29]), "+f"(d[30]), "+f"(d[31]), "+f"(d[32]), "+f"(d[33]), "+f"(d[34]), "+f"(d[35]), "+f"(d[36]), "+f"(d[37]), "+f"(d[38]), "+f"(d[39]), "+f"(d[40]), "+f"(d[41]), "+f"(d[42]), "+f"(d[43]), "+f"(d[44]), "+f"(d[45]), "+f"(d[46]), "+f"(d[47]), "+f"(d[48]), "+f"(d[49]), "+f"(d[50]), "+f"(d[51]), "+f"(d[52]), "+f"(d[53]), "+f"(d[54]), "+f"(d[55]), "+f"(d[56]), "+f"(d[57]), "+f"(d[58]), "+f"(d[59]), "+f"(d[60]), "+f"(d[61]), "+f"(d[62]), "+f"(d[63]), "+f"(d[64]), "+f"(d[65]), "+f"(d[66]), "+f"(d[67]), "+f"(d[68]), "+f"(d[69]), "+f"(d[70]), "+f"(d[71])
    : "l"(da), "l"(db), "r"(sc), "n"(TB));
}
template<int TB> __device__ __forceinline__ void wgmma_n192_rs(float (&d)[96], const uint32_t (&a)[4], uint64_t db, int sc) {
  asm volatile("{\n.reg .pred p;\nsetp.ne.b32 p, %101, 0;\n"
    "wgmma.mma_async.sync.aligned.m64n192k16.f32.bf16.bf16 {%0, %1, %2, %3, %4, %5, %6, %7, %8, %9, %10, %11, %12, %13, %14, %15, %16, %17, %18, %19, %20, %21, %22, %23, %24, %25, %26, %27, %28, %29, %30, %31, %32, %33, %34, %35, %36, %37, %38, %39, %40, %41, %42, %43, %44, %45, %46, %47, %48, %49, %50, %51, %52, %53, %54, %55, %56, %57, %58, %59, %60, %61, %62, %63, %64, %65, %66, %67, %68, %69, %70, %71, %72, %73, %74, %75, %76, %77, %78, %79, %80, %81, %82, %83, %84, %85, %86, %87, %88, %89, %90, %91, %92, %93, %94, %95}, {%96, %97, %98, %99}, %100, p, 1, 1, %102;\n}\n"
    : "+f"(d[0]), "+f"(d[1]), "+f"(d[2]), "+f"(d[3]), "+f"(d[4]), "+f"(d[5]), "+f"(d[6]), "+f"(d[7]), "+f"(d[8]), "+f"(d[9]), "+f"(d[10]), "+f"(d[11]), "+f"(d[12]), "+f"(d[13]), "+f"(d[14]), "+f"(d[15]), "+f"(d[16]), "+f"(d[17]), "+f"(d[18]), "+f"(d[19]), "+f"(d[20]), "+f"(d[21]), "+f"(d[22]), "+f"(d[23]), "+f"(d[24]), "+f"(d[25]), "+f"(d[26]), "+f"(d[27]), "+f"(d[28]), "+f"(d[29]), "+f"(d[30]), "+f"(d[31]), "+f"(d[32]), "+f"(d[33]), "+f"(d[34]), "+f"(d[35]), "+f"(d[36]), "+f"(d[37]), "+f"(d[38]), "+f"(d[39]), "+f"(d[40]), "+f"(d[41]), "+f"(d[42]), "+f"(d[43]), "+f"(d[44]), "+f"(d[45]), "+f"(d[46]), "+f"(d[47]), "+f"(d[48]), "+f"(d[49]), "+f"(d[50]), "+f"(d[51]), "+f"(d[52]), "+f"(d[53]), "+f"(d[54]), "+f"(d[55]), "+f"(d[56]), "+f"(d[57]), "+f"(d[58]), "+f"(d[59]), "+f"(d[60]), "+f"(d[61]), "+f"(d[62]), "+f"(d[63]), "+f"(d[64]), "+f"(d[65]), "+f"(d[66]), "+f"(d[67]), "+f"(d[68]), "+f"(d[69]), "+f"(d[70]), "+f"(d[71]), "+f"(d[72]), "+f"(d[73]), "+f"(d[74]), "+f"(d[75]), "+f"(d[76]), "+f"(d[77]), "+f"(d[78]), "+f"(d[79]), "+f"(d[80]), "+f"(d[81]), "+f"(d[82]), "+f"(d[83]), "+f"(d[84]), "+f"(d[85]), "+f"(d[86]), "+f"(d[87]), "+f"(d[88]), "+f"(d[89]), "+f"(d[90]), "+f"(d[91]), "+f"(d[92]), "+f"(d[93]), "+f"(d[94]), "+f"(d[95])
    : "r"(a[0]), "r"(a[1]), "r"(a[2]), "r"(a[3]), "l"(db), "r"(sc), "n"(TB));
}
template<int TB> __device__ __forceinline__ void wgmma_n64_rs(float (&d)[32], const uint32_t (&a)[4], uint64_t db, int sc) {
  asm volatile("{\n.reg .pred p;\nsetp.ne.b32 p, %37, 0;\n"
    "wgmma.mma_async.sync.aligned.m64n64k16.f32.bf16.bf16 {%0, %1, %2, %3, %4, %5, %6, %7, %8, %9, %10, %11, %12, %13, %14, %15, %16, %17, %18, %19, %20, %21, %22, %23, %24, %25, %26, %27, %28, %29, %30, %31}, {%32, %33, %34, %35}, %36, p, 1, 1, %38;\n}\n"
    : "+f"(d[0]), "+f"(d[1]), "+f"(d[2]), "+f"(d[3]), "+f"(d[4]), "+f"(d[5]), "+f"(d[6]), "+f"(d[7]), "+f"(d[8]), "+f"(d[9]), "+f"(d[10]), "+f"(d[11]), "+f"(d[12]), "+f"(d[13]), "+f"(d[14]), "+f"(d[15]), "+f"(d[16]), "+f"(d[17]), "+f"(d[18]), "+f"(d[19]), "+f"(d[20]), "+f"(d[21]), "+f"(d[22]), "+f"(d[23]), "+f"(d[24]), "+f"(d[25]), "+f"(d[26]), "+f"(d[27]), "+f"(d[28]), "+f"(d[29]), "+f"(d[30]), "+f"(d[31])
    : "r"(a[0]), "r"(a[1]), "r"(a[2]), "r"(a[3]), "l"(db), "r"(sc), "n"(TB));
}
template<int TB> __device__ __forceinline__ void wgmma_n64_ss(float (&d)[32], uint64_t da, uint64_t db, int sc) {
  asm volatile("{\n.reg .pred p;\nsetp.ne.b32 p, %34, 0;\n"
    "wgmma.mma_async.sync.aligned.m64n64k16.f32.bf16.bf16 {%0, %1, %2, %3, %4, %5, %6, %7, %8, %9, %10, %11, %12, %13, %14, %15, %16, %17, %18, %19, %20, %21, %22, %23, %24, %25, %26, %27, %28, %29, %30, %31}, %32, %33, p, 1, 1, 0, %35;\n}\n"
    : "+f"(d[0]), "+f"(d[1]), "+f"(d[2]), "+f"(d[3]), "+f"(d[4]), "+f"(d[5]), "+f"(d[6]), "+f"(d[7]), "+f"(d[8]), "+f"(d[9]), "+f"(d[10]), "+f"(d[11]), "+f"(d[12]), "+f"(d[13]), "+f"(d[14]), "+f"(d[15]), "+f"(d[16]), "+f"(d[17]), "+f"(d[18]), "+f"(d[19]), "+f"(d[20]), "+f"(d[21]), "+f"(d[22]), "+f"(d[23]), "+f"(d[24]), "+f"(d[25]), "+f"(d[26]), "+f"(d[27]), "+f"(d[28]), "+f"(d[29]), "+f"(d[30]), "+f"(d[31])
    : "l"(da), "l"(db), "r"(sc), "n"(TB));
}

struct FragAddr {
  uint32_t rowoff;
  uint32_t rx;
  uint32_t hi;
  __device__ __forceinline__ FragAddr(int warp_in_wg, int lane) {
    int row = 16 * warp_in_wg + (lane & 7) + ((lane >> 3) & 1) * 8;
    rowoff = row * 128;
    rx = row & 7;
    hi = lane >> 4;
  }
  __device__ __forceinline__ uint32_t at(uint32_t chunk_base, int kk4) const {
    return chunk_base + rowoff + ((((uint32_t)kk4 * 2 + hi) ^ rx) << 4);
  }
};

__device__ __forceinline__ void layernorm_frags(uint32_t (&f)[12][4]) {
  float s0 = 0.f, s1 = 0.f;
#pragma unroll
  for (int k = 0; k < 12; k++) {
    s0 += bf_lo(f[k][0]) + bf_hi(f[k][0]) + bf_lo(f[k][2]) + bf_hi(f[k][2]);
    s1 += bf_lo(f[k][1]) + bf_hi(f[k][1]) + bf_lo(f[k][3]) + bf_hi(f[k][3]);
  }
  s0 += __shfl_xor_sync(0xffffffffu, s0, 1); s0 += __shfl_xor_sync(0xffffffffu, s0, 2);
  s1 += __shfl_xor_sync(0xffffffffu, s1, 1); s1 += __shfl_xor_sync(0xffffffffu, s1, 2);
  const float m0 = s0 * (1.f / 192.f), m1 = s1 * (1.f / 192.f);
  float v0 = 0.f, v1 = 0.f;
#pragma unroll
  for (int k = 0; k < 12; k++) {
    float a;
    a = bf_lo(f[k][0]) - m0; v0 += a * a; a = bf_hi(f[k][0]) - m0; v0 += a * a;
    a = bf_lo(f[k][2]) - m0; v0 += a * a; a = bf_hi(f[k][2]) - m0; v0 += a * a;
    a = bf_lo(f[k][1]) - m1; v1 += a * a; a = bf_hi(f[k][1]) - m1; v1 += a * a;
    a = bf_lo(f[k][3]) - m1; v1 += a * a; a = bf_hi(f[k][3]) - m1; v1 += a * a;
  }
  v0 += __shfl_xor_sync(0xffffffffu, v0, 1); v0 += __shfl_xor_sync(0xffffffffu, v0, 2);
  v1 += __shfl_xor_sync(0xffffffffu, v1, 1); v1 += __shfl_xor_sync(0xffffffffu, v1, 2);
  const float r0 = rsqrtf(v0 * (1.f / 192.f) + 1e-5f), r1 = rsqrtf(v1 * (1.f / 192.f) + 1e-5f);
#pragma unroll
  for (int k = 0; k < 12; k++) {
    f[k][0] = pack_bf16((bf_lo(f[k][0]) - m0) * r0, (bf_hi(f[k][0]) - m0) * r0);
    f[k][2] = pack_bf16((bf_lo(f[k][2]) - m0) * r0, (bf_hi(f[k][2]) - m0) * r0);
    f[k][1] = pack_bf16((bf_lo(f[k][1]) - m1) * r1, (bf_hi(f[k][1]) - m1) * r1);
    f[k][3] = pack_bf16((bf_lo(f[k][3]) - m1) * r1, (bf_hi(f[k][3]) - m1) * r1);
  }
}

constexpr int A_NST = 5;
constexpr int A_XS = 0;
constexpr int A_VB = 49152;
constexpr int A_W = 98304;
constexpr int A_BAR = A_W + A_NST * 24576;
constexpr int A_SMEM = A_BAR + 256 + 1024;
constexpr int A_FOLD = 36;

__device__ __forceinline__ void a_issue(float (&acc)[32], const uint32_t (&af)[12][4], uint32_t sb, int s) {
  const int st = s % A_NST;
  mbar_wait(sb + A_BAR + st * 8, (s / A_NST) & 1);
  const uint64_t wd = mk_desc_o(sb + A_W + st * 24576, 8192, 1024);
  wg_fence();
#pragma unroll
  for (int kk = 0; kk < 12; kk++) wgmma_n64_rs<1>(acc, af[kk], wd + kk * 128, kk > 0);
  wg_commit();
}
__device__ __forceinline__ void a_release(uint32_t sb, int s, int lane) {
  if (lane == 0) mbar_arrive(sb + A_BAR + 64 + (s % A_NST) * 8);
}
__device__ __forceinline__ void cvt_frags(uint32_t (*dst)[4], const float (&acc)[32]) {
#pragma unroll
  for (int k = 0; k < 4; k++) {
    dst[k][0] = pack_bf16(acc[8 * k + 0], acc[8 * k + 1]);
    dst[k][1] = pack_bf16(acc[8 * k + 2], acc[8 * k + 3]);
    dst[k][2] = pack_bf16(acc[8 * k + 4], acc[8 * k + 5]);
    dst[k][3] = pack_bf16(acc[8 * k + 6], acc[8 * k + 7]);
  }
}
__device__ __forceinline__ void store_chunk(const float (&acc)[32], uint32_t chunk_base, const FragAddr& fa) {
  uint32_t t[4][4];
  cvt_frags(t, acc);
#pragma unroll
  for (int k = 0; k < 4; k++) stsm_x4(fa.at(chunk_base, k), t[k]);
}
__device__ __forceinline__ void resid_chunk(uint32_t (*dst)[4], const float* acc, float s0, float s1, uint32_t chunk_base,
                                            const FragAddr& fa) {
#pragma unroll
  for (int k = 0; k < 4; k++) {
    uint32_t x[4];
    ldsm_x4(x, fa.at(chunk_base, k));
    uint32_t o[4];
    o[0] = pack_bf16(fmaf(acc[8 * k + 0], s0, bf_lo(x[0])), fmaf(acc[8 * k + 1], s0, bf_hi(x[0])));
    o[1] = pack_bf16(fmaf(acc[8 * k + 2], s1, bf_lo(x[1])), fmaf(acc[8 * k + 3], s1, bf_hi(x[1])));
    o[2] = pack_bf16(fmaf(acc[8 * k + 4], s0, bf_lo(x[2])), fmaf(acc[8 * k + 5], s0, bf_hi(x[2])));
    o[3] = pack_bf16(fmaf(acc[8 * k + 6], s1, bf_lo(x[3])), fmaf(acc[8 * k + 7], s1, bf_hi(x[3])));
    stsm_x4(fa.at(chunk_base, k), o);
    if (dst) { dst[k][0] = o[0]; dst[k][1] = o[1]; dst[k][2] = o[2]; dst[k][3] = o[3]; }
  }
}

__global__ void __launch_bounds__(384, 1)
kernelA(const __grid_constant__ CUtensorMap tm_x, const __grid_constant__ CUtensorMap tm_wq64t,
        const __grid_constant__ CUtensorMap tm_wot, const __grid_constant__ CUtensorMap tm_wq64s,
        const __grid_constant__ CUtensorMap tm_wos, const __grid_constant__ CUtensorMap tm_wf,
        const __grid_constant__ CUtensorMap tm_x1, const __grid_constant__ CUtensorMap tm_qkv) {
  extern __shared__ uint8_t smem_raw[];
  const uint32_t sb = (smem_u32(smem_raw) + 1023) & ~1023u;
  const int tid = threadIdx.x, warp = tid >> 5, lane = tid & 31;
  const bool is_fold = blockIdx.x < A_FOLD;
  const int blk = blockIdx.x - A_FOLD;
  if (tid == 256) {
    for (int i = 0; i < A_NST; i++) { mbar_init(sb + A_BAR + i * 8, 1); mbar_init(sb + A_BAR + 64 + i * 8, 8); }
    mbar_init(sb + A_BAR + 128, 1); mbar_init(sb + A_BAR + 136, 1);
    asm volatile("fence.mbarrier_init.release.cluster;" ::: "memory");
    if (!is_fold) {
      for (int w = 0; w < 2; w++) {
        const uint32_t bar = sb + A_BAR + 128 + w * 8;
        mbar_expect_tx(bar, 3 * 63 * 128);
        for (int c = 0; c < 3; c++)
          tma_load_3d(sb + A_XS + w * 24576 + c * 8192, &tm_x, bar, c * 64, (blk * 2 + w) * 9, 0);
      }
    } else {
      const int mat = blockIdx.x / 9, rs = (blockIdx.x % 9) / 3, cs = blockIdx.x % 3;
      const CUtensorMap* mq = (mat < 2) ? &tm_wq64t : &tm_wq64s;
      const CUtensorMap* mo = (mat < 2) ? &tm_wot : &tm_wos;
      const uint32_t bar = sb + A_BAR + 128;
      mbar_expect_tx(bar, 2 * 24576);
      for (int c = 0; c < 3; c++) tma_load_2d(sb + c * 8192, mq, bar, ((mat & 1) ? 384 : 0) + c * 64, rs * 64);
      if (mat & 1) tma_load_2d(sb + 24576, mo, bar, cs * 64, 0);
      else for (int c = 0; c < 3; c++) tma_load_2d(sb + 24576 + c * 8192, mq, bar, 192 + c * 64, cs * 64);
    }
  }
  if (blockIdx.x == 0 && tid < 128) g_flag[tid] = 0;
  if (!is_fold && tid < 48) {
    uint32_t a = sb + A_XS + (tid >> 3) * 8192 + 63 * 128 + (tid & 7) * 16;
    asm volatile("st.shared.v4.b32 [%0], {%1,%1,%1,%1};" ::"r"(a), "r"(0) : "memory");
  }
  __syncthreads();

  if (warp >= 8) {
    asm volatile("setmaxnreg.dec.sync.aligned.u32 24;");
    if (warp == 8 && lane == 0 && !is_fold) {
      for (int s = 0; s < 12; s++) {
        const int st = s % A_NST;
        const int g = s / 3;
        const int mat = (g == 0) ? 1 : (g == 1) ? 0 : g;
        if (s % 3 == 0) {
          uint32_t n = 0, v;
          do {
            asm volatile("ld.acquire.gpu.global.u32 %0, [%1];" : "=r"(v) : "l"(&g_wflag[mat]) : "memory");
          } while (v < 9u && ++n < (1u << 22));
          asm volatile("fence.proxy.async;" ::: "memory");
        }
        if (s >= A_NST) mbar_wait(sb + A_BAR + 64 + st * 8, ((s / A_NST) - 1) & 1);
        mbar_expect_tx(sb + A_BAR + st * 8, 24576);
        tma_load_2d(sb + A_W + st * 24576, &tm_wf, sb + A_BAR + st * 8, (mat & 1) * 192 + (s % 3) * 64, (mat >> 1) * 192);
      }
    }
    return;
  }

  asm volatile("setmaxnreg.inc.sync.aligned.u32 240;");
  const int wg = warp >> 2, wq = warp & 3;

  if (is_fold) {
    if (wg == 0) {
      const int mat = blockIdx.x / 9, rs = (blockIdx.x % 9) / 3, cs = blockIdx.x % 3;
      float d[32];
      mbar_wait(sb + A_BAR + 128, 0);
      const uint64_t ad = mk_desc_o(sb, 16, 1024);
      if (mat & 1) {
        const uint64_t bd = mk_desc_o(sb + 24576, 8192, 1024);
        wg_fence();
#pragma unroll
        for (int kk = 0; kk < 12; kk++) wgmma_n64_ss<1>(d, ad + (kk >> 2) * 512 + (kk & 3) * 2, bd + kk * 128, kk > 0);
        wg_commit();
      } else {
        const uint64_t bd = mk_desc_o(sb + 24576, 16, 1024);
        wg_fence();
#pragma unroll
        for (int kk = 0; kk < 12; kk++)
          wgmma_n64_ss<0>(d, ad + (kk >> 2) * 512 + (kk & 3) * 2, bd + (kk >> 2) * 512 + (kk & 3) * 2, kk > 0);
        wg_commit();
      }
      wg_wait<0>(); reg_fence(d);
      const int r0 = rs * 64 + wq * 16 + (lane >> 2);
      uint32_t* dst = reinterpret_cast<uint32_t*>(g_wf + ((size_t)(mat >> 1) * 192 + r0) * 384 + (mat & 1) * 192 + cs * 64 + (lane & 3) * 2);
#pragma unroll
      for (int j = 0; j < 8; j++) {
        dst[j * 4] = pack_bf16(d[4 * j], d[4 * j + 1]);
        dst[8 * 192 + j * 4] = pack_bf16(d[4 * j + 2], d[4 * j + 3]);
      }
      asm volatile("fence.proxy.async;" ::: "memory");
      __threadfence();
      named_bar(1, 128);
      if (tid == 0) atomicAdd(&g_wflag[mat], 1u);
    }
    return;
  }

  const int n0 = (blk * 2 + wg) * 9;
  const FragAddr fa(wq, lane);
  const uint32_t xs = sb + A_XS + wg * 24576, vb = sb + A_VB + wg * 24576;
  const int barid = 1 + wg;
  const bool elected = (tid & 127) == 0;

  uint32_t h[12][4];
  TS(0, 0);
  mbar_wait(sb + A_BAR + 128 + wg * 8, 0);
  TS(0, 1);
#pragma unroll
  for (int k = 0; k < 12; k++) ldsm_x4(h[k], fa.at(xs + (k >> 2) * 8192, k & 3));
  layernorm_frags(h);
#pragma unroll
  for (int k = 0; k < 12; k++) stsm_x4(fa.at(xs + (k >> 2) * 8192, k & 3), h[k]);

  float acc0[32], acc1[32];
  uint32_t qf[12][4];
  TS(0, 2);
  a_issue(acc0, h, sb, 0);
  TS(0, 3);
  a_issue(acc1, h, sb, 1); wg_wait<1>(); reg_fence(acc0); a_release(sb, 0, lane); store_chunk(acc0, vb, fa);
  a_issue(acc0, h, sb, 2); wg_wait<1>(); reg_fence(acc1); a_release(sb, 1, lane); store_chunk(acc1, vb + 8192, fa);
  a_issue(acc1, h, sb, 3); wg_wait<1>(); reg_fence(acc0); a_release(sb, 2, lane); store_chunk(acc0, vb + 16384, fa);
  fence_proxy_async();
  named_bar(barid, 128);
  a_issue(acc0, h, sb, 4); wg_wait<1>(); reg_fence(acc1); a_release(sb, 3, lane); cvt_frags(&qf[0], acc1);
  a_issue(acc1, h, sb, 5); wg_wait<1>(); reg_fence(acc0); a_release(sb, 4, lane); cvt_frags(&qf[4], acc0);
  wg_wait<0>(); reg_fence(acc1); a_release(sb, 5, lane); cvt_frags(&qf[8], acc1);
  TS(0, 4);
  {
    const uint64_t kd = mk_desc_o(xs, 16, 1024);
    wg_fence();
#pragma unroll
    for (int kk = 0; kk < 12; kk++) wgmma_n64_rs<0>(acc0, qf[kk], kd + (kk >> 2) * 512 + (kk & 3) * 2, kk > 0);
    wg_commit();
    wg_wait<0>(); reg_fence(acc0);
  }
  named_bar(barid, 128);
  if (elected) {
    const uint32_t bar = sb + A_BAR + 128 + wg * 8;
    mbar_expect_tx(bar, 3 * 63 * 128);
    for (int c = 0; c < 3; c++) tma_load_3d(xs + c * 8192, &tm_x, bar, c * 64, n0, 0);
  }
  uint32_t pf[4][4];
  {
    const int r0 = 16 * wq + (lane >> 2), r1 = r0 + 8;
    const unsigned long long MB = 0x0040201008040201ull;
    const unsigned long long mk0 = (MB << (r0 % 9)) >> (2 * (lane & 3));
    const unsigned long long mk1 = (MB << (r1 % 9)) >> (2 * (lane & 3));
    const float cs = 0.07216878364870322f * 1.4426950408889634f;
    float mx0 = -INFINITY, mx1 = -INFINITY;
#pragma unroll
    for (int j = 0; j < 8; j++) {
#pragma unroll
      for (int e = 0; e < 2; e++) {
        bool v0 = (mk0 >> (8 * j + e)) & 1, v1 = (mk1 >> (8 * j + e)) & 1;
        acc0[4 * j + e] = v0 ? acc0[4 * j + e] * cs : -INFINITY;
        acc0[4 * j + 2 + e] = v1 ? acc0[4 * j + 2 + e] * cs : -INFINITY;
        mx0 = fmaxf(mx0, acc0[4 * j + e]);
        mx1 = fmaxf(mx1, acc0[4 * j + 2 + e]);
      }
    }
    mx0 = fmaxf(mx0, __shfl_xor_sync(0xffffffffu, mx0, 1)); mx0 = fmaxf(mx0, __shfl_xor_sync(0xffffffffu, mx0, 2));
    mx1 = fmaxf(mx1, __shfl_xor_sync(0xffffffffu, mx1, 1)); mx1 = fmaxf(mx1, __shfl_xor_sync(0xffffffffu, mx1, 2));
    float l0 = 0.f, l1 = 0.f;
#pragma unroll
    for (int j = 0; j < 8; j++) {
#pragma unroll
      for (int e = 0; e < 2; e++) {
        acc0[4 * j + e] = ex2(acc0[4 * j + e] - mx0); l0 += acc0[4 * j + e];
        acc0[4 * j + 2 + e] = ex2(acc0[4 * j + 2 + e] - mx1); l1 += acc0[4 * j + 2 + e];
      }
    }
    l0 += __shfl_xor_sync(0xffffffffu, l0, 1); l0 += __shfl_xor_sync(0xffffffffu, l0, 2);
    l1 += __shfl_xor_sync(0xffffffffu, l1, 1); l1 += __shfl_xor_sync(0xffffffffu, l1, 2);
    const float i0 = 1.f / l0, i1 = 1.f / l1;
#pragma unroll
    for (int j = 0; j < 8; j++) {
      acc0[4 * j] *= i0; acc0[4 * j + 1] *= i0; acc0[4 * j + 2] *= i1; acc0[4 * j + 3] *= i1;
    }
    cvt_frags(pf, acc0);
  }
  TS(0, 5);
  {
    float oacc[96];
    const uint64_t vd = mk_desc_o(vb, 8192, 1024);
    wg_fence();
#pragma unroll
    for (int kk = 0; kk < 4; kk++) wgmma_n192_rs<1>(oacc, pf[kk], vd + kk * 128, kk > 0);
    wg_commit();
    wg_wait<0>(); reg_fence(oacc);
    TS(0, 6);
    mbar_wait(sb + A_BAR + 128 + wg * 8, 1);
#pragma unroll
    for (int c = 0; c < 3; c++) resid_chunk(&h[4 * c], &oacc[32 * c], 1.f, 1.f, xs + c * 8192, fa);
  }
  TS(0, 7);
  layernorm_frags(h);
  named_bar(barid, 128);
#pragma unroll
  for (int k = 0; k < 12; k++) stsm_x4(fa.at(vb + (k >> 2) * 8192, k & 3), h[k]);
  TS(0, 8);
  a_issue(acc0, h, sb, 6);
  fence_proxy_async();
  named_bar(barid, 128);
  if (elected) {
    for (int c = 0; c < 3; c++) tma_store_3d(&tm_x1, xs + c * 8192, c * 64, n0, 0);
    for (int c = 0; c < 3; c++) tma_store_3d(&tm_qkv, vb + c * 8192, 192 + c * 64, n0, 0);
    bulk_commit();
  }
  a_issue(acc1, h, sb, 7); wg_wait<1>(); reg_fence(acc0); a_release(sb, 6, lane);
  if (elected) bulk_wait_read0();
  named_bar(barid, 128);
  store_chunk(acc0, xs, fa);
  a_issue(acc0, h, sb, 8); wg_wait<1>(); reg_fence(acc1); store_chunk(acc1, xs + 8192, fa);
  a_issue(acc1, h, sb, 9); wg_wait<1>(); reg_fence(acc0); store_chunk(acc0, xs + 16384, fa);
  fence_proxy_async();
  named_bar(barid, 128);
  if (elected) {
    for (int c = 0; c < 3; c++) tma_store_3d(&tm_qkv, xs + c * 8192, c * 64, n0, 0);
    bulk_commit();
  }
  a_issue(acc0, h, sb, 10); wg_wait<1>(); reg_fence(acc1); store_chunk(acc1, vb, fa);
  a_issue(acc1, h, sb, 11); wg_wait<1>(); reg_fence(acc0); store_chunk(acc0, vb + 8192, fa);
  wg_wait<0>(); reg_fence(acc1); store_chunk(acc1, vb + 16384, fa);
  fence_proxy_async();
  named_bar(barid, 128);
  TS(0, 9);
  if (elected) {
    for (int c = 0; c < 3; c++) tma_store_3d(&tm_qkv, vb + c * 8192, 384 + c * 64, n0, 0);
    bulk_commit();
    bulk_wait0();
  }
  TS(0, 10);
}

constexpr int B_GRID = 132;
constexpr int B_SLOT = 55296;
constexpr int B_Q = 0;
constexpr int B_KV = 49152;
constexpr int B_BAR = B_KV + 3 * B_SLOT;
constexpr int B_SMEM = B_BAR + 256 + 1024;

__device__ __forceinline__ void bar_arrive(int id, int nthreads) {
  asm volatile("bar.arrive %0, %1;" ::"r"(id), "r"(nthreads) : "memory");
}
__device__ __forceinline__ void b_segment(int sg, int& tile, int& k0, int& k1) {
  const int grp = blockIdx.x / 12, ci = blockIdx.x - grp * 12;
  if (ci < 7) { tile = grp * 7 + ci; k0 = 3; k1 = 9; }
  else {
    const int hh = ci - 7;
    tile = grp * 7 + ((0x54210 >> (4 * hh)) & 15) + sg;
    k0 = sg ? 0 : ((0x10210 >> (4 * hh)) & 15);
    k1 = sg ? ((0x31321 >> (4 * hh)) & 15) : 3;
  }
}

__global__ void __launch_bounds__(384, 1)
kernelB(const __grid_constant__ CUtensorMap tm_q, const __grid_constant__ CUtensorMap tm_kv,
        const __grid_constant__ CUtensorMap tm_x1, const __grid_constant__ CUtensorMap tm_out) {
  extern __shared__ uint8_t smem_raw[];
  const uint32_t sb = (smem_u32(smem_raw) + 1023) & ~1023u;
  const int tid = threadIdx.x, warp = tid >> 5, lane = tid & 31;
  const uint32_t bF = sb + B_BAR, bE = sb + B_BAR + 32, bQF = sb + B_BAR + 64, bQE = sb + B_BAR + 72;
  if (tid == 0) {
    for (int i = 0; i < 3; i++) { mbar_init(bF + i * 8, 1); mbar_init(bE + i * 8, 8); }
    mbar_init(bQF, 1); mbar_init(bQE, 8);
    asm volatile("fence.mbarrier_init.release.cluster;" ::: "memory");
  }
  __syncthreads();
  const int grp = blockIdx.x / 12, ci = blockIdx.x - grp * 12;
  const bool owner = ci < 7;
  const int nseg = owner ? 1 : 2;

  if (warp >= 8) {
    asm volatile("setmaxnreg.dec.sync.aligned.u32 24;");
    if (warp == 8 && lane == 0) {
      if (blockIdx.x == 0) { g_wflag[0] = 0; g_wflag[1] = 0; g_wflag[2] = 0; g_wflag[3] = 0; }
      int it = 0;
      for (int sg = 0; sg < nseg; sg++) {
        int tile, k0, k1;
        b_segment(sg, tile, k0, k1);
        const int t = tile / 11, qt = tile - t * 11;
        if (sg > 0) mbar_wait(bQE, 0);
        mbar_expect_tx(bQF, 49152);
        for (int c = 0; c < 3; c++) tma_load_3d(sb + B_Q + c * 16384, &tm_q, bQF, c * 64, qt * 128, t);
        const int n = k1 - k0;
        for (int e = 0; e < 2 * n; e++) {
          const int sl = it % 3;
          if (it >= 3) mbar_wait(bE + sl * 8, ((it / 3) - 1) & 1);
          mbar_expect_tx(bF + sl * 8, B_SLOT);
          for (int c = 0; c < 3; c++)
            tma_load_3d(sb + B_KV + sl * B_SLOT + c * 18432, &tm_kv, bF + sl * 8, 192 + (e & 1) * 192 + c * 64, (k0 + (e >> 1)) * 144, t);
          it++;
        }
      }
      if (owner) {
        const int tile = grp * 7 + ci;
        const int t = tile / 11, qt = tile - t * 11;
        mbar_wait(bQE, 0);
        mbar_expect_tx(bQF, 49152);
        for (int c = 0; c < 3; c++) tma_load_3d(sb + B_Q + c * 16384, &tm_x1, bQF, c * 64, qt * 128, t);
      }
    } else if ((warp == 9 || warp == 10) && !owner) {
      for (int sg = 0; sg < 2; sg++) {
        named_bar(5 + (warp - 9), 160);
        if (lane == 0) {
          __threadfence();
          atomicAdd(&g_flag[(grp * 5 + (ci - 7)) * 2 + sg], 1u);
        }
        __syncwarp();
      }
    }
    return;
  }

  asm volatile("setmaxnreg.inc.sync.aligned.u32 240;");
  const int wg = warp >> 2, wq = warp & 3;
  const int wtid = tid & 127;
  const float cs = 0.07216878364870322f * 1.4426950408889634f;
  float oacc[96], sacc[72];
  uint32_t pf[9][4];
  float m0, m1, l0, l1;
  int it = 0;
  const uint32_t qb = sb + B_Q + wg * 8192;
  if (wg == 1) bar_arrive(3, 256);
  TS(1, 0);
  int tsi = 1;

  auto issue_qk = [&](int slot) {
    const uint64_t kd = mk_desc_o(sb + B_KV + slot * B_SLOT, 16, 1024);
    const uint64_t qd = mk_desc_o(qb, 16, 1024);
#pragma unroll
    for (int kk = 0; kk < 12; kk++)
      wgmma_n144_ss<0>(sacc, qd + (kk >> 2) * 1024 + (kk & 3) * 2, kd + (kk >> 2) * 1152 + (kk & 3) * 2, kk > 0);
    wg_commit();
  };
  auto issue_pv = [&](int slot, int accum) {
    const uint64_t vd = mk_desc_o(sb + B_KV + slot * B_SLOT, 18432, 1024);
#pragma unroll
    for (int kk = 0; kk < 9; kk++) wgmma_n192_rs<1>(oacc, pf[kk], vd + kk * 128, kk > 0 ? 1 : accum);
    wg_commit();
  };
  auto softmax = [&](bool rescale) {
    float t0[4], t1[4];
#pragma unroll
    for (int q = 0; q < 4; q++) {
      t0[q] = fmaxf(sacc[4 * q], sacc[4 * q + 1]);
      t1[q] = fmaxf(sacc[4 * q + 2], sacc[4 * q + 3]);
    }
#pragma unroll
    for (int j = 4; j < 18; j++) {
      t0[j & 3] = fmaxf(t0[j & 3], fmaxf(sacc[4 * j], sacc[4 * j + 1]));
      t1[j & 3] = fmaxf(t1[j & 3], fmaxf(sacc[4 * j + 2], sacc[4 * j + 3]));
    }
    float mx0 = fmaxf(fmaxf(t0[0], t0[1]), fmaxf(fmaxf(t0[2], t0[3]), m0));
    float mx1 = fmaxf(fmaxf(t1[0], t1[1]), fmaxf(fmaxf(t1[2], t1[3]), m1));
    mx0 = fmaxf(mx0, __shfl_xor_sync(0xffffffffu, mx0, 1)); mx1 = fmaxf(mx1, __shfl_xor_sync(0xffffffffu, mx1, 1));
    mx0 = fmaxf(mx0, __shfl_xor_sync(0xffffffffu, mx0, 2)); mx1 = fmaxf(mx1, __shfl_xor_sync(0xffffffffu, mx1, 2));
    const float a0 = ex2((m0 - mx0) * cs), a1 = ex2((m1 - mx1) * cs);
    m0 = mx0; m1 = mx1;
    const float mc0 = mx0 * cs, mc1 = mx1 * cs;
#pragma unroll
    for (int q = 0; q < 4; q++) { t0[q] = 0.f; t1[q] = 0.f; }
#pragma unroll
    for (int k = 0; k < 9; k++) {
      float p[8];
#pragma unroll
      for (int e = 0; e < 8; e++) p[e] = ex2(fmaf(sacc[8 * k + e], cs, (e & 2) ? -mc1 : -mc0));
      t0[0] += p[0]; t0[1] += p[1]; t0[2] += p[4]; t0[3] += p[5];
      t1[0] += p[2]; t1[1] += p[3]; t1[2] += p[6]; t1[3] += p[7];
      pf[k][0] = pack_bf16(p[0], p[1]); pf[k][1] = pack_bf16(p[2], p[3]);
      pf[k][2] = pack_bf16(p[4], p[5]); pf[k][3] = pack_bf16(p[6], p[7]);
    }
    l0 = l0 * a0 + ((t0[0] + t0[1]) + (t0[2] + t0[3]));
    l1 = l1 * a1 + ((t1[0] + t1[1]) + (t1[2] + t1[3]));
    if (rescale) {
#pragma unroll
      for (int i = 0; i < 24; i++) {
        oacc[4 * i] *= a0; oacc[4 * i + 1] *= a0; oacc[4 * i + 2] *= a1; oacc[4 * i + 3] *= a1;
      }
    }
  };

  for (int sg = 0; sg < nseg; sg++) {
    int n;
    { int tile, k0, k1; b_segment(sg, tile, k0, k1); n = k1 - k0; }
    m0 = m1 = -INFINITY; l0 = l1 = 0.f;
    mbar_wait(bQF, sg & 1);
    {
      const int sl = it % 3;
      mbar_wait(bF + sl * 8, (it / 3) & 1);
      named_bar(3 + wg, 256);
      wg_fence();
      issue_qk(sl);
      bar_arrive(3 + (wg ^ 1), 256);
      wg_wait<0>(); reg_fence(sacc);
      if (lane == 0) { mbar_arrive(bE + sl * 8); if (n == 1) mbar_arrive(bQE); }
      it++;
      softmax(false);
    }
    TS(1, tsi); tsi++;
    for (int j = 1; j < n; j++) {
      const int slv = it % 3, slk = (it + 1) % 3;
      mbar_wait(bF + slv * 8, (it / 3) & 1);
      named_bar(3 + wg, 256);
      wg_fence();
      issue_pv(slv, j > 1);
      mbar_wait(bF + slk * 8, ((it + 1) / 3) & 1);
      issue_qk(slk);
      bar_arrive(3 + (wg ^ 1), 256);
      wg_wait<1>(); reg_fence(oacc);
      if (lane == 0) mbar_arrive(bE + slv * 8);
      wg_wait<0>(); reg_fence(sacc);
      if (lane == 0) { mbar_arrive(bE + slk * 8); if (j == n - 1) mbar_arrive(bQE); }
      it += 2;
      softmax(true);
      TS(1, tsi); tsi++;
    }
    {
      const int sl = it % 3;
      mbar_wait(bF + sl * 8, (it / 3) & 1);
      named_bar(3 + wg, 256);
      wg_fence();
      issue_pv(sl, n > 1);
      if (!(wg == 1 && sg == nseg - 1)) bar_arrive(3 + (wg ^ 1), 256);
      wg_wait<0>(); reg_fence(oacc);
      if (lane == 0) mbar_arrive(bE + sl * 8);
      it++;
    }
    TS(1, tsi); tsi++;
    if (!owner) {
      const int slot = (grp * 5 + (ci - 7)) * 2 + sg;
      uint4* dst = g_part + (size_t)(slot * 2 + wg) * 13 * 128 + wtid;
#pragma unroll
      for (int i = 0; i < 12; i++)
        dst[i * 128] = make_uint4(pack_bf16(oacc[8 * i], oacc[8 * i + 1]), pack_bf16(oacc[8 * i + 2], oacc[8 * i + 3]),
                                  pack_bf16(oacc[8 * i + 4], oacc[8 * i + 5]), pack_bf16(oacc[8 * i + 6], oacc[8 * i + 7]));
      dst[12 * 128] = make_uint4(__float_as_uint(m0), __float_as_uint(m1), __float_as_uint(l0), __float_as_uint(l1));
      bar_arrive(5 + wg, 160);
      TS(1, tsi); tsi++;
    }
  }
  if (!owner) return;

  {
    const int first = (0x9765310 >> (4 * ci)) & 15, cnt = (0x1211221 >> (4 * ci)) & 15;
    for (int q = 0; q < cnt; q++) {
      const int slot = grp * 10 + first + q;
      if (wtid == 0) {
        uint32_t n = 0, v;
        do {
          asm volatile("ld.acquire.gpu.global.u32 %0, [%1];" : "=r"(v) : "l"(&g_flag[slot]) : "memory");
        } while (v < 2u && ++n < (1u << 22));
      }
      named_bar(1 + wg, 128);
      const uint4* src = g_part + (size_t)(slot * 2 + wg) * 13 * 128 + wtid;
      const uint4 mlu = __ldcg(src + 12 * 128);
      uint4 pv[12];
#pragma unroll
      for (int i = 0; i < 12; i++) pv[i] = __ldcg(src + i * 128);
      const float pm0 = __uint_as_float(mlu.x), pm1 = __uint_as_float(mlu.y);
      const float mx0 = fmaxf(m0, pm0), mx1 = fmaxf(m1, pm1);
      const float a0 = ex2((m0 - mx0) * cs), a1 = ex2((m1 - mx1) * cs);
      const float b0 = ex2((pm0 - mx0) * cs), b1 = ex2((pm1 - mx1) * cs);
      m0 = mx0; m1 = mx1;
      l0 = l0 * a0 + __uint_as_float(mlu.z) * b0; l1 = l1 * a1 + __uint_as_float(mlu.w) * b1;
#pragma unroll
      for (int i = 0; i < 12; i++) {
        oacc[8 * i + 0] = oacc[8 * i + 0] * a0 + bf_lo(pv[i].x) * b0; oacc[8 * i + 1] = oacc[8 * i + 1] * a0 + bf_hi(pv[i].x) * b0;
        oacc[8 * i + 2] = oacc[8 * i + 2] * a1 + bf_lo(pv[i].y) * b1; oacc[8 * i + 3] = oacc[8 * i + 3] * a1 + bf_hi(pv[i].y) * b1;
        oacc[8 * i + 4] = oacc[8 * i + 4] * a0 + bf_lo(pv[i].z) * b0; oacc[8 * i + 5] = oacc[8 * i + 5] * a0 + bf_hi(pv[i].z) * b0;
        oacc[8 * i + 6] = oacc[8 * i + 6] * a1 + bf_lo(pv[i].w) * b1; oacc[8 * i + 7] = oacc[8 * i + 7] * a1 + bf_hi(pv[i].w) * b1;
      }
    }
  }
  TS(1, 21);
  l0 += __shfl_xor_sync(0xffffffffu, l0, 1); l0 += __shfl_xor_sync(0xffffffffu, l0, 2);
  l1 += __shfl_xor_sync(0xffffffffu, l1, 1); l1 += __shfl_xor_sync(0xffffffffu, l1, 2);
  const float i0 = 1.f / l0, i1 = 1.f / l1;
  mbar_wait(bQF, 1);
  const FragAddr fa(wq, lane);
#pragma unroll
  for (int c = 0; c < 3; c++) resid_chunk(nullptr, &oacc[32 * c], i0, i1, qb + c * 16384, fa);
  fence_proxy_async();
  named_bar(1 + wg, 128);
  TS(1, 22);
  if (wtid == 0) {
    const int tile = grp * 7 + ci;
    const int t = tile / 11, qt = tile - t * 11;
    if (qt * 128 + wg * 64 < NL) {
      for (int c = 0; c < 3; c++) tma_store_3d(&tm_out, qb + c * 16384, c * 64, qt * 128 + wg * 64, t);
      bulk_commit();
      bulk_wait0();
    }
  }
  TS(1, 23);
}

typedef CUresult (*EncodeFn)(CUtensorMap*, CUtensorMapDataType, cuuint32_t, void*, const cuuint64_t*, const cuuint64_t*,
                             const cuuint32_t*, const cuuint32_t*, CUtensorMapInterleave, CUtensorMapSwizzle,
                             CUtensorMapL2promotion, CUtensorMapFloatOOBfill);

void make_map(EncodeFn enc, CUtensorMap* m, const void* ptr, int rank, const uint64_t* dims, const uint32_t* box) {
  cuuint64_t gd[3], gs[2];
  cuuint32_t bx[3], es[3] = {1, 1, 1};
  uint64_t stride = 2;
  for (int i = 0; i < rank; i++) {
    gd[i] = dims[i]; bx[i] = box[i];
    stride *= dims[i];
    if (i < rank - 1) gs[i] = stride;
  }
  enc(m, CU_TENSOR_MAP_DATA_TYPE_BFLOAT16, rank, const_cast<void*>(ptr), gd, gs, bx, es, CU_TENSOR_MAP_INTERLEAVE_NONE,
      CU_TENSOR_MAP_SWIZZLE_128B, CU_TENSOR_MAP_L2_PROMOTION_L2_256B, CU_TENSOR_MAP_FLOAT_OOB_FILL_NONE);
}

}

extern "C" void kernel_launch(void* const* d_in, const int* in_sizes, int n_in, void* d_out, int out_size) {
  (void)in_sizes; (void)n_in; (void)out_size;
  EncodeFn enc = nullptr;
  cudaDriverEntryPointQueryResult qres;
  cudaGetDriverEntryPoint("cuTensorMapEncodeTiled", (void**)&enc, cudaEnableDefault, &qres);
  void *p_x1, *p_qkv, *p_wf;
  cudaGetSymbolAddress(&p_wf, g_wf);
  cudaGetSymbolAddress(&p_x1, g_x1);
  cudaGetSymbolAddress(&p_qkv, g_qkv);
  cudaFuncSetAttribute(kernelA, cudaFuncAttributeMaxDynamicSharedMemorySize, A_SMEM);
  cudaFuncSetAttribute(kernelB, cudaFuncAttributeMaxDynamicSharedMemorySize, B_SMEM);

  CUtensorMap tm_x, tm_wqkvt, tm_wot, tm_wqkvs, tm_x1s, tm_qkvs, tm_q, tm_kv, tm_wos, tm_x1l, tm_out, tm_wf;
  const uint64_t d_act[3] = {192, 1296, 7}, d_qkv[3] = {576, 1296, 7}, d_w3[2] = {576, 192}, d_w1[2] = {192, 192}, d_wf[2] = {384, 384};
  const uint32_t b_a[3] = {64, 9, 7}, b_w[2] = {64, 192}, b_q[3] = {64, 128, 1}, b_kv[3] = {64, 144, 1}, b_o[3] = {64, 64, 1}, b_w64[2] = {64, 64};
  make_map(enc, &tm_x, d_in[0], 3, d_act, b_a);
  make_map(enc, &tm_wqkvt, d_in[1], 2, d_w3, b_w64);
  make_map(enc, &tm_wot, d_in[2], 2, d_w1, b_w);
  make_map(enc, &tm_wqkvs, d_in[3], 2, d_w3, b_w64);
  make_map(enc, &tm_wos, d_in[4], 2, d_w1, b_w);
  make_map(enc, &tm_wf, p_wf, 2, d_wf, b_w);
  make_map(enc, &tm_x1s, p_x1, 3, d_act, b_a);
  make_map(enc, &tm_qkvs, p_qkv, 3, d_qkv, b_a);
  make_map(enc, &tm_q, p_qkv, 3, d_qkv, b_q);
  make_map(enc, &tm_kv, p_qkv, 3, d_qkv, b_kv);
  make_map(enc, &tm_x1l, p_x1, 3, d_act, b_q);
  make_map(enc, &tm_out, d_out, 3, d_act, b_o);

  kernelA<<<72 + A_FOLD, 384, A_SMEM>>>(tm_x, tm_wqkvt, tm_wot, tm_wqkvs, tm_wos, tm_wf, tm_x1s, tm_qkvs);
  kernelB<<<B_GRID, 384, B_SMEM>>>(tm_q, tm_kv, tm_x1l, tm_out);
}
```

```cpp
#include <cuda_runtime.h>
#include <cuda_bf16.h>
#include <cuda.h>
#include <stdint.h>

namespace {

constexpr int TT = 7, NL = 1296, CC = 192;

__device__ __align__(1024) __nv_bfloat16 g_x1[TT * NL * CC];
__device__ __align__(1024) __nv_bfloat16 g_qkv[TT * NL * 3 * CC];
__device__ __align__(1024) __nv_bfloat16 g_wf[2 * CC * 2 * CC];
__device__ __align__(1024) uint4 g_part[110 * 2 * 13 * 128];
__device__ unsigned int g_flag[128];
__device__ unsigned int g_wflag[4];

#define TS(k, i)

__device__ __forceinline__ uint32_t smem_u32(const void* p) { return (uint32_t)__cvta_generic_to_shared(p); }
__device__ __forceinline__ void mbar_init(uint32_t bar, uint32_t cnt) {
  asm volatile("mbarrier.init.shared::cta.b64 [%0], %1;" ::"r"(bar), "r"(cnt));
}
__device__ __forceinline__ void mbar_expect_tx(uint32_t bar, uint32_t bytes) {
  asm volatile("mbarrier.arrive.expect_tx.shared::cta.b64 _, [%0], %1;" ::"r"(bar), "r"(bytes) : "memory");
}
__device__ __forceinline__ void mbar_arrive(uint32_t bar) {
  asm volatile("mbarrier.arrive.shared::cta.b64 _, [%0];" ::"r"(bar) : "memory");
}
__device__ __forceinline__ bool mbar_try(uint32_t bar, uint32_t parity) {
  uint32_t ok;
  asm volatile("{\n.reg .pred p;\nmbarrier.try_wait.parity.shared::cta.b64 p, [%1], %2;\nselp.u32 %0, 1, 0, p;\n}"
               : "=r"(ok) : "r"(bar), "r"(parity) : "memory");
  return ok != 0;
}
__device__ __forceinline__ void mbar_wait(uint32_t bar, uint32_t parity) {
  if (mbar_try(bar, parity)) return;
  uint32_t n = 0;
  while (!mbar_try(bar, parity)) {
    if (++n > (1u << 22)) break;
  }
}
__device__ __forceinline__ void tma_load_2d(uint32_t dst, const CUtensorMap* m, uint32_t bar, int c0, int c1) {
  asm volatile("cp.async.bulk.tensor.2d.shared::cluster.global.mbarrier::complete_tx::bytes [%0], [%1, {%3, %4}], [%2];"
               ::"r"(dst), "l"(m), "r"(bar), "r"(c0), "r"(c1) : "memory");
}
__device__ __forceinline__ void tma_load_3d(uint32_t dst, const CUtensorMap* m, uint32_t bar, int c0, int c1, int c2) {
  asm volatile("cp.async.bulk.tensor.3d.shared::cluster.global.mbarrier::complete_tx::bytes [%0], [%1, {%3, %4, %5}], [%2];"
               ::"r"(dst), "l"(m), "r"(bar), "r"(c0), "r"(c1), "r"(c2) : "memory");
}
__device__ __forceinline__ void tma_store_3d(const CUtensorMap* m, uint32_t src, int c0, int c1, int c2) {
  asm volatile("cp.async.bulk.tensor.3d.global.shared::cta.bulk_group [%0, {%2, %3, %4}], [%1];"
               ::"l"(m), "r"(src), "r"(c0), "r"(c1), "r"(c2) : "memory");
}
__device__ __forceinline__ void bulk_commit() { asm volatile("cp.async.bulk.commit_group;" ::: "memory"); }
__device__ __forceinline__ void bulk_wait_read0() { asm volatile("cp.async.bulk.wait_group.read 0;" ::: "memory"); }
__device__ __forceinline__ void bulk_wait0() { asm volatile("cp.async.bulk.wait_group 0;" ::: "memory"); }
__device__ __forceinline__ void fence_proxy_async() { asm volatile("fence.proxy.async.shared::cta;" ::: "memory"); }
__device__ __forceinline__ void prefetch_tmap(const CUtensorMap* m) {
  asm volatile("prefetch.tensormap [%0];" ::"l"(m) : "memory");
}
__device__ __forceinline__ void wg_fence() { asm volatile("wgmma.fence.sync.aligned;" ::: "memory"); }
__device__ __forceinline__ void wg_commit() { asm volatile("wgmma.commit_group.sync.aligned;" ::: "memory"); }
template <int N> __device__ __forceinline__ void wg_wait() { asm volatile("wgmma.wait_group.sync.aligned %0;" ::"n"(N) : "memory"); }
__device__ __forceinline__ void named_bar(int id, int nthreads) {
  asm volatile("bar.sync %0, %1;" ::"r"(id), "r"(nthreads) : "memory");
}
__device__ __forceinline__ void ldsm_x4(uint32_t (&r)[4], uint32_t addr) {
  asm volatile("ldmatrix.sync.aligned.m8n8.x4.shared.b16 {%0,%1,%2,%3}, [%4];"
               : "=r"(r[0]), "=r"(r[1]), "=r"(r[2]), "=r"(r[3]) : "r"(addr) : "memory");
}
__device__ __forceinline__ void stsm_x4(uint32_t addr, const uint32_t (&r)[4]) {
  asm volatile("stmatrix.sync.aligned.m8n8.x4.shared.b16 [%0], {%1,%2,%3,%4};"
               ::"r"(addr), "r"(r[0]), "r"(r[1]), "r"(r[2]), "r"(r[3]) : "memory");
}
__device__ __forceinline__ uint32_t pack_bf16(float lo, float hi) {
  uint32_t r;
  asm("cvt.rn.bf16x2.f32 %0, %1, %2;" : "=r"(r) : "f"(hi), "f"(lo));
  return r;
}
__device__ __forceinline__ float bf_lo(uint32_t v) { return __uint_as_float(v << 16); }
__device__ __forceinline__ float bf_hi(uint32_t v) { return __uint_as_float(v & 0xffff0000u); }
__device__ __forceinline__ float ex2(float x) {
  float y;
  asm("ex2.approx.ftz.f32 %0, %1;" : "=f"(y) : "f"(x));
  return y;
}
__device__ __forceinline__ uint64_t mk_desc(uint32_t addr, uint32_t lbo, uint32_t sbo) {
  return (uint64_t)((addr & 0x3FFFF) >> 4) | ((uint64_t)((lbo & 0x3FFFF) >> 4) << 16) |
         ((uint64_t)((sbo & 0x3FFFF) >> 4) << 32) | (1ull << 62);
}
__device__ __forceinline__ uint64_t mk_desc_o(uint32_t addr, uint32_t lbo, uint32_t sbo) {
  asm volatile("" : "+r"(addr));
  return mk_desc(addr, lbo, sbo);
}
template <int N> __device__ __forceinline__ void reg_fence(uint32_t (&d)[N]) {
#pragma unroll
  for (int i = 0; i < N; i++) asm volatile("" : "+r"(d[i])::"memory");
}
template <int N> __device__ __forceinline__ void reg_fence(float (&d)[N]) {
#pragma unroll
  for (int i = 0; i < N; i++) asm volatile("" : "+f"(d[i])::"memory");
}

template<int TB> __device__ __forceinline__ void wgmma_n144_ss(float (&d)[72], uint64_t da, uint64_t db, int sc) {
  asm volatile("{\n.reg .pred p;\nsetp.ne.b32 p, %74, 0;\n"
    "wgmma.mma_async.sync.aligned.m64n144k16.f32.bf16.bf16 {%0, %1, %2, %3, %4, %5, %6, %7, %8, %9, %10, %11, %12, %13, %14, %15, %16, %17, %18, %19, %20, %21, %22, %23, %24, %25, %26, %27, %28, %29, %30, %31, %32, %33, %34, %35, %36, %37, %38, %39, %40, %41, %42, %43, %44, %45, %46, %47, %48, %49, %50, %51, %52, %53, %54, %55, %56, %57, %58, %59, %60, %61, %62, %63, %64, %65, %66, %67, %68, %69, %70, %71}, %72, %73, p, 1, 1, 0, %75;\n}\n"
    : "+f"(d[0]), "+f"(d[1]), "+f"(d[2]), "+f"(d[3]), "+f"(d[4]), "+f"(d[5]), "+f"(d[6]), "+f"(d[7]), "+f"(d[8]), "+f"(d[9]), "+f"(d[10]), "+f"(d[11]), "+f"(d[12]), "+f"(d[13]), "+f"(d[14]), "+f"(d[15]), "+f"(d[16]), "+f"(d[17]), "+f"(d[18]), "+f"(d[19]), "+f"(d[20]), "+f"(d[21]), "+f"(d[22]), "+f"(d[23]), "+f"(d[24]), "+f"(d[25]), "+f"(d[26]), "+f"(d[27]), "+f"(d[28]), "+f"(d[29]), "+f"(d[30]), "+f"(d[31]), "+f"(d[32]), "+f"(d[33]), "+f"(d[34]), "+f"(d[35]), "+f"(d[36]), "+f"(d[37]), "+f"(d[38]), "+f"(d[39]), "+f"(d[40]), "+f"(d[41]), "+f"(d[42]), "+f"(d[43]), "+f"(d[44]), "+f"(d[45]), "+f"(d[46]), "+f"(d[47]), "+f"(d[48]), "+f"(d[49]), "+f"(d[50]), "+f"(d[51]), "+f"(d[52]), "+f"(d[53]), "+f"(d[54]), "+f"(d[55]), "+f"(d[56]), "+f"(d[57]), "+f"(d[58]), "+f"(d[59]), "+f"(d[60]), "+f"(d[61]), "+f"(d[62]), "+f"(d[63]), "+f"(d[64]), "+f"(d[65]), "+f"(d[66]), "+f"(d[67]), "+f"(d[68]), "+f"(d[69]), "+f"(d[70]), "+f"(d[71])
    : "l"(da), "l"(db), "r"(sc), "n"(TB));
}
template<int TB> __device__ __forceinline__ void wgmma_n192_rs(float (&d)[96], const uint32_t (&a)[4], uint64_t db, int sc) {
  asm volatile("{\n.reg .pred p;\nsetp.ne.b32 p, %101, 0;\n"
    "wgmma.mma_async.sync.aligned.m64n192k16.f32.bf16.bf16 {%0, %1, %2, %3, %4, %5, %6, %7, %8, %9, %10, %11, %12, %13, %14, %15, %16, %17, %18, %19, %20, %21, %22, %23, %24, %25, %26, %27, %28, %29, %30, %31, %32, %33, %34, %35, %36, %37, %38, %39, %40, %41, %42, %43, %44, %45, %46, %47, %48, %49, %50, %51, %52, %53, %54, %55, %56, %57, %58, %59, %60, %61, %62, %63, %64, %65, %66, %67, %68, %69, %70, %71, %72, %73, %74, %75, %76, %77, %78, %79, %80, %81, %82, %83, %84, %85, %86, %87, %88, %89, %90, %91, %92, %93, %94, %95}, {%96, %97, %98, %99}, %100, p, 1, 1, %102;\n}\n"
    : "+f"(d[0]), "+f"(d[1]), "+f"(d[2]), "+f"(d[3]), "+f"(d[4]), "+f"(d[5]), "+f"(d[6]), "+f"(d[7]), "+f"(d[8]), "+f"(d[9]), "+f"(d[10]), "+f"(d[11]), "+f"(d[12]), "+f"(d[13]), "+f"(d[14]), "+f"(d[15]), "+f"(d[16]), "+f"(d[17]), "+f"(d[18]), "+f"(d[19]), "+f"(d[20]), "+f"(d[21]), "+f"(d[22]), "+f"(d[23]), "+f"(d[24]), "+f"(d[25]), "+f"(d[26]), "+f"(d[27]), "+f"(d[28]), "+f"(d[29]), "+f"(d[30]), "+f"(d[31]), "+f"(d[32]), "+f"(d[33]), "+f"(d[34]), "+f"(d[35]), "+f"(d[36]), "+f"(d[37]), "+f"(d[38]), "+f"(d[39]), "+f"(d[40]), "+f"(d[41]), "+f"(d[42]), "+f"(d[43]), "+f"(d[44]), "+f"(d[45]), "+f"(d[46]), "+f"(d[47]), "+f"(d[48]), "+f"(d[49]), "+f"(d[50]), "+f"(d[51]), "+f"(d[52]), "+f"(d[53]), "+f"(d[54]), "+f"(d[55]), "+f"(d[56]), "+f"(d[57]), "+f"(d[58]), "+f"(d[59]), "+f"(d[60]), "+f"(d[61]), "+f"(d[62]), "+f"(d[63]), "+f"(d[64]), "+f"(d[65]), "+f"(d[66]), "+f"(d[67]), "+f"(d[68]), "+f"(d[69]), "+f"(d[70]), "+f"(d[71]), "+f"(d[72]), "+f"(d[73]), "+f"(d[74]), "+f"(d[75]), "+f"(d[76]), "+f"(d[77]), "+f"(d[78]), "+f"(d[79]), "+f"(d[80]), "+f"(d[81]), "+f"(d[82]), "+f"(d[83]), "+f"(d[84]), "+f"(d[85]), "+f"(d[86]), "+f"(d[87]), "+f"(d[88]), "+f"(d[89]), "+f"(d[90]), "+f"(d[91]), "+f"(d[92]), "+f"(d[93]), "+f"(d[94]), "+f"(d[95])
    : "r"(a[0]), "r"(a[1]), "r"(a[2]), "r"(a[3]), "l"(db), "r"(sc), "n"(TB));
}
template<int TB> __device__ __forceinline__ void wgmma_n64_rs(float (&d)[32], const uint32_t (&a)[4], uint64_t db, int sc) {
  asm volatile("{\n.reg .pred p;\nsetp.ne.b32 p, %37, 0;\n"
    "wgmma.mma_async.sync.aligned.m64n64k16.f32.bf16.bf16 {%0, %1, %2, %3, %4, %5, %6, %7, %8, %9, %10, %11, %12, %13, %14, %15, %16, %17, %18, %19, %20, %21, %22, %23, %24, %25, %26, %27, %28, %29, %30, %31}, {%32, %33, %34, %35}, %36, p, 1, 1, %38;\n}\n"
    : "+f"(d[0]), "+f"(d[1]), "+f"(d[2]), "+f"(d[3]), "+f"(d[4]), "+f"(d[5]), "+f"(d[6]), "+f"(d[7]), "+f"(d[8]), "+f"(d[9]), "+f"(d[10]), "+f"(d[11]), "+f"(d[12]), "+f"(d[13]), "+f"(d[14]), "+f"(d[15]), "+f"(d[16]), "+f"(d[17]), "+f"(d[18]), "+f"(d[19]), "+f"(d[20]), "+f"(d[21]), "+f"(d[22]), "+f"(d[23]), "+f"(d[24]), "+f"(d[25]), "+f"(d[26]), "+f"(d[27]), "+f"(d[28]), "+f"(d[29]), "+f"(d[30]), "+f"(d[31])
    : "r"(a[0]), "r"(a[1]), "r"(a[2]), "r"(a[3]), "l"(db), "r"(sc), "n"(TB));
}
template<int TB> __device__ __forceinline__ void wgmma_n64_ss(float (&d)[32], uint64_t da, uint64_t db, int sc) {
  asm volatile("{\n.reg .pred p;\nsetp.ne.b32 p, %34, 0;\n"
    "wgmma.mma_async.sync.aligned.m64n64k16.f32.bf16.bf16 {%0, %1, %2, %3, %4, %5, %6, %7, %8, %9, %10, %11, %12, %13, %14, %15, %16, %17, %18, %19, %20, %21, %22, %23, %24, %25, %26, %27, %28, %29, %30, %31}, %32, %33, p, 1, 1, 0, %35;\n}\n"
    : "+f"(d[0]), "+f"(d[1]), "+f"(d[2]), "+f"(d[3]), "+f"(d[4]), "+f"(d[5]), "+f"(d[6]), "+f"(d[7]), "+f"(d[8]), "+f"(d[9]), "+f"(d[10]), "+f"(d[11]), "+f"(d[12]), "+f"(d[13]), "+f"(d[14]), "+f"(d[15]), "+f"(d[16]), "+f"(d[17]), "+f"(d[18]), "+f"(d[19]), "+f"(d[20]), "+f"(d[21]), "+f"(d[22]), "+f"(d[23]), "+f"(d[24]), "+f"(d[25]), "+f"(d[26]), "+f"(d[27]), "+f"(d[28]), "+f"(d[29]), "+f"(d[30]), "+f"(d[31])
    : "l"(da), "l"(db), "r"(sc), "n"(TB));
}

struct FragAddr {
  uint32_t rowoff;
  uint32_t rx;
  uint32_t hi;
  __device__ __forceinline__ FragAddr(int warp_in_wg, int lane) {
    int row = 16 * warp_in_wg + (lane & 7) + ((lane >> 3) & 1) * 8;
    rowoff = row * 128;
    rx = row & 7;
    hi = lane >> 4;
  }
  __device__ __forceinline__ uint32_t at(uint32_t chunk_base, int kk4) const {
    return chunk_base + rowoff + ((((uint32_t)kk4 * 2 + hi) ^ rx) << 4);
  }
};

__device__ __forceinline__ void layernorm_frags(uint32_t (&f)[12][4]) {
  float s0 = 0.f, s1 = 0.f;
#pragma unroll
  for (int k = 0; k < 12; k++) {
    s0 += bf_lo(f[k][0]) + bf_hi(f[k][0]) + bf_lo(f[k][2]) + bf_hi(f[k][2]);
    s1 += bf_lo(f[k][1]) + bf_hi(f[k][1]) + bf_lo(f[k][3]) + bf_hi(f[k][3]);
  }
  s0 += __shfl_xor_sync(0xffffffffu, s0, 1); s0 += __shfl_xor_sync(0xffffffffu, s0, 2);
  s1 += __shfl_xor_sync(0xffffffffu, s1, 1); s1 += __shfl_xor_sync(0xffffffffu, s1, 2);
  const float m0 = s0 * (1.f / 192.f), m1 = s1 * (1.f / 192.f);
  float v0 = 0.f, v1 = 0.f;
#pragma unroll
  for (int k = 0; k < 12; k++) {
    float a;
    a = bf_lo(f[k][0]) - m0; v0 += a * a; a = bf_hi(f[k][0]) - m0; v0 += a * a;
    a = bf_lo(f[k][2]) - m0; v0 += a * a; a = bf_hi(f[k][2]) - m0; v0 += a * a;
    a = bf_lo(f[k][1]) - m1; v1 += a * a; a = bf_hi(f[k][1]) - m1; v1 += a * a;
    a = bf_lo(f[k][3]) - m1; v1 += a * a; a = bf_hi(f[k][3]) - m1; v1 += a * a;
  }
  v0 += __shfl_xor_sync(0xffffffffu, v0, 1); v0 += __shfl_xor_sync(0xffffffffu, v0, 2);
  v1 += __shfl_xor_sync(0xffffffffu, v1, 1); v1 += __shfl_xor_sync(0xffffffffu, v1, 2);
  const float r0 = rsqrtf(v0 * (1.f / 192.f) + 1e-5f), r1 = rsqrtf(v1 * (1.f / 192.f) + 1e-5f);
#pragma unroll
  for (int k = 0; k < 12; k++) {
    f[k][0] = pack_bf16((bf_lo(f[k][0]) - m0) * r0, (bf_hi(f[k][0]) - m0) * r0);
    f[k][2] = pack_bf16((bf_lo(f[k][2]) - m0) * r0, (bf_hi(f[k][2]) - m0) * r0);
    f[k][1] = pack_bf16((bf_lo(f[k][1]) - m1) * r1, (bf_hi(f[k][1]) - m1) * r1);
    f[k][3] = pack_bf16((bf_lo(f[k][3]) - m1) * r1, (bf_hi(f[k][3]) - m1) * r1);
  }
}

constexpr int A_NST = 5;
constexpr int A_XS = 0;
constexpr int A_VB = 49152;
constexpr int A_W = 98304;
constexpr int A_BAR = A_W + A_NST * 24576;
constexpr int A_SMEM = A_BAR + 256 + 1024;
constexpr int A_FOLD = 36;

__device__ __forceinline__ void a_issue(float (&acc)[32], const uint32_t (&af)[12][4], uint32_t sb, int s) {
  const int st = s % A_NST;
  mbar_wait(sb + A_BAR + st * 8, (s / A_NST) & 1);
  const uint64_t wd = mk_desc_o(sb + A_W + st * 24576, 8192, 1024);
  wg_fence();
#pragma unroll
  for (int kk = 0; kk < 12; kk++) wgmma_n64_rs<1>(acc, af[kk], wd + kk * 128, kk > 0);
  wg_commit();
}
__device__ __forceinline__ void a_release(uint32_t sb, int s, int lane) {
  if (lane == 0) mbar_arrive(sb + A_BAR + 64 + (s % A_NST) * 8);
}
__device__ __forceinline__ void cvt_frags(uint32_t (*dst)[4], const float (&acc)[32]) {
#pragma unroll
  for (int k = 0; k < 4; k++) {
    dst[k][0] = pack_bf16(acc[8 * k + 0], acc[8 * k + 1]);
    dst[k][1] = pack_bf16(acc[8 * k + 2], acc[8 * k + 3]);
    dst[k][2] = pack_bf16(acc[8 * k + 4], acc[8 * k + 5]);
    dst[k][3] = pack_bf16(acc[8 * k + 6], acc[8 * k + 7]);
  }
}
__device__ __forceinline__ void store_chunk(const float (&acc)[32], uint32_t chunk_base, const FragAddr& fa) {
  uint32_t t[4][4];
  cvt_frags(t, acc);
#pragma unroll
  for (int k = 0; k < 4; k++) stsm_x4(fa.at(chunk_base, k), t[k]);
}
__device__ __forceinline__ void resid_chunk(uint32_t (*dst)[4], const float* acc, float s0, float s1, uint32_t chunk_base,
                                            const FragAddr& fa) {
#pragma unroll
  for (int k = 0; k < 4; k++) {
    uint32_t x[4];
    ldsm_x4(x, fa.at(chunk_base, k));
    uint32_t o[4];
    o[0] = pack_bf16(fmaf(acc[8 * k + 0], s0, bf_lo(x[0])), fmaf(acc[8 * k + 1], s0, bf_hi(x[0])));
    o[1] = pack_bf16(fmaf(acc[8 * k + 2], s1, bf_lo(x[1])), fmaf(acc[8 * k + 3], s1, bf_hi(x[1])));
    o[2] = pack_bf16(fmaf(acc[8 * k + 4], s0, bf_lo(x[2])), fmaf(acc[8 * k + 5], s0, bf_hi(x[2])));
    o[3] = pack_bf16(fmaf(acc[8 * k + 6], s1, bf_lo(x[3])), fmaf(acc[8 * k + 7], s1, bf_hi(x[3])));
    stsm_x4(fa.at(chunk_base, k), o);
    if (dst) { dst[k][0] = o[0]; dst[k][1] = o[1]; dst[k][2] = o[2]; dst[k][3] = o[3]; }
  }
}

__global__ void __launch_bounds__(384, 1)
kernelA(const __grid_constant__ CUtensorMap tm_x, const __grid_constant__ CUtensorMap tm_wq64t,
        const __grid_constant__ CUtensorMap tm_wot, const __grid_constant__ CUtensorMap tm_wq64s,
        const __grid_constant__ CUtensorMap tm_wos, const __grid_constant__ CUtensorMap tm_wf,
        const __grid_constant__ CUtensorMap tm_x1, const __grid_constant__ CUtensorMap tm_qkv) {
  extern __shared__ uint8_t smem_raw[];
  const uint32_t sb = (smem_u32(smem_raw) + 1023) & ~1023u;
  const int tid = threadIdx.x, warp = tid >> 5, lane = tid & 31;
  const bool is_fold = blockIdx.x < A_FOLD;
  const int blk = blockIdx.x - A_FOLD;
  if (tid == 256) {
    for (int i = 0; i < A_NST; i++) { mbar_init(sb + A_BAR + i * 8, 1); mbar_init(sb + A_BAR + 64 + i * 8, 8); }
    mbar_init(sb + A_BAR + 128, 1); mbar_init(sb + A_BAR + 136, 1);
    asm volatile("fence.mbarrier_init.release.cluster;" ::: "memory");
    if (!is_fold) {
      for (int w = 0; w < 2; w++) {
        const uint32_t bar = sb + A_BAR + 128 + w * 8;
        mbar_expect_tx(bar, 3 * 63 * 128);
        for (int c = 0; c < 3; c++)
          tma_load_3d(sb + A_XS + w * 24576 + c * 8192, &tm_x, bar, c * 64, (blk * 2 + w) * 9, 0);
      }
    } else {
      const int mat = blockIdx.x / 9, rs = (blockIdx.x % 9) / 3, cs = blockIdx.x % 3;
      const CUtensorMap* mq = (mat < 2) ? &tm_wq64t : &tm_wq64s;
      const CUtensorMap* mo = (mat < 2) ? &tm_wot : &tm_wos;
      const uint32_t bar = sb + A_BAR + 128;
      mbar_expect_tx(bar, 2 * 24576);
      for (int c = 0; c < 3; c++) tma_load_2d(sb + c * 8192, mq, bar, ((mat & 1) ? 384 : 0) + c * 64, rs * 64);
      if (mat & 1) tma_load_2d(sb + 24576, mo, bar, cs * 64, 0);
      else for (int c = 0; c < 3; c++) tma_load_2d(sb + 24576 + c * 8192, mq, bar, 192 + c * 64, cs * 64);
    }
  }
  asm volatile("griddepcontrol.launch_dependents;" ::: "memory");
  if (blockIdx.x == 0 && tid < 128) g_flag[tid] = 0;
  if (!is_fold && tid < 48) {
    uint32_t a = sb + A_XS + (tid >> 3) * 8192 + 63 * 128 + (tid & 7) * 16;
    asm volatile("st.shared.v4.b32 [%0], {%1,%1,%1,%1};" ::"r"(a), "r"(0) : "memory");
  }
  __syncthreads();

  if (warp >= 8) {
    asm volatile("setmaxnreg.dec.sync.aligned.u32 24;");
    if (warp == 8 && lane == 0 && !is_fold) {
      for (int s = 0; s < 12; s++) {
        const int st = s % A_NST;
        const int g = s / 3;
        const int mat = (g == 0) ? 1 : (g == 1) ? 0 : g;
        if (s % 3 == 0) {
          uint32_t n = 0, v;
          do {
            asm volatile("ld.acquire.gpu.global.u32 %0, [%1];" : "=r"(v) : "l"(&g_wflag[mat]) : "memory");
          } while (v < 9u && ++n < (1u << 22));
          asm volatile("fence.proxy.async;" ::: "memory");
        }
        if (s >= A_NST) mbar_wait(sb + A_BAR + 64 + st * 8, ((s / A_NST) - 1) & 1);
        mbar_expect_tx(sb + A_BAR + st * 8, 24576);
        tma_load_2d(sb + A_W + st * 24576, &tm_wf, sb + A_BAR + st * 8, (mat & 1) * 192 + (s % 3) * 64, (mat >> 1) * 192);
      }
    }
    return;
  }

  asm volatile("setmaxnreg.inc.sync.aligned.u32 240;");
  const int wg = warp >> 2, wq = warp & 3;

  if (is_fold) {
    if (wg == 0) {
      const int mat = blockIdx.x / 9, rs = (blockIdx.x % 9) / 3, cs = blockIdx.x % 3;
      float d[32];
      mbar_wait(sb + A_BAR + 128, 0);
      const uint64_t ad = mk_desc_o(sb, 16, 1024);
      if (mat & 1) {
        const uint64_t bd = mk_desc_o(sb + 24576, 8192, 1024);
        wg_fence();
#pragma unroll
        for (int kk = 0; kk < 12; kk++) wgmma_n64_ss<1>(d, ad + (kk >> 2) * 512 + (kk & 3) * 2, bd + kk * 128, kk > 0);
        wg_commit();
      } else {
        const uint64_t bd = mk_desc_o(sb + 24576, 16, 1024);
        wg_fence();
#pragma unroll
        for (int kk = 0; kk < 12; kk++)
          wgmma_n64_ss<0>(d, ad + (kk >> 2) * 512 + (kk & 3) * 2, bd + (kk >> 2) * 512 + (kk & 3) * 2, kk > 0);
        wg_commit();
      }
      wg_wait<0>(); reg_fence(d);
      const int r0 = rs * 64 + wq * 16 + (lane >> 2);
      uint32_t* dst = reinterpret_cast<uint32_t*>(g_wf + ((size_t)(mat >> 1) * 192 + r0) * 384 + (mat & 1) * 192 + cs * 64 + (lane & 3) * 2);
#pragma unroll
      for (int j = 0; j < 8; j++) {
        dst[j * 4] = pack_bf16(d[4 * j], d[4 * j + 1]);
        dst[8 * 192 + j * 4] = pack_bf16(d[4 * j + 2], d[4 * j + 3]);
      }
      asm volatile("fence.proxy.async;" ::: "memory");
      __threadfence();
      named_bar(1, 128);
      if (tid == 0) atomicAdd(&g_wflag[mat], 1u);
    }
    return;
  }

  const int n0 = (blk * 2 + wg) * 9;
  const FragAddr fa(wq, lane);
  const uint32_t xs = sb + A_XS + wg * 24576, vb = sb + A_VB + wg * 24576;
  const int barid = 1 + wg;
  const bool elected = (tid & 127) == 0;

  uint32_t h[12][4];
  TS(0, 0);
  mbar_wait(sb + A_BAR + 128 + wg * 8, 0);
  TS(0, 1);
#pragma unroll
  for (int k = 0; k < 12; k++) ldsm_x4(h[k], fa.at(xs + (k >> 2) * 8192, k & 3));
  layernorm_frags(h);
#pragma unroll
  for (int k = 0; k < 12; k++) stsm_x4(fa.at(xs + (k >> 2) * 8192, k & 3), h[k]);

  float acc0[32], acc1[32];
  uint32_t qf[12][4];
  TS(0, 2);
  a_issue(acc0, h, sb, 0);
  TS(0, 3);
  a_issue(acc1, h, sb, 1); wg_wait<1>(); reg_fence(acc0); a_release(sb, 0, lane); store_chunk(acc0, vb, fa);
  a_issue(acc0, h, sb, 2); wg_wait<1>(); reg_fence(acc1); a_release(sb, 1, lane); store_chunk(acc1, vb + 8192, fa);
  a_issue(acc1, h, sb, 3); wg_wait<1>(); reg_fence(acc0); a_release(sb, 2, lane); store_chunk(acc0, vb + 16384, fa);
  fence_proxy_async();
  named_bar(barid, 128);
  a_issue(acc0, h, sb, 4); wg_wait<1>(); reg_fence(acc1); a_release(sb, 3, lane); cvt_frags(&qf[0], acc1);
  a_issue(acc1, h, sb, 5); wg_wait<1>(); reg_fence(acc0); a_release(sb, 4, lane); cvt_frags(&qf[4], acc0);
  wg_wait<0>(); reg_fence(acc1); a_release(sb, 5, lane); cvt_frags(&qf[8], acc1);
  TS(0, 4);
  {
    const uint64_t kd = mk_desc_o(xs, 16, 1024);
    wg_fence();
#pragma unroll
    for (int kk = 0; kk < 12; kk++) wgmma_n64_rs<0>(acc0, qf[kk], kd + (kk >> 2) * 512 + (kk & 3) * 2, kk > 0);
    wg_commit();
    wg_wait<0>(); reg_fence(acc0);
  }
  named_bar(barid, 128);
  if (elected) {
    const uint32_t bar = sb + A_BAR + 128 + wg * 8;
    mbar_expect_tx(bar, 3 * 63 * 128);
    for (int c = 0; c < 3; c++) tma_load_3d(xs + c * 8192, &tm_x, bar, c * 64, n0, 0);
  }
  uint32_t pf[4][4];
  {
    const int r0 = 16 * wq + (lane >> 2), r1 = r0 + 8;
    const unsigned long long MB = 0x0040201008040201ull;
    const unsigned long long mk0 = (MB << (r0 % 9)) >> (2 * (lane & 3));
    const unsigned long long mk1 = (MB << (r1 % 9)) >> (2 * (lane & 3));
    const float cs = 0.07216878364870322f * 1.4426950408889634f;
    float mx0 = -INFINITY, mx1 = -INFINITY;
#pragma unroll
    for (int j = 0; j < 8; j++) {
#pragma unroll
      for (int e = 0; e < 2; e++) {
        bool v0 = (mk0 >> (8 * j + e)) & 1, v1 = (mk1 >> (8 * j + e)) & 1;
        acc0[4 * j + e] = v0 ? acc0[4 * j + e] * cs : -INFINITY;
        acc0[4 * j + 2 + e] = v1 ? acc0[4 * j + 2 + e] * cs : -INFINITY;
        mx0 = fmaxf(mx0, acc0[4 * j + e]);
        mx1 = fmaxf(mx1, acc0[4 * j + 2 + e]);
      }
    }
    mx0 = fmaxf(mx0, __shfl_xor_sync(0xffffffffu, mx0, 1)); mx0 = fmaxf(mx0, __shfl_xor_sync(0xffffffffu, mx0, 2));
    mx1 = fmaxf(mx1, __shfl_xor_sync(0xffffffffu, mx1, 1)); mx1 = fmaxf(mx1, __shfl_xor_sync(0xffffffffu, mx1, 2));
    float l0 = 0.f, l1 = 0.f;
#pragma unroll
    for (int j = 0; j < 8; j++) {
#pragma unroll
      for (int e = 0; e < 2; e++) {
        acc0[4 * j + e] = ex2(acc0[4 * j + e] - mx0); l0 += acc0[4 * j + e];
        acc0[4 * j + 2 + e] = ex2(acc0[4 * j + 2 + e] - mx1); l1 += acc0[4 * j + 2 + e];
      }
    }
    l0 += __shfl_xor_sync(0xffffffffu, l0, 1); l0 += __shfl_xor_sync(0xffffffffu, l0, 2);
    l1 += __shfl_xor_sync(0xffffffffu, l1, 1); l1 += __shfl_xor_sync(0xffffffffu, l1, 2);
    const float i0 = 1.f / l0, i1 = 1.f / l1;
#pragma unroll
    for (int j = 0; j < 8; j++) {
      acc0[4 * j] *= i0; acc0[4 * j + 1] *= i0; acc0[4 * j + 2] *= i1; acc0[4 * j + 3] *= i1;
    }
    cvt_frags(pf, acc0);
  }
  TS(0, 5);
  {
    float oacc[96];
    const uint64_t vd = mk_desc_o(vb, 8192, 1024);
    wg_fence();
#pragma unroll
    for (int kk = 0; kk < 4; kk++) wgmma_n192_rs<1>(oacc, pf[kk], vd + kk * 128, kk > 0);
    wg_commit();
    wg_wait<0>(); reg_fence(oacc);
    TS(0, 6);
    mbar_wait(sb + A_BAR + 128 + wg * 8, 1);
#pragma unroll
    for (int c = 0; c < 3; c++) resid_chunk(&h[4 * c], &oacc[32 * c], 1.f, 1.f, xs + c * 8192, fa);
  }
  TS(0, 7);
  layernorm_frags(h);
  named_bar(barid, 128);
#pragma unroll
  for (int k = 0; k < 12; k++) stsm_x4(fa.at(vb + (k >> 2) * 8192, k & 3), h[k]);
  TS(0, 8);
  a_issue(acc0, h, sb, 6);
  fence_proxy_async();
  named_bar(barid, 128);
  if (elected) {
    for (int c = 0; c < 3; c++) tma_store_3d(&tm_x1, xs + c * 8192, c * 64, n0, 0);
    for (int c = 0; c < 3; c++) tma_store_3d(&tm_qkv, vb + c * 8192, 192 + c * 64, n0, 0);
    bulk_commit();
  }
  a_issue(acc1, h, sb, 7); wg_wait<1>(); reg_fence(acc0); a_release(sb, 6, lane);
  if (elected) bulk_wait_read0();
  named_bar(barid, 128);
  store_chunk(acc0, xs, fa);
  a_issue(acc0, h, sb, 8); wg_wait<1>(); reg_fence(acc1); store_chunk(acc1, xs + 8192, fa);
  a_issue(acc1, h, sb, 9); wg_wait<1>(); reg_fence(acc0); store_chunk(acc0, xs + 16384, fa);
  fence_proxy_async();
  named_bar(barid, 128);
  if (elected) {
    for (int c = 0; c < 3; c++) tma_store_3d(&tm_qkv, xs + c * 8192, c * 64, n0, 0);
    bulk_commit();
  }
  a_issue(acc0, h, sb, 10); wg_wait<1>(); reg_fence(acc1); store_chunk(acc1, vb, fa);
  a_issue(acc1, h, sb, 11); wg_wait<1>(); reg_fence(acc0); store_chunk(acc0, vb + 8192, fa);
  wg_wait<0>(); reg_fence(acc1); store_chunk(acc1, vb + 16384, fa);
  fence_proxy_async();
  named_bar(barid, 128);
  TS(0, 9);
  if (elected) {
    for (int c = 0; c < 3; c++) tma_store_3d(&tm_qkv, vb + c * 8192, 384 + c * 64, n0, 0);
    bulk_commit();
    bulk_wait_read0();
  }
  TS(0, 10);
}

constexpr int B_GRID = 132;
constexpr int B_SLOT = 55296;
constexpr int B_Q = 0;
constexpr int B_KV = 49152;
constexpr int B_BAR = B_KV + 3 * B_SLOT;
constexpr int B_SMEM = B_BAR + 256 + 1024;

__device__ __forceinline__ void bar_arrive(int id, int nthreads) {
  asm volatile("bar.arrive %0, %1;" ::"r"(id), "r"(nthreads) : "memory");
}
__device__ __forceinline__ void b_segment(int sg, int& tile, int& k0, int& k1) {
  const int grp = blockIdx.x / 12, ci = blockIdx.x - grp * 12;
  if (ci < 7) { tile = grp * 7 + ci; k0 = 3; k1 = 9; }
  else {
    const int hh = ci - 7;
    tile = grp * 7 + ((0x54210 >> (4 * hh)) & 15) + sg;
    k0 = sg ? 0 : ((0x10210 >> (4 * hh)) & 15);
    k1 = sg ? ((0x31321 >> (4 * hh)) & 15) : 3;
  }
}

__global__ void __launch_bounds__(384, 1)
kernelB(const __grid_constant__ CUtensorMap tm_q, const __grid_constant__ CUtensorMap tm_kv,
        const __grid_constant__ CUtensorMap tm_x1, const __grid_constant__ CUtensorMap tm_out) {
  extern __shared__ uint8_t smem_raw[];
  const uint32_t sb = (smem_u32(smem_raw) + 1023) & ~1023u;
  const int tid = threadIdx.x, warp = tid >> 5, lane = tid & 31;
  const uint32_t bF = sb + B_BAR, bE = sb + B_BAR + 32, bQF = sb + B_BAR + 64, bQE = sb + B_BAR + 72;
  if (tid == 0) {
    for (int i = 0; i < 3; i++) { mbar_init(bF + i * 8, 1); mbar_init(bE + i * 8, 8); }
    mbar_init(bQF, 1); mbar_init(bQE, 8);
    asm volatile("fence.mbarrier_init.release.cluster;" ::: "memory");
    prefetch_tmap(&tm_q); prefetch_tmap(&tm_kv); prefetch_tmap(&tm_x1); prefetch_tmap(&tm_out);
  }
  __syncthreads();
  asm volatile("griddepcontrol.wait;" ::: "memory");
  const int grp = blockIdx.x / 12, ci = blockIdx.x - grp * 12;
  const bool owner = ci < 7;
  const int nseg = owner ? 1 : 2;

  if (warp >= 8) {
    asm volatile("setmaxnreg.dec.sync.aligned.u32 24;");
    if (warp == 8 && lane == 0) {
      if (blockIdx.x == 0) { g_wflag[0] = 0; g_wflag[1] = 0; g_wflag[2] = 0; g_wflag[3] = 0; }
      int it = 0;
      for (int sg = 0; sg < nseg; sg++) {
        int tile, k0, k1;
        b_segment(sg, tile, k0, k1);
        const int t = tile / 11, qt = tile - t * 11;
        if (sg > 0) mbar_wait(bQE, 0);
        mbar_expect_tx(bQF, 49152);
        for (int c = 0; c < 3; c++) tma_load_3d(sb + B_Q + c * 16384, &tm_q, bQF, c * 64, qt * 128, t);
        const int n = k1 - k0;
        for (int e = 0; e < 2 * n; e++) {
          const int sl = it % 3;
          if (it >= 3) mbar_wait(bE + sl * 8, ((it / 3) - 1) & 1);
          mbar_expect_tx(bF + sl * 8, B_SLOT);
          for (int c = 0; c < 3; c++)
            tma_load_3d(sb + B_KV + sl * B_SLOT + c * 18432, &tm_kv, bF + sl * 8, 192 + (e & 1) * 192 + c * 64, (k0 + (e >> 1)) * 144, t);
          it++;
        }
      }
      if (owner) {
        const int tile = grp * 7 + ci;
        const int t = tile / 11, qt = tile - t * 11;
        mbar_wait(bQE, 0);
        mbar_expect_tx(bQF, 49152);
        for (int c = 0; c < 3; c++) tma_load_3d(sb + B_Q + c * 16384, &tm_x1, bQF, c * 64, qt * 128, t);
      }
    } else if ((warp == 9 || warp == 10) && !owner) {
      for (int sg = 0; sg < 2; sg++) {
        named_bar(5 + (warp - 9), 160);
        if (lane == 0) {
          __threadfence();
          atomicAdd(&g_flag[(grp * 5 + (ci - 7)) * 2 + sg], 1u);
        }
        __syncwarp();
      }
    }
    return;
  }

  asm volatile("setmaxnreg.inc.sync.aligned.u32 240;");
  const int wg = warp >> 2, wq = warp & 3;
  const int wtid = tid & 127;
  const float cs = 0.07216878364870322f * 1.4426950408889634f;
  float oacc[96], sacc[72];
  uint32_t pf[9][4];
  float m0, m1, l0, l1;
  int it = 0;
  const uint32_t qb = sb + B_Q + wg * 8192;
  if (wg == 1) bar_arrive(3, 256);
  TS(1, 0);
  int tsi = 1;

  auto issue_qk = [&](int slot) {
    const uint64_t kd = mk_desc_o(sb + B_KV + slot * B_SLOT, 16, 1024);
    const uint64_t qd = mk_desc_o(qb, 16, 1024);
#pragma unroll
    for (int kk = 0; kk < 12; kk++)
      wgmma_n144_ss<0>(sacc, qd + (kk >> 2) * 1024 + (kk & 3) * 2, kd + (kk >> 2) * 1152 + (kk & 3) * 2, kk > 0);
    wg_commit();
  };
  auto issue_pv = [&](int slot, int accum) {
    const uint64_t vd = mk_desc_o(sb + B_KV + slot * B_SLOT, 18432, 1024);
#pragma unroll
    for (int kk = 0; kk < 9; kk++) wgmma_n192_rs<1>(oacc, pf[kk], vd + kk * 128, kk > 0 ? 1 : accum);
    wg_commit();
  };
  auto softmax = [&](bool rescale) {
    float t0[4], t1[4];
#pragma unroll
    for (int q = 0; q < 4; q++) {
      t0[q] = fmaxf(sacc[4 * q], sacc[4 * q + 1]);
      t1[q] = fmaxf(sacc[4 * q + 2], sacc[4 * q + 3]);
    }
#pragma unroll
    for (int j = 4; j < 18; j++) {
      t0[j & 3] = fmaxf(t0[j & 3], fmaxf(sacc[4 * j], sacc[4 * j + 1]));
      t1[j & 3] = fmaxf(t1[j & 3], fmaxf(sacc[4 * j + 2], sacc[4 * j + 3]));
    }
    float mx0 = fmaxf(fmaxf(t0[0], t0[1]), fmaxf(fmaxf(t0[2], t0[3]), m0));
    float mx1 = fmaxf(fmaxf(t1[0], t1[1]), fmaxf(fmaxf(t1[2], t1[3]), m1));
    mx0 = fmaxf(mx0, __shfl_xor_sync(0xffffffffu, mx0, 1)); mx1 = fmaxf(mx1, __shfl_xor_sync(0xffffffffu, mx1, 1));
    mx0 = fmaxf(mx0, __shfl_xor_sync(0xffffffffu, mx0, 2)); mx1 = fmaxf(mx1, __shfl_xor_sync(0xffffffffu, mx1, 2));
    const float a0 = ex2((m0 - mx0) * cs), a1 = ex2((m1 - mx1) * cs);
    m0 = mx0; m1 = mx1;
    const float mc0 = mx0 * cs, mc1 = mx1 * cs;
#pragma unroll
    for (int q = 0; q < 4; q++) { t0[q] = 0.f; t1[q] = 0.f; }
#pragma unroll
    for (int k = 0; k < 9; k++) {
      float p[8];
#pragma unroll
      for (int e = 0; e < 8; e++) p[e] = ex2(fmaf(sacc[8 * k + e], cs, (e & 2) ? -mc1 : -mc0));
      t0[0] += p[0]; t0[1] += p[1]; t0[2] += p[4]; t0[3] += p[5];
      t1[0] += p[2]; t1[1] += p[3]; t1[2] += p[6]; t1[3] += p[7];
      pf[k][0] = pack_bf16(p[0], p[1]); pf[k][1] = pack_bf16(p[2], p[3]);
      pf[k][2] = pack_bf16(p[4], p[5]); pf[k][3] = pack_bf16(p[6], p[7]);
    }
    l0 = l0 * a0 + ((t0[0] + t0[1]) + (t0[2] + t0[3]));
    l1 = l1 * a1 + ((t1[0] + t1[1]) + (t1[2] + t1[3]));
    if (rescale) {
#pragma unroll
      for (int i = 0; i < 24; i++) {
        oacc[4 * i] *= a0; oacc[4 * i + 1] *= a0; oacc[4 * i + 2] *= a1; oacc[4 * i + 3] *= a1;
      }
    }
  };

  for (int sg = 0; sg < nseg; sg++) {
    int n;
    { int tile, k0, k1; b_segment(sg, tile, k0, k1); n = k1 - k0; }
    m0 = m1 = -INFINITY; l0 = l1 = 0.f;
    mbar_wait(bQF, sg & 1);
    {
      const int sl = it % 3;
      mbar_wait(bF + sl * 8, (it / 3) & 1);
      named_bar(3 + wg, 256);
      wg_fence();
      issue_qk(sl);
      bar_arrive(3 + (wg ^ 1), 256);
      wg_wait<0>(); reg_fence(sacc);
      if (lane == 0) { mbar_arrive(bE + sl * 8); if (n == 1) mbar_arrive(bQE); }
      it++;
      softmax(false);
    }
    TS(1, tsi); tsi++;
    for (int j = 1; j < n; j++) {
      const int slv = it % 3, slk = (it + 1) % 3;
      mbar_wait(bF + slv * 8, (it / 3) & 1);
      named_bar(3 + wg, 256);
      wg_fence();
      issue_pv(slv, j > 1);
      mbar_wait(bF + slk * 8, ((it + 1) / 3) & 1);
      issue_qk(slk);
      bar_arrive(3 + (wg ^ 1), 256);
      wg_wait<1>(); reg_fence(oacc);
      if (lane == 0) mbar_arrive(bE + slv * 8);
      wg_wait<0>(); reg_fence(sacc);
      if (lane == 0) { mbar_arrive(bE + slk * 8); if (j == n - 1) mbar_arrive(bQE); }
      it += 2;
      softmax(true);
      TS(1, tsi); tsi++;
    }
    {
      const int sl = it % 3;
      mbar_wait(bF + sl * 8, (it / 3) & 1);
      named_bar(3 + wg, 256);
      wg_fence();
      issue_pv(sl, n > 1);
      if (!(wg == 1 && sg == nseg - 1)) bar_arrive(3 + (wg ^ 1), 256);
      wg_wait<0>(); reg_fence(oacc);
      if (lane == 0) mbar_arrive(bE + sl * 8);
      it++;
    }
    TS(1, tsi); tsi++;
    if (!owner) {
      const int slot = (grp * 5 + (ci - 7)) * 2 + sg;
      uint4* dst = g_part + (size_t)(slot * 2 + wg) * 13 * 128 + wtid;
#pragma unroll
      for (int i = 0; i < 12; i++)
        dst[i * 128] = make_uint4(pack_bf16(oacc[8 * i], oacc[8 * i + 1]), pack_bf16(oacc[8 * i + 2], oacc[8 * i + 3]),
                                  pack_bf16(oacc[8 * i + 4], oacc[8 * i + 5]), pack_bf16(oacc[8 * i + 6], oacc[8 * i + 7]));
      dst[12 * 128] = make_uint4(__float_as_uint(m0), __float_as_uint(m1), __float_as_uint(l0), __float_as_uint(l1));
      bar_arrive(5 + wg, 160);
      TS(1, tsi); tsi++;
    }
  }
  if (!owner) return;

  {
    const int first = (0x9765310 >> (4 * ci)) & 15, cnt = (0x1211221 >> (4 * ci)) & 15;
    const int slot0 = grp * 10 + first;
    if (wtid < cnt) {
      uint32_t n = 0, v;
      do {
        asm volatile("ld.acquire.gpu.global.u32 %0, [%1];" : "=r"(v) : "l"(&g_flag[slot0 + wtid]) : "memory");
      } while (v < 2u && ++n < (1u << 22));
    }
    named_bar(1 + wg, 128);
    uint4 pv[2][13];
#pragma unroll
    for (int q = 0; q < 2; q++) {
      if (q < cnt) {
        const uint4* src = g_part + (size_t)((slot0 + q) * 2 + wg) * 13 * 128 + wtid;
#pragma unroll
        for (int i = 0; i < 13; i++) pv[q][i] = __ldcg(src + i * 128);
      }
    }
#pragma unroll
    for (int q = 0; q < 2; q++) {
      if (q < cnt) {
        const float pm0 = __uint_as_float(pv[q][12].x), pm1 = __uint_as_float(pv[q][12].y);
        const float mx0 = fmaxf(m0, pm0), mx1 = fmaxf(m1, pm1);
        const float a0 = ex2((m0 - mx0) * cs), a1 = ex2((m1 - mx1) * cs);
        const float b0 = ex2((pm0 - mx0) * cs), b1 = ex2((pm1 - mx1) * cs);
        m0 = mx0; m1 = mx1;
        l0 = l0 * a0 + __uint_as_float(pv[q][12].z) * b0; l1 = l1 * a1 + __uint_as_float(pv[q][12].w) * b1;
#pragma unroll
        for (int i = 0; i < 12; i++) {
          const uint4 v = pv[q][i];
          oacc[8 * i + 0] = oacc[8 * i + 0] * a0 + bf_lo(v.x) * b0; oacc[8 * i + 1] = oacc[8 * i + 1] * a0 + bf_hi(v.x) * b0;
          oacc[8 * i + 2] = oacc[8 * i + 2] * a1 + bf_lo(v.y) * b1; oacc[8 * i + 3] = oacc[8 * i + 3] * a1 + bf_hi(v.y) * b1;
          oacc[8 * i + 4] = oacc[8 * i + 4] * a0 + bf_lo(v.z) * b0; oacc[8 * i + 5] = oacc[8 * i + 5] * a0 + bf_hi(v.z) * b0;
          oacc[8 * i + 6] = oacc[8 * i + 6] * a1 + bf_lo(v.w) * b1; oacc[8 * i + 7] = oacc[8 * i + 7] * a1 + bf_hi(v.w) * b1;
        }
      }
    }
  }
  TS(1, 21);
  l0 += __shfl_xor_sync(0xffffffffu, l0, 1); l0 += __shfl_xor_sync(0xffffffffu, l0, 2);
  l1 += __shfl_xor_sync(0xffffffffu, l1, 1); l1 += __shfl_xor_sync(0xffffffffu, l1, 2);
  const float i0 = 1.f / l0, i1 = 1.f / l1;
  mbar_wait(bQF, 1);
  const FragAddr fa(wq, lane);
#pragma unroll
  for (int c = 0; c < 3; c++) resid_chunk(nullptr, &oacc[32 * c], i0, i1, qb + c * 16384, fa);
  fence_proxy_async();
  named_bar(1 + wg, 128);
  TS(1, 22);
  if (wtid == 0) {
    const int tile = grp * 7 + ci;
    const int t = tile / 11, qt = tile - t * 11;
    if (qt * 128 + wg * 64 < NL) {
      for (int c = 0; c < 3; c++) tma_store_3d(&tm_out, qb + c * 16384, c * 64, qt * 128 + wg * 64, t);
      bulk_commit();
      bulk_wait_read0();
    }
  }
  TS(1, 23);
}

typedef CUresult (*EncodeFn)(CUtensorMap*, CUtensorMapDataType, cuuint32_t, void*, const cuuint64_t*, const cuuint64_t*,
                             const cuuint32_t*, const cuuint32_t*, CUtensorMapInterleave, CUtensorMapSwizzle,
                             CUtensorMapL2promotion, CUtensorMapFloatOOBfill);

void make_map(EncodeFn enc, CUtensorMap* m, const void* ptr, int rank, const uint64_t* dims, const uint32_t* box) {
  cuuint64_t gd[3], gs[2];
  cuuint32_t bx[3], es[3] = {1, 1, 1};
  uint64_t stride = 2;
  for (int i = 0; i < rank; i++) {
    gd[i] = dims[i]; bx[i] = box[i];
    stride *= dims[i];
    if (i < rank - 1) gs[i] = stride;
  }
  enc(m, CU_TENSOR_MAP_DATA_TYPE_BFLOAT16, rank, const_cast<void*>(ptr), gd, gs, bx, es, CU_TENSOR_MAP_INTERLEAVE_NONE,
      CU_TENSOR_MAP_SWIZZLE_128B, CU_TENSOR_MAP_L2_PROMOTION_L2_256B, CU_TENSOR_MAP_FLOAT_OOB_FILL_NONE);
}

}

extern "C" void kernel_launch(void* const* d_in, const int* in_sizes, int n_in, void* d_out, int out_size) {
  (void)in_sizes; (void)n_in; (void)out_size;
  EncodeFn enc = nullptr;
  cudaDriverEntryPointQueryResult qres;
  cudaGetDriverEntryPoint("cuTensorMapEncodeTiled", (void**)&enc, cudaEnableDefault, &qres);
  void *p_x1, *p_qkv, *p_wf;
  cudaGetSymbolAddress(&p_wf, g_wf);
  cudaGetSymbolAddress(&p_x1, g_x1);
  cudaGetSymbolAddress(&p_qkv, g_qkv);
  cudaFuncSetAttribute(kernelA, cudaFuncAttributeMaxDynamicSharedMemorySize, A_SMEM);
  cudaFuncSetAttribute(kernelB, cudaFuncAttributeMaxDynamicSharedMemorySize, B_SMEM);

  CUtensorMap tm_x, tm_wqkvt, tm_wot, tm_wqkvs, tm_x1s, tm_qkvs, tm_q, tm_kv, tm_wos, tm_x1l, tm_out, tm_wf;
  const uint64_t d_act[3] = {192, 1296, 7}, d_qkv[3] = {576, 1296, 7}, d_w3[2] = {576, 192}, d_w1[2] = {192, 192}, d_wf[2] = {384, 384};
  const uint32_t b_a[3] = {64, 9, 7}, b_w[2] = {64, 192}, b_q[3] = {64, 128, 1}, b_kv[3] = {64, 144, 1}, b_o[3] = {64, 64, 1}, b_w64[2] = {64, 64};
  make_map(enc, &tm_x, d_in[0], 3, d_act, b_a);
  make_map(enc, &tm_wqkvt, d_in[1], 2, d_w3, b_w64);
  make_map(enc, &tm_wot, d_in[2], 2, d_w1, b_w);
  make_map(enc, &tm_wqkvs, d_in[3], 2, d_w3, b_w64);
  make_map(enc, &tm_wos, d_in[4], 2, d_w1, b_w);
  make_map(enc, &tm_wf, p_wf, 2, d_wf, b_w);
  make_map(enc, &tm_x1s, p_x1, 3, d_act, b_a);
  make_map(enc, &tm_qkvs, p_qkv, 3, d_qkv, b_a);
  make_map(enc, &tm_q, p_qkv, 3, d_qkv, b_q);
  make_map(enc, &tm_kv, p_qkv, 3, d_qkv, b_kv);
  make_map(enc, &tm_x1l, p_x1, 3, d_act, b_q);
  make_map(enc, &tm_out, d_out, 3, d_act, b_o);

  kernelA<<<72 + A_FOLD, 384, A_SMEM, cudaStreamPerThread>>>(tm_x, tm_wqkvt, tm_wot, tm_wqkvs, tm_wos, tm_wf, tm_x1s, tm_qkvs);
  cudaLaunchConfig_t cfg = {};
  cfg.gridDim = dim3(B_GRID); cfg.blockDim = dim3(384); cfg.dynamicSmemBytes = B_SMEM; cfg.stream = cudaStreamPerThread;
  cudaLaunchAttribute at[1];
  at[0].id = cudaLaunchAttributeProgrammaticStreamSerialization;
  at[0].val.programmaticStreamSerializationAllowed = 1;
  cfg.attrs = at; cfg.numAttrs = 1;
  cudaLaunchKernelEx(&cfg, kernelB, tm_q, tm_kv, tm_x1l, tm_out);
}
```

```cpp
#include <cuda_runtime.h>
#include <cuda_bf16.h>
#include <cuda.h>
#include <stdint.h>

namespace {

constexpr int TT = 7, NL = 1296, CC = 192;

__device__ __align__(1024) __nv_bfloat16 g_x1[TT * NL * CC];
__device__ __align__(1024) __nv_bfloat16 g_qkv[TT * NL * 3 * CC];
__device__ __align__(1024) __nv_bfloat16 g_wf[2 * CC * 2 * CC];
__device__ __align__(1024) uint4 g_part[110 * 2 * 13 * 128];
__device__ unsigned int g_flag[128];
__device__ unsigned int g_wflag[4];

#define TS(k, i)

__device__ __forceinline__ uint32_t smem_u32(const void* p) { return (uint32_t)__cvta_generic_to_shared(p); }
__device__ __forceinline__ void mbar_init(uint32_t bar, uint32_t cnt) {
  asm volatile("mbarrier.init.shared::cta.b64 [%0], %1;" ::"r"(bar), "r"(cnt));
}
__device__ __forceinline__ void mbar_expect_tx(uint32_t bar, uint32_t bytes) {
  asm volatile("mbarrier.arrive.expect_tx.shared::cta.b64 _, [%0], %1;" ::"r"(bar), "r"(bytes) : "memory");
}
__device__ __forceinline__ void mbar_arrive(uint32_t bar) {
  asm volatile("mbarrier.arrive.shared::cta.b64 _, [%0];" ::"r"(bar) : "memory");
}
__device__ __forceinline__ bool mbar_try(uint32_t bar, uint32_t parity) {
  uint32_t ok;
  asm volatile("{\n.reg .pred p;\nmbarrier.try_wait.parity.shared::cta.b64 p, [%1], %2;\nselp.u32 %0, 1, 0, p;\n}"
               : "=r"(ok) : "r"(bar), "r"(parity) : "memory");
  return ok != 0;
}
__device__ __forceinline__ void mbar_wait(uint32_t bar, uint32_t parity) {
  if (mbar_try(bar, parity)) return;
  uint32_t n = 0;
  while (!mbar_try(bar, parity)) {
    if (++n > (1u << 22)) break;
  }
}
__device__ __forceinline__ void tma_load_2d(uint32_t dst, const CUtensorMap* m, uint32_t bar, int c0, int c1) {
  asm volatile("cp.async.bulk.tensor.2d.shared::cluster.global.mbarrier::complete_tx::bytes [%0], [%1, {%3, %4}], [%2];"
               ::"r"(dst), "l"(m), "r"(bar), "r"(c0), "r"(c1) : "memory");
}
__device__ __forceinline__ void tma_load_3d(uint32_t dst, const CUtensorMap* m, uint32_t bar, int c0, int c1, int c2) {
  asm volatile("cp.async.bulk.tensor.3d.shared::cluster.global.mbarrier::complete_tx::bytes [%0], [%1, {%3, %4, %5}], [%2];"
               ::"r"(dst), "l"(m), "r"(bar), "r"(c0), "r"(c1), "r"(c2) : "memory");
}
__device__ __forceinline__ void tma_store_3d(const CUtensorMap* m, uint32_t src, int c0, int c1, int c2) {
  asm volatile("cp.async.bulk.tensor.3d.global.shared::cta.bulk_group [%0, {%2, %3, %4}], [%1];"
               ::"l"(m), "r"(src), "r"(c0), "r"(c1), "r"(c2) : "memory");
}
__device__ __forceinline__ void bulk_commit() { asm volatile("cp.async.bulk.commit_group;" ::: "memory"); }
__device__ __forceinline__ void bulk_wait_read0() { asm volatile("cp.async.bulk.wait_group.read 0;" ::: "memory"); }
__device__ __forceinline__ void bulk_wait_read1() { asm volatile("cp.async.bulk.wait_group.read 1;" ::: "memory"); }
__device__ __forceinline__ void bulk_wait0() { asm volatile("cp.async.bulk.wait_group 0;" ::: "memory"); }
__device__ __forceinline__ void fence_proxy_async() { asm volatile("fence.proxy.async.shared::cta;" ::: "memory"); }
__device__ __forceinline__ void prefetch_tmap(const CUtensorMap* m) {
  asm volatile("prefetch.tensormap [%0];" ::"l"(m) : "memory");
}
__device__ __forceinline__ void wg_fence() { asm volatile("wgmma.fence.sync.aligned;" ::: "memory"); }
__device__ __forceinline__ void wg_commit() { asm volatile("wgmma.commit_group.sync.aligned;" ::: "memory"); }
template <int N> __device__ __forceinline__ void wg_wait() { asm volatile("wgmma.wait_group.sync.aligned %0;" ::"n"(N) : "memory"); }
__device__ __forceinline__ void named_bar(int id, int nthreads) {
  asm volatile("bar.sync %0, %1;" ::"r"(id), "r"(nthreads) : "memory");
}
__device__ __forceinline__ void ldsm_x4(uint32_t (&r)[4], uint32_t addr) {
  asm volatile("ldmatrix.sync.aligned.m8n8.x4.shared.b16 {%0,%1,%2,%3}, [%4];"
               : "=r"(r[0]), "=r"(r[1]), "=r"(r[2]), "=r"(r[3]) : "r"(addr) : "memory");
}
__device__ __forceinline__ void stsm_x4(uint32_t addr, const uint32_t (&r)[4]) {
  asm volatile("stmatrix.sync.aligned.m8n8.x4.shared.b16 [%0], {%1,%2,%3,%4};"
               ::"r"(addr), "r"(r[0]), "r"(r[1]), "r"(r[2]), "r"(r[3]) : "memory");
}
__device__ __forceinline__ uint32_t pack_bf16(float lo, float hi) {
  uint32_t r;
  asm("cvt.rn.bf16x2.f32 %0, %1, %2;" : "=r"(r) : "f"(hi), "f"(lo));
  return r;
}
__device__ __forceinline__ float bf_lo(uint32_t v) { return __uint_as_float(v << 16); }
__device__ __forceinline__ float bf_hi(uint32_t v) { return __uint_as_float(v & 0xffff0000u); }
__device__ __forceinline__ float ex2(float x) {
  float y;
  asm("ex2.approx.ftz.f32 %0, %1;" : "=f"(y) : "f"(x));
  return y;
}
__device__ __forceinline__ uint64_t mk_desc(uint32_t addr, uint32_t lbo, uint32_t sbo) {
  return (uint64_t)((addr & 0x3FFFF) >> 4) | ((uint64_t)((lbo & 0x3FFFF) >> 4) << 16) |
         ((uint64_t)((sbo & 0x3FFFF) >> 4) << 32) | (1ull << 62);
}
__device__ __forceinline__ uint64_t mk_desc_o(uint32_t addr, uint32_t lbo, uint32_t sbo) {
  asm volatile("" : "+r"(addr));
  return mk_desc(addr, lbo, sbo);
}
template <int N> __device__ __forceinline__ void reg_fence(uint32_t (&d)[N]) {
#pragma unroll
  for (int i = 0; i < N; i++) asm volatile("" : "+r"(d[i])::"memory");
}
template <int N> __device__ __forceinline__ void reg_fence(float (&d)[N]) {
#pragma unroll
  for (int i = 0; i < N; i++) asm volatile("" : "+f"(d[i])::"memory");
}

template<int TB> __device__ __forceinline__ void wgmma_n144_ss(float (&d)[72], uint64_t da, uint64_t db, int sc) {
  asm volatile("{\n.reg .pred p;\nsetp.ne.b32 p, %74, 0;\n"
    "wgmma.mma_async.sync.aligned.m64n144k16.f32.bf16.bf16 {%0, %1, %2, %3, %4, %5, %6, %7, %8, %9, %10, %11, %12, %13, %14, %15, %16, %17, %18, %19, %20, %21, %22, %23, %24, %25, %26, %27, %28, %29, %30, %31, %32, %33, %34, %35, %36, %37, %38, %39, %40, %41, %42, %43, %44, %45, %46, %47, %48, %49, %50, %51, %52, %53, %54, %55, %56, %57, %58, %59, %60, %61, %62, %63, %64, %65, %66, %67, %68, %69, %70, %71}, %72, %73, p, 1, 1, 0, %75;\n}\n"
    : "+f"(d[0]), "+f"(d[1]), "+f"(d[2]), "+f"(d[3]), "+f"(d[4]), "+f"(d[5]), "+f"(d[6]), "+f"(d[7]), "+f"(d[8]), "+f"(d[9]), "+f"(d[10]), "+f"(d[11]), "+f"(d[12]), "+f"(d[13]), "+f"(d[14]), "+f"(d[15]), "+f"(d[16]), "+f"(d[17]), "+f"(d[18]), "+f"(d[19]), "+f"(d[20]), "+f"(d[21]), "+f"(d[22]), "+f"(d[23]), "+f"(d[24]), "+f"(d[25]), "+f"(d[26]), "+f"(d[27]), "+f"(d[28]), "+f"(d[29]), "+f"(d[30]), "+f"(d[31]), "+f"(d[32]), "+f"(d[33]), "+f"(d[34]), "+f"(d[35]), "+f"(d[36]), "+f"(d[37]), "+f"(d[38]), "+f"(d[39]), "+f"(d[40]), "+f"(d[41]), "+f"(d[42]), "+f"(d[43]), "+f"(d[44]), "+f"(d[45]), "+f"(d[46]), "+f"(d[47]), "+f"(d[48]), "+f"(d[49]), "+f"(d[50]), "+f"(d[51]), "+f"(d[52]), "+f"(d[53]), "+f"(d[54]), "+f"(d[55]), "+f"(d[56]), "+f"(d[57]), "+f"(d[58]), "+f"(d[59]), "+f"(d[60]), "+f"(d[61]), "+f"(d[62]), "+f"(d[63]), "+f"(d[64]), "+f"(d[65]), "+f"(d[66]), "+f"(d[67]), "+f"(d[68]), "+f"(d[69]), "+f"(d[70]), "+f"(d[71])
    : "l"(da), "l"(db), "r"(sc), "n"(TB));
}
template<int TB> __device__ __forceinline__ void wgmma_n192_rs(float (&d)[96], const uint32_t (&a)[4], uint64_t db, int sc) {
  asm volatile("{\n.reg .pred p;\nsetp.ne.b32 p, %101, 0;\n"
    "wgmma.mma_async.sync.aligned.m64n192k16.f32.bf16.bf16 {%0, %1, %2, %3, %4, %5, %6, %7, %8, %9, %10, %11, %12, %13, %14, %15, %16, %17, %18, %19, %20, %21, %22, %23, %24, %25, %26, %27, %28, %29, %30, %31, %32, %33, %34, %35, %36, %37, %38, %39, %40, %41, %42, %43, %44, %45, %46, %47, %48, %49, %50, %51, %52, %53, %54, %55, %56, %57, %58, %59, %60, %61, %62, %63, %64, %65, %66, %67, %68, %69, %70, %71, %72, %73, %74, %75, %76, %77, %78, %79, %80, %81, %82, %83, %84, %85, %86, %87, %88, %89, %90, %91, %92, %93, %94, %95}, {%96, %97, %98, %99}, %100, p, 1, 1, %102;\n}\n"
    : "+f"(d[0]), "+f"(d[1]), "+f"(d[2]), "+f"(d[3]), "+f"(d[4]), "+f"(d[5]), "+f"(d[6]), "+f"(d[7]), "+f"(d[8]), "+f"(d[9]), "+f"(d[10]), "+f"(d[11]), "+f"(d[12]), "+f"(d[13]), "+f"(d[14]), "+f"(d[15]), "+f"(d[16]), "+f"(d[17]), "+f"(d[18]), "+f"(d[19]), "+f"(d[20]), "+f"(d[21]), "+f"(d[22]), "+f"(d[23]), "+f"(d[24]), "+f"(d[25]), "+f"(d[26]), "+f"(d[27]), "+f"(d[28]), "+f"(d[29]), "+f"(d[30]), "+f"(d[31]), "+f"(d[32]), "+f"(d[33]), "+f"(d[34]), "+f"(d[35]), "+f"(d[36]), "+f"(d[37]), "+f"(d[38]), "+f"(d[39]), "+f"(d[40]), "+f"(d[41]), "+f"(d[42]), "+f"(d[43]), "+f"(d[44]), "+f"(d[45]), "+f"(d[46]), "+f"(d[47]), "+f"(d[48]), "+f"(d[49]), "+f"(d[50]), "+f"(d[51]), "+f"(d[52]), "+f"(d[53]), "+f"(d[54]), "+f"(d[55]), "+f"(d[56]), "+f"(d[57]), "+f"(d[58]), "+f"(d[59]), "+f"(d[60]), "+f"(d[61]), "+f"(d[62]), "+f"(d[63]), "+f"(d[64]), "+f"(d[65]), "+f"(d[66]), "+f"(d[67]), "+f"(d[68]), "+f"(d[69]), "+f"(d[70]), "+f"(d[71]), "+f"(d[72]), "+f"(d[73]), "+f"(d[74]), "+f"(d[75]), "+f"(d[76]), "+f"(d[77]), "+f"(d[78]), "+f"(d[79]), "+f"(d[80]), "+f"(d[81]), "+f"(d[82]), "+f"(d[83]), "+f"(d[84]), "+f"(d[85]), "+f"(d[86]), "+f"(d[87]), "+f"(d[88]), "+f"(d[89]), "+f"(d[90]), "+f"(d[91]), "+f"(d[92]), "+f"(d[93]), "+f"(d[94]), "+f"(d[95])
    : "r"(a[0]), "r"(a[1]), "r"(a[2]), "r"(a[3]), "l"(db), "r"(sc), "n"(TB));
}
template<int TB> __device__ __forceinline__ void wgmma_n64_rs(float (&d)[32], const uint32_t (&a)[4], uint64_t db, int sc) {
  asm volatile("{\n.reg .pred p;\nsetp.ne.b32 p, %37, 0;\n"
    "wgmma.mma_async.sync.aligned.m64n64k16.f32.bf16.bf16 {%0, %1, %2, %3, %4, %5, %6, %7, %8, %9, %10, %11, %12, %13, %14, %15, %16, %17, %18, %19, %20, %21, %22, %23, %24, %25, %26, %27, %28, %29, %30, %31}, {%32, %33, %34, %35}, %36, p, 1, 1, %38;\n}\n"
    : "+f"(d[0]), "+f"(d[1]), "+f"(d[2]), "+f"(d[3]), "+f"(d[4]), "+f"(d[5]), "+f"(d[6]), "+f"(d[7]), "+f"(d[8]), "+f"(d[9]), "+f"(d[10]), "+f"(d[11]), "+f"(d[12]), "+f"(d[13]), "+f"(d[14]), "+f"(d[15]), "+f"(d[16]), "+f"(d[17]), "+f"(d[18]), "+f"(d[19]), "+f"(d[20]), "+f"(d[21]), "+f"(d[22]), "+f"(d[23]), "+f"(d[24]), "+f"(d[25]), "+f"(d[26]), "+f"(d[27]), "+f"(d[28]), "+f"(d[29]), "+f"(d[30]), "+f"(d[31])
    : "r"(a[0]), "r"(a[1]), "r"(a[2]), "r"(a[3]), "l"(db), "r"(sc), "n"(TB));
}
template<int TB> __device__ __forceinline__ void wgmma_n64_ss(float (&d)[32], uint64_t da, uint64_t db, int sc) {
  asm volatile("{\n.reg .pred p;\nsetp.ne.b32 p, %34, 0;\n"
    "wgmma.mma_async.sync.aligned.m64n64k16.f32.bf16.bf16 {%0, %1, %2, %3, %4, %5, %6, %7, %8, %9, %10, %11, %12, %13, %14, %15, %16, %17, %18, %19, %20, %21, %22, %23, %24, %25, %26, %27, %28, %29, %30, %31}, %32, %33, p, 1, 1, 0, %35;\n}\n"
    : "+f"(d[0]), "+f"(d[1]), "+f"(d[2]), "+f"(d[3]), "+f"(d[4]), "+f"(d[5]), "+f"(d[6]), "+f"(d[7]), "+f"(d[8]), "+f"(d[9]), "+f"(d[10]), "+f"(d[11]), "+f"(d[12]), "+f"(d[13]), "+f"(d[14]), "+f"(d[15]), "+f"(d[16]), "+f"(d[17]), "+f"(d[18]), "+f"(d[19]), "+f"(d[20]), "+f"(d[21]), "+f"(d[22]), "+f"(d[23]), "+f"(d[24]), "+f"(d[25]), "+f"(d[26]), "+f"(d[27]), "+f"(d[28]), "+f"(d[29]), "+f"(d[30]), "+f"(d[31])
    : "l"(da), "l"(db), "r"(sc), "n"(TB));
}

struct FragAddr {
  uint32_t rowoff;
  uint32_t rx;
  uint32_t hi;
  __device__ __forceinline__ FragAddr(int warp_in_wg, int lane) {
    int row = 16 * warp_in_wg + (lane & 7) + ((lane >> 3) & 1) * 8;
    rowoff = row * 128;
    rx = row & 7;
    hi = lane >> 4;
  }
  __device__ __forceinline__ uint32_t at(uint32_t chunk_base, int kk4) const {
    return chunk_base + rowoff + ((((uint32_t)kk4 * 2 + hi) ^ rx) << 4);
  }
};

__device__ __forceinline__ void layernorm_frags(uint32_t (&f)[12][4]) {
  float s0[2] = {0.f, 0.f}, s1[2] = {0.f, 0.f}, q0[2] = {0.f, 0.f}, q1[2] = {0.f, 0.f};
#pragma unroll
  for (int k = 0; k < 12; k++) {
#pragma unroll
    for (int hf = 0; hf < 2; hf++) {
      const float a = bf_lo(f[k][2 * hf]), b = bf_hi(f[k][2 * hf]);
      const float c = bf_lo(f[k][2 * hf + 1]), d = bf_hi(f[k][2 * hf + 1]);
      s0[hf] += a + b; q0[hf] = fmaf(a, a, fmaf(b, b, q0[hf]));
      s1[hf] += c + d; q1[hf] = fmaf(c, c, fmaf(d, d, q1[hf]));
    }
  }
  float sa = s0[0] + s0[1], sb_ = s1[0] + s1[1], qa = q0[0] + q0[1], qb_ = q1[0] + q1[1];
  sa += __shfl_xor_sync(0xffffffffu, sa, 1); sb_ += __shfl_xor_sync(0xffffffffu, sb_, 1);
  qa += __shfl_xor_sync(0xffffffffu, qa, 1); qb_ += __shfl_xor_sync(0xffffffffu, qb_, 1);
  sa += __shfl_xor_sync(0xffffffffu, sa, 2); sb_ += __shfl_xor_sync(0xffffffffu, sb_, 2);
  qa += __shfl_xor_sync(0xffffffffu, qa, 2); qb_ += __shfl_xor_sync(0xffffffffu, qb_, 2);
  const float m0 = sa * (1.f / 192.f), m1 = sb_ * (1.f / 192.f);
  const float v0 = fmaxf(fmaf(-m0, m0, qa * (1.f / 192.f)), 0.f), v1 = fmaxf(fmaf(-m1, m1, qb_ * (1.f / 192.f)), 0.f);
  const float r0 = rsqrtf(v0 + 1e-5f), r1 = rsqrtf(v1 + 1e-5f);
  const float c0 = -m0 * r0, c1 = -m1 * r1;
#pragma unroll
  for (int k = 0; k < 12; k++) {
    f[k][0] = pack_bf16(fmaf(bf_lo(f[k][0]), r0, c0), fmaf(bf_hi(f[k][0]), r0, c0));
    f[k][2] = pack_bf16(fmaf(bf_lo(f[k][2]), r0, c0), fmaf(bf_hi(f[k][2]), r0, c0));
    f[k][1] = pack_bf16(fmaf(bf_lo(f[k][1]), r1, c1), fmaf(bf_hi(f[k][1]), r1, c1));
    f[k][3] = pack_bf16(fmaf(bf_lo(f[k][3]), r1, c1), fmaf(bf_hi(f[k][3]), r1, c1));
  }
}

constexpr int A_NST = 5;
constexpr int A_XS = 0;
constexpr int A_VB = 49152;
constexpr int A_W = 98304;
constexpr int A_BAR = A_W + A_NST * 24576;
constexpr int A_SMEM = A_BAR + 256 + 1024;
constexpr int A_FOLD = 36;

__device__ __forceinline__ void a_issue(float (&acc)[32], const uint32_t (&af)[12][4], uint32_t sb, int s) {
  const int st = s % A_NST;
  mbar_wait(sb + A_BAR + st * 8, (s / A_NST) & 1);
  const uint64_t wd = mk_desc_o(sb + A_W + st * 24576, 8192, 1024);
  wg_fence();
#pragma unroll
  for (int kk = 0; kk < 12; kk++) wgmma_n64_rs<1>(acc, af[kk], wd + kk * 128, kk > 0);
  wg_commit();
}
__device__ __forceinline__ void a_release(uint32_t sb, int s, int lane) {
  if (lane == 0) mbar_arrive(sb + A_BAR + 64 + (s % A_NST) * 8);
}
__device__ __forceinline__ void cvt_frags(uint32_t (*dst)[4], const float (&acc)[32]) {
#pragma unroll
  for (int k = 0; k < 4; k++) {
    dst[k][0] = pack_bf16(acc[8 * k + 0], acc[8 * k + 1]);
    dst[k][1] = pack_bf16(acc[8 * k + 2], acc[8 * k + 3]);
    dst[k][2] = pack_bf16(acc[8 * k + 4], acc[8 * k + 5]);
    dst[k][3] = pack_bf16(acc[8 * k + 6], acc[8 * k + 7]);
  }
}
__device__ __forceinline__ void store_chunk(const float (&acc)[32], uint32_t chunk_base, const FragAddr& fa) {
  uint32_t t[4][4];
  cvt_frags(t, acc);
#pragma unroll
  for (int k = 0; k < 4; k++) stsm_x4(fa.at(chunk_base, k), t[k]);
}
__device__ __forceinline__ void resid_chunk(uint32_t (*dst)[4], const float* acc, float s0, float s1, uint32_t chunk_base,
                                            const FragAddr& fa) {
#pragma unroll
  for (int k = 0; k < 4; k++) {
    uint32_t x[4];
    ldsm_x4(x, fa.at(chunk_base, k));
    uint32_t o[4];
    o[0] = pack_bf16(fmaf(acc[8 * k + 0], s0, bf_lo(x[0])), fmaf(acc[8 * k + 1], s0, bf_hi(x[0])));
    o[1] = pack_bf16(fmaf(acc[8 * k + 2], s1, bf_lo(x[1])), fmaf(acc[8 * k + 3], s1, bf_hi(x[1])));
    o[2] = pack_bf16(fmaf(acc[8 * k + 4], s0, bf_lo(x[2])), fmaf(acc[8 * k + 5], s0, bf_hi(x[2])));
    o[3] = pack_bf16(fmaf(acc[8 * k + 6], s1, bf_lo(x[3])), fmaf(acc[8 * k + 7], s1, bf_hi(x[3])));
    stsm_x4(fa.at(chunk_base, k), o);
    if (dst) { dst[k][0] = o[0]; dst[k][1] = o[1]; dst[k][2] = o[2]; dst[k][3] = o[3]; }
  }
}

__global__ void __launch_bounds__(384, 1)
kernelA(const __grid_constant__ CUtensorMap tm_x, const __grid_constant__ CUtensorMap tm_wq64t,
        const __grid_constant__ CUtensorMap tm_wot, const __grid_constant__ CUtensorMap tm_wq64s,
        const __grid_constant__ CUtensorMap tm_wos, const __grid_constant__ CUtensorMap tm_wf,
        const __grid_constant__ CUtensorMap tm_x1, const __grid_constant__ CUtensorMap tm_qkv) {
  extern __shared__ uint8_t smem_raw[];
  const uint32_t sb = (smem_u32(smem_raw) + 1023) & ~1023u;
  const int tid = threadIdx.x, warp = tid >> 5, lane = tid & 31;
  const bool is_fold = blockIdx.x < A_FOLD;
  const int blk = blockIdx.x - A_FOLD;
  if (tid == 256) {
    for (int i = 0; i < A_NST; i++) { mbar_init(sb + A_BAR + i * 8, 1); mbar_init(sb + A_BAR + 64 + i * 8, 8); }
    mbar_init(sb + A_BAR + 128, 1); mbar_init(sb + A_BAR + 136, 1);
    asm volatile("fence.mbarrier_init.release.cluster;" ::: "memory");
    if (!is_fold) {
      for (int w = 0; w < 2; w++) {
        const uint32_t bar = sb + A_BAR + 128 + w * 8;
        mbar_expect_tx(bar, 3 * 63 * 128);
        for (int c = 0; c < 3; c++)
          tma_load_3d(sb + A_XS + w * 24576 + c * 8192, &tm_x, bar, c * 64, (blk * 2 + w) * 9, 0);
      }
    } else {
      const int mat = blockIdx.x / 9, rs = (blockIdx.x % 9) / 3, cs = blockIdx.x % 3;
      const CUtensorMap* mq = (mat < 2) ? &tm_wq64t : &tm_wq64s;
      const CUtensorMap* mo = (mat < 2) ? &tm_wot : &tm_wos;
      const uint32_t bar = sb + A_BAR + 128;
      mbar_expect_tx(bar, 2 * 24576);
      for (int c = 0; c < 3; c++) tma_load_2d(sb + c * 8192, mq, bar, ((mat & 1) ? 384 : 0) + c * 64, rs * 64);
      if (mat & 1) tma_load_2d(sb + 24576, mo, bar, cs * 64, 0);
      else for (int c = 0; c < 3; c++) tma_load_2d(sb + 24576 + c * 8192, mq, bar, 192 + c * 64, cs * 64);
    }
  }
  asm volatile("griddepcontrol.launch_dependents;" ::: "memory");
  if (blockIdx.x == 0 && tid < 128) g_flag[tid] = 0;
  if (!is_fold && tid < 48) {
    uint32_t a = sb + A_XS + (tid >> 3) * 8192 + 63 * 128 + (tid & 7) * 16;
    asm volatile("st.shared.v4.b32 [%0], {%1,%1,%1,%1};" ::"r"(a), "r"(0) : "memory");
  }
  __syncthreads();

  if (warp >= 8) {
    asm volatile("setmaxnreg.dec.sync.aligned.u32 24;");
    if (warp == 8 && lane == 0 && !is_fold) {
      for (int s = 0; s < 12; s++) {
        const int st = s % A_NST;
        const int g = s / 3;
        const int mat = (g == 0) ? 1 : (g == 1) ? 0 : g;
        if (s % 3 == 0) {
          uint32_t n = 0, v;
          do {
            asm volatile("ld.acquire.gpu.global.u32 %0, [%1];" : "=r"(v) : "l"(&g_wflag[mat]) : "memory");
          } while (v < 9u && ++n < (1u << 22));
          asm volatile("fence.proxy.async;" ::: "memory");
        }
        if (s >= A_NST) mbar_wait(sb + A_BAR + 64 + st * 8, ((s / A_NST) - 1) & 1);
        mbar_expect_tx(sb + A_BAR + st * 8, 24576);
        tma_load_2d(sb + A_W + st * 24576, &tm_wf, sb + A_BAR + st * 8, (mat & 1) * 192 + (s % 3) * 64, (mat >> 1) * 192);
      }
    }
    return;
  }

  asm volatile("setmaxnreg.inc.sync.aligned.u32 240;");
  const int wg = warp >> 2, wq = warp & 3;

  if (is_fold) {
    if (wg == 0) {
      const int mat = blockIdx.x / 9, rs = (blockIdx.x % 9) / 3, cs = blockIdx.x % 3;
      float d[32];
      mbar_wait(sb + A_BAR + 128, 0);
      const uint64_t ad = mk_desc_o(sb, 16, 1024);
      if (mat & 1) {
        const uint64_t bd = mk_desc_o(sb + 24576, 8192, 1024);
        wg_fence();
#pragma unroll
        for (int kk = 0; kk < 12; kk++) wgmma_n64_ss<1>(d, ad + (kk >> 2) * 512 + (kk & 3) * 2, bd + kk * 128, kk > 0);
        wg_commit();
      } else {
        const uint64_t bd = mk_desc_o(sb + 24576, 16, 1024);
        wg_fence();
#pragma unroll
        for (int kk = 0; kk < 12; kk++)
          wgmma_n64_ss<0>(d, ad + (kk >> 2) * 512 + (kk & 3) * 2, bd + (kk >> 2) * 512 + (kk & 3) * 2, kk > 0);
        wg_commit();
      }
      wg_wait<0>(); reg_fence(d);
      const int r0 = rs * 64 + wq * 16 + (lane >> 2);
      uint32_t* dst = reinterpret_cast<uint32_t*>(g_wf + ((size_t)(mat >> 1) * 192 + r0) * 384 + (mat & 1) * 192 + cs * 64 + (lane & 3) * 2);
#pragma unroll
      for (int j = 0; j < 8; j++) {
        dst[j * 4] = pack_bf16(d[4 * j], d[4 * j + 1]);
        dst[8 * 192 + j * 4] = pack_bf16(d[4 * j + 2], d[4 * j + 3]);
      }
      asm volatile("fence.proxy.async;" ::: "memory");
      named_bar(1, 128);
      if (tid == 0) { __threadfence(); atomicAdd(&g_wflag[mat], 1u); }
    }
    return;
  }

  const int n0 = (blk * 2 + wg) * 9;
  const FragAddr fa(wq, lane);
  const uint32_t xs = sb + A_XS + wg * 24576, vb = sb + A_VB + wg * 24576;
  const int barid = 1 + wg;
  const bool elected = (tid & 127) == 0;

  uint32_t h[12][4];
  TS(0, 0);
  mbar_wait(sb + A_BAR + 128 + wg * 8, 0);
  TS(0, 1);
#pragma unroll
  for (int k = 0; k < 12; k++) ldsm_x4(h[k], fa.at(xs + (k >> 2) * 8192, k & 3));
  layernorm_frags(h);
#pragma unroll
  for (int k = 0; k < 12; k++) stsm_x4(fa.at(xs + (k >> 2) * 8192, k & 3), h[k]);

  float acc0[32], acc1[32];
  uint32_t qf[12][4];
  TS(0, 2);
  a_issue(acc0, h, sb, 0);
  TS(0, 3);
  a_issue(acc1, h, sb, 1); wg_wait<1>(); reg_fence(acc0); a_release(sb, 0, lane); store_chunk(acc0, vb, fa);
  a_issue(acc0, h, sb, 2); wg_wait<1>(); reg_fence(acc1); a_release(sb, 1, lane); store_chunk(acc1, vb + 8192, fa);
  a_issue(acc1, h, sb, 3); wg_wait<1>(); reg_fence(acc0); a_release(sb, 2, lane); store_chunk(acc0, vb + 16384, fa);
  fence_proxy_async();
  named_bar(barid, 128);
  a_issue(acc0, h, sb, 4); wg_wait<1>(); reg_fence(acc1); a_release(sb, 3, lane); cvt_frags(&qf[0], acc1);
  a_issue(acc1, h, sb, 5); wg_wait<1>(); reg_fence(acc0); a_release(sb, 4, lane); cvt_frags(&qf[4], acc0);
  wg_wait<0>(); reg_fence(acc1); a_release(sb, 5, lane); cvt_frags(&qf[8], acc1);
  TS(0, 4);
  {
    const uint64_t kd = mk_desc_o(xs, 16, 1024);
    wg_fence();
#pragma unroll
    for (int kk = 0; kk < 12; kk++) wgmma_n64_rs<0>(acc0, qf[kk], kd + (kk >> 2) * 512 + (kk & 3) * 2, kk > 0);
    wg_commit();
    wg_wait<0>(); reg_fence(acc0);
  }
  named_bar(barid, 128);
  if (elected) {
    const uint32_t bar = sb + A_BAR + 128 + wg * 8;
    mbar_expect_tx(bar, 3 * 63 * 128);
    for (int c = 0; c < 3; c++) tma_load_3d(xs + c * 8192, &tm_x, bar, c * 64, n0, 0);
  }
  uint32_t pf[4][4];
  {
    const int r0 = 16 * wq + (lane >> 2), r1 = r0 + 8;
    const unsigned long long MB = 0x0040201008040201ull;
    const unsigned long long mk0 = (MB << (r0 % 9)) >> (2 * (lane & 3));
    const unsigned long long mk1 = (MB << (r1 % 9)) >> (2 * (lane & 3));
    const float cs = 0.07216878364870322f * 1.4426950408889634f;
    float mx0 = -INFINITY, mx1 = -INFINITY;
#pragma unroll
    for (int j = 0; j < 8; j++) {
#pragma unroll
      for (int e = 0; e < 2; e++) {
        bool v0 = (mk0 >> (8 * j + e)) & 1, v1 = (mk1 >> (8 * j + e)) & 1;
        acc0[4 * j + e] = v0 ? acc0[4 * j + e] * cs : -INFINITY;
        acc0[4 * j + 2 + e] = v1 ? acc0[4 * j + 2 + e] * cs : -INFINITY;
        mx0 = fmaxf(mx0, acc0[4 * j + e]);
        mx1 = fmaxf(mx1, acc0[4 * j + 2 + e]);
      }
    }
    mx0 = fmaxf(mx0, __shfl_xor_sync(0xffffffffu, mx0, 1)); mx0 = fmaxf(mx0, __shfl_xor_sync(0xffffffffu, mx0, 2));
    mx1 = fmaxf(mx1, __shfl_xor_sync(0xffffffffu, mx1, 1)); mx1 = fmaxf(mx1, __shfl_xor_sync(0xffffffffu, mx1, 2));
    float l0 = 0.f, l1 = 0.f;
#pragma unroll
    for (int j = 0; j < 8; j++) {
#pragma unroll
      for (int e = 0; e < 2; e++) {
        acc0[4 * j + e] = ex2(acc0[4 * j + e] - mx0); l0 += acc0[4 * j + e];
        acc0[4 * j + 2 + e] = ex2(acc0[4 * j + 2 + e] - mx1); l1 += acc0[4 * j + 2 + e];
      }
    }
    l0 += __shfl_xor_sync(0xffffffffu, l0, 1); l0 += __shfl_xor_sync(0xffffffffu, l0, 2);
    l1 += __shfl_xor_sync(0xffffffffu, l1, 1); l1 += __shfl_xor_sync(0xffffffffu, l1, 2);
    const float i0 = 1.f / l0, i1 = 1.f / l1;
#pragma unroll
    for (int j = 0; j < 8; j++) {
      acc0[4 * j] *= i0; acc0[4 * j + 1] *= i0; acc0[4 * j + 2] *= i1; acc0[4 * j + 3] *= i1;
    }
    cvt_frags(pf, acc0);
  }
  TS(0, 5);
  {
    float oacc[96];
    const uint64_t vd = mk_desc_o(vb, 8192, 1024);
    wg_fence();
#pragma unroll
    for (int kk = 0; kk < 4; kk++) wgmma_n192_rs<1>(oacc, pf[kk], vd + kk * 128, kk > 0);
    wg_commit();
    wg_wait<0>(); reg_fence(oacc);
    TS(0, 6);
    mbar_wait(sb + A_BAR + 128 + wg * 8, 1);
#pragma unroll
    for (int c = 0; c < 3; c++) resid_chunk(&h[4 * c], &oacc[32 * c], 1.f, 1.f, xs + c * 8192, fa);
  }
  TS(0, 7);
  fence_proxy_async();
  named_bar(barid, 128);
  if (elected) {
    for (int c = 0; c < 3; c++) tma_store_3d(&tm_x1, xs + c * 8192, c * 64, n0, 0);
    bulk_commit();
  }
  layernorm_frags(h);
#pragma unroll
  for (int k = 0; k < 12; k++) stsm_x4(fa.at(vb + (k >> 2) * 8192, k & 3), h[k]);
  TS(0, 8);
  a_issue(acc0, h, sb, 6);
  a_issue(acc1, h, sb, 7);
  fence_proxy_async();
  if (elected) bulk_wait_read0();
  named_bar(barid, 128);
  if (elected) {
    for (int c = 0; c < 3; c++) tma_store_3d(&tm_qkv, vb + c * 8192, 192 + c * 64, n0, 0);
    bulk_commit();
  }
  wg_wait<1>(); reg_fence(acc0); a_release(sb, 6, lane); store_chunk(acc0, xs, fa);
  a_issue(acc0, h, sb, 8); wg_wait<1>(); reg_fence(acc1); store_chunk(acc1, xs + 8192, fa);
  a_issue(acc1, h, sb, 9); wg_wait<1>(); reg_fence(acc0); store_chunk(acc0, xs + 16384, fa);
  a_issue(acc0, h, sb, 10);
  fence_proxy_async();
  if (elected) bulk_wait_read0();
  named_bar(barid, 128);
  if (elected) {
    for (int c = 0; c < 3; c++) tma_store_3d(&tm_qkv, xs + c * 8192, c * 64, n0, 0);
    bulk_commit();
  }
  wg_wait<1>(); reg_fence(acc1); store_chunk(acc1, vb, fa);
  a_issue(acc1, h, sb, 11); wg_wait<1>(); reg_fence(acc0); store_chunk(acc0, vb + 8192, fa);
  wg_wait<0>(); reg_fence(acc1); store_chunk(acc1, vb + 16384, fa);
  fence_proxy_async();
  named_bar(barid, 128);
  TS(0, 9);
  if (elected) {
    for (int c = 0; c < 3; c++) tma_store_3d(&tm_qkv, vb + c * 8192, 384 + c * 64, n0, 0);
    bulk_commit();
    bulk_wait_read0();
  }
  TS(0, 10);
}

constexpr int B_GRID = 132;
constexpr int B_SLOT = 55296;
constexpr int B_Q = 0;
constexpr int B_KV = 49152;
constexpr int B_BAR = B_KV + 3 * B_SLOT;
constexpr int B_SMEM = B_BAR + 256 + 1024;

__device__ __forceinline__ void bar_arrive(int id, int nthreads) {
  asm volatile("bar.arrive %0, %1;" ::"r"(id), "r"(nthreads) : "memory");
}
__device__ __forceinline__ void b_segment(int sg, int& tile, int& k0, int& k1) {
  const int grp = blockIdx.x / 12, ci = blockIdx.x - grp * 12;
  if (ci < 7) { tile = grp * 7 + ci; k0 = 3; k1 = 9; }
  else {
    const int hh = ci - 7;
    tile = grp * 7 + ((0x54210 >> (4 * hh)) & 15) + sg;
    k0 = sg ? 0 : ((0x10210 >> (4 * hh)) & 15);
    k1 = sg ? ((0x31321 >> (4 * hh)) & 15) : 3;
  }
}

__global__ void __launch_bounds__(384, 1)
kernelB(const __grid_constant__ CUtensorMap tm_q, const __grid_constant__ CUtensorMap tm_kv,
        const __grid_constant__ CUtensorMap tm_x1, const __grid_constant__ CUtensorMap tm_out) {
  extern __shared__ uint8_t smem_raw[];
  const uint32_t sb = (smem_u32(smem_raw) + 1023) & ~1023u;
  const int tid = threadIdx.x, warp = tid >> 5, lane = tid & 31;
  const uint32_t bF = sb + B_BAR, bE = sb + B_BAR + 32, bQF = sb + B_BAR + 64, bQE = sb + B_BAR + 72;
  if (tid == 0) {
    for (int i = 0; i < 3; i++) { mbar_init(bF + i * 8, 1); mbar_init(bE + i * 8, 8); }
    mbar_init(bQF, 1); mbar_init(bQE, 8);
    asm volatile("fence.mbarrier_init.release.cluster;" ::: "memory");
    prefetch_tmap(&tm_q); prefetch_tmap(&tm_kv); prefetch_tmap(&tm_x1); prefetch_tmap(&tm_out);
  }
  __syncthreads();
  asm volatile("griddepcontrol.wait;" ::: "memory");
  const int grp = blockIdx.x / 12, ci = blockIdx.x - grp * 12;
  const bool owner = ci < 7;
  const int nseg = owner ? 1 : 2;

  if (warp >= 8) {
    asm volatile("setmaxnreg.dec.sync.aligned.u32 24;");
    if (warp == 8 && lane == 0) {
      if (blockIdx.x == 0) { g_wflag[0] = 0; g_wflag[1] = 0; g_wflag[2] = 0; g_wflag[3] = 0; }
      int it = 0;
      for (int sg = 0; sg < nseg; sg++) {
        int tile, k0, k1;
        b_segment(sg, tile, k0, k1);
        const int t = tile / 11, qt = tile - t * 11;
        if (sg > 0) mbar_wait(bQE, 0);
        mbar_expect_tx(bQF, 49152);
        for (int c = 0; c < 3; c++) tma_load_3d(sb + B_Q + c * 16384, &tm_q, bQF, c * 64, qt * 128, t);
        const int n = k1 - k0;
        for (int e = 0; e < 2 * n; e++) {
          const int sl = it % 3;
          if (it >= 3) mbar_wait(bE + sl * 8, ((it / 3) - 1) & 1);
          mbar_expect_tx(bF + sl * 8, B_SLOT);
          for (int c = 0; c < 3; c++)
            tma_load_3d(sb + B_KV + sl * B_SLOT + c * 18432, &tm_kv, bF + sl * 8, 192 + (e & 1) * 192 + c * 64, (k0 + (e >> 1)) * 144, t);
          it++;
        }
      }
      if (owner) {
        const int tile = grp * 7 + ci;
        const int t = tile / 11, qt = tile - t * 11;
        mbar_wait(bQE, 0);
        mbar_expect_tx(bQF, 49152);
        for (int c = 0; c < 3; c++) tma_load_3d(sb + B_Q + c * 16384, &tm_x1, bQF, c * 64, qt * 128, t);
      }
    } else if ((warp == 9 || warp == 10) && !owner) {
      for (int sg = 0; sg < 2; sg++) {
        named_bar(5 + (warp - 9), 160);
        if (lane == 0) {
          __threadfence();
          atomicAdd(&g_flag[(grp * 5 + (ci - 7)) * 2 + sg], 1u);
        }
        __syncwarp();
      }
    }
    return;
  }

  asm volatile("setmaxnreg.inc.sync.aligned.u32 240;");
  const int wg = warp >> 2, wq = warp & 3;
  const int wtid = tid & 127;
  const float cs = 0.07216878364870322f * 1.4426950408889634f;
  float oacc[96], sacc[72];
  uint32_t pf[9][4];
  float m0, m1, l0, l1;
  int it = 0;
  const uint32_t qb = sb + B_Q + wg * 8192;
  if (wg == 1) bar_arrive(3, 256);
  TS(1, 0);
  int tsi = 1;

  auto issue_qk = [&](int slot) {
    const uint64_t kd = mk_desc_o(sb + B_KV + slot * B_SLOT, 16, 1024);
    const uint64_t qd = mk_desc_o(qb, 16, 1024);
#pragma unroll
    for (int kk = 0; kk < 12; kk++)
      wgmma_n144_ss<0>(sacc, qd + (kk >> 2) * 1024 + (kk & 3) * 2, kd + (kk >> 2) * 1152 + (kk & 3) * 2, kk > 0);
    wg_commit();
  };
  auto issue_pv = [&](int slot, int accum) {
    const uint64_t vd = mk_desc_o(sb + B_KV + slot * B_SLOT, 18432, 1024);
#pragma unroll
    for (int kk = 0; kk < 9; kk++) wgmma_n192_rs<1>(oacc, pf[kk], vd + kk * 128, kk > 0 ? 1 : accum);
    wg_commit();
  };
  auto softmax = [&](bool rescale) {
    float t0[4], t1[4];
#pragma unroll
    for (int q = 0; q < 4; q++) {
      t0[q] = fmaxf(sacc[4 * q], sacc[4 * q + 1]);
      t1[q] = fmaxf(sacc[4 * q + 2], sacc[4 * q + 3]);
    }
#pragma unroll
    for (int j = 4; j < 18; j++) {
      t0[j & 3] = fmaxf(t0[j & 3], fmaxf(sacc[4 * j], sacc[4 * j + 1]));
      t1[j & 3] = fmaxf(t1[j & 3], fmaxf(sacc[4 * j + 2], sacc[4 * j + 3]));
    }
    float mx0 = fmaxf(fmaxf(t0[0], t0[1]), fmaxf(fmaxf(t0[2], t0[3]), m0));
    float mx1 = fmaxf(fmaxf(t1[0], t1[1]), fmaxf(fmaxf(t1[2], t1[3]), m1));
    mx0 = fmaxf(mx0, __shfl_xor_sync(0xffffffffu, mx0, 1)); mx1 = fmaxf(mx1, __shfl_xor_sync(0xffffffffu, mx1, 1));
    mx0 = fmaxf(mx0, __shfl_xor_sync(0xffffffffu, mx0, 2)); mx1 = fmaxf(mx1, __shfl_xor_sync(0xffffffffu, mx1, 2));
    const float a0 = ex2((m0 - mx0) * cs), a1 = ex2((m1 - mx1) * cs);
    m0 = mx0; m1 = mx1;
    const float mc0 = mx0 * cs, mc1 = mx1 * cs;
#pragma unroll
    for (int q = 0; q < 4; q++) { t0[q] = 0.f; t1[q] = 0.f; }
#pragma unroll
    for (int k = 0; k < 9; k++) {
      float p[8];
#pragma unroll
      for (int e = 0; e < 8; e++) p[e] = ex2(fmaf(sacc[8 * k + e], cs, (e & 2) ? -mc1 : -mc0));
      t0[0] += p[0]; t0[1] += p[1]; t0[2] += p[4]; t0[3] += p[5];
      t1[0] += p[2]; t1[1] += p[3]; t1[2] += p[6]; t1[3] += p[7];
      pf[k][0] = pack_bf16(p[0], p[1]); pf[k][1] = pack_bf16(p[2], p[3]);
      pf[k][2] = pack_bf16(p[4], p[5]); pf[k][3] = pack_bf16(p[6], p[7]);
    }
    l0 = l0 * a0 + ((t0[0] + t0[1]) + (t0[2] + t0[3]));
    l1 = l1 * a1 + ((t1[0] + t1[1]) + (t1[2] + t1[3]));
    if (rescale) {
#pragma unroll
      for (int i = 0; i < 24; i++) {
        oacc[4 * i] *= a0; oacc[4 * i + 1] *= a0; oacc[4 * i + 2] *= a1; oacc[4 * i + 3] *= a1;
      }
    }
  };

  for (int sg = 0; sg < nseg; sg++) {
    int n;
    { int tile, k0, k1; b_segment(sg, tile, k0, k1); n = k1 - k0; }
    m0 = m1 = -INFINITY; l0 = l1 = 0.f;
    mbar_wait(bQF, sg & 1);
    {
      const int sl = it % 3;
      mbar_wait(bF + sl * 8, (it / 3) & 1);
      named_bar(3 + wg, 256);
      wg_fence();
      issue_qk(sl);
      bar_arrive(3 + (wg ^ 1), 256);
      wg_wait<0>(); reg_fence(sacc);
      if (lane == 0) { mbar_arrive(bE + sl * 8); if (n == 1) mbar_arrive(bQE); }
      it++;
      softmax(false);
    }
    TS(1, tsi); tsi++;
    for (int j = 1; j < n; j++) {
      const int slv = it % 3, slk = (it + 1) % 3;
      mbar_wait(bF + slv * 8, (it / 3) & 1);
      named_bar(3 + wg, 256);
      wg_fence();
      issue_pv(slv, j > 1);
      mbar_wait(bF + slk * 8, ((it + 1) / 3) & 1);
      issue_qk(slk);
      bar_arrive(3 + (wg ^ 1), 256);
      wg_wait<1>(); reg_fence(oacc);
      if (lane == 0) mbar_arrive(bE + slv * 8);
      wg_wait<0>(); reg_fence(sacc);
      if (lane == 0) { mbar_arrive(bE + slk * 8); if (j == n - 1) mbar_arrive(bQE); }
      it += 2;
      softmax(true);
      TS(1, tsi); tsi++;
    }
    {
      const int sl = it % 3;
      mbar_wait(bF + sl * 8, (it / 3) & 1);
      named_bar(3 + wg, 256);
      wg_fence();
      issue_pv(sl, n > 1);
      if (!(wg == 1 && sg == nseg - 1)) bar_arrive(3 + (wg ^ 1), 256);
      wg_wait<0>(); reg_fence(oacc);
      if (lane == 0) mbar_arrive(bE + sl * 8);
      it++;
    }
    TS(1, tsi); tsi++;
    if (!owner) {
      const int slot = (grp * 5 + (ci - 7)) * 2 + sg;
      uint4* dst = g_part + (size_t)(slot * 2 + wg) * 13 * 128 + wtid;
#pragma unroll
      for (int i = 0; i < 12; i++)
        dst[i * 128] = make_uint4(pack_bf16(oacc[8 * i], oacc[8 * i + 1]), pack_bf16(oacc[8 * i + 2], oacc[8 * i + 3]),
                                  pack_bf16(oacc[8 * i + 4], oacc[8 * i + 5]), pack_bf16(oacc[8 * i + 6], oacc[8 * i + 7]));
      dst[12 * 128] = make_uint4(__float_as_uint(m0), __float_as_uint(m1), __float_as_uint(l0), __float_as_uint(l1));
      bar_arrive(5 + wg, 160);
      TS(1, tsi); tsi++;
    }
  }
  if (!owner) return;

  {
    const int first = (0x9765310 >> (4 * ci)) & 15, cnt = (0x1211221 >> (4 * ci)) & 15;
    const int slot0 = grp * 10 + first;
    if (wtid < cnt) {
      uint32_t n = 0, v;
      do {
        asm volatile("ld.acquire.gpu.global.u32 %0, [%1];" : "=r"(v) : "l"(&g_flag[slot0 + wtid]) : "memory");
      } while (v < 2u && ++n < (1u << 22));
    }
    named_bar(1 + wg, 128);
    uint4 pv[2][13];
#pragma unroll
    for (int q = 0; q < 2; q++) {
      if (q < cnt) {
        const uint4* src = g_part + (size_t)((slot0 + q) * 2 + wg) * 13 * 128 + wtid;
#pragma unroll
        for (int i = 0; i < 13; i++) pv[q][i] = __ldcg(src + i * 128);
      }
    }
#pragma unroll
    for (int q = 0; q < 2; q++) {
      if (q < cnt) {
        const float pm0 = __uint_as_float(pv[q][12].x), pm1 = __uint_as_float(pv[q][12].y);
        const float mx0 = fmaxf(m0, pm0), mx1 = fmaxf(m1, pm1);
        const float a0 = ex2((m0 - mx0) * cs), a1 = ex2((m1 - mx1) * cs);
        const float b0 = ex2((pm0 - mx0) * cs), b1 = ex2((pm1 - mx1) * cs);
        m0 = mx0; m1 = mx1;
        l0 = l0 * a0 + __uint_as_float(pv[q][12].z) * b0; l1 = l1 * a1 + __uint_as_float(pv[q][12].w) * b1;
#pragma unroll
        for (int i = 0; i < 12; i++) {
          const uint4 v = pv[q][i];
          oacc[8 * i + 0] = oacc[8 * i + 0] * a0 + bf_lo(v.x) * b0; oacc[8 * i + 1] = oacc[8 * i + 1] * a0 + bf_hi(v.x) * b0;
          oacc[8 * i + 2] = oacc[8 * i + 2] * a1 + bf_lo(v.y) * b1; oacc[8 * i + 3] = oacc[8 * i + 3] * a1 + bf_hi(v.y) * b1;
          oacc[8 * i + 4] = oacc[8 * i + 4] * a0 + bf_lo(v.z) * b0; oacc[8 * i + 5] = oacc[8 * i + 5] * a0 + bf_hi(v.z) * b0;
          oacc[8 * i + 6] = oacc[8 * i + 6] * a1 + bf_lo(v.w) * b1; oacc[8 * i + 7] = oacc[8 * i + 7] * a1 + bf_hi(v.w) * b1;
        }
      }
    }
  }
  TS(1, 21);
  l0 += __shfl_xor_sync(0xffffffffu, l0, 1); l0 += __shfl_xor_sync(0xffffffffu, l0, 2);
  l1 += __shfl_xor_sync(0xffffffffu, l1, 1); l1 += __shfl_xor_sync(0xffffffffu, l1, 2);
  const float i0 = 1.f / l0, i1 = 1.f / l1;
  mbar_wait(bQF, 1);
  const FragAddr fa(wq, lane);
#pragma unroll
  for (int c = 0; c < 3; c++) resid_chunk(nullptr, &oacc[32 * c], i0, i1, qb + c * 16384, fa);
  fence_proxy_async();
  named_bar(1 + wg, 128);
  TS(1, 22);
  if (wtid == 0) {
    const int tile = grp * 7 + ci;
    const int t = tile / 11, qt = tile - t * 11;
    if (qt * 128 + wg * 64 < NL) {
      for (int c = 0; c < 3; c++) tma_store_3d(&tm_out, qb + c * 16384, c * 64, qt * 128 + wg * 64, t);
      bulk_commit();
      bulk_wait_read0();
    }
  }
  TS(1, 23);
}

typedef CUresult (*EncodeFn)(CUtensorMap*, CUtensorMapDataType, cuuint32_t, void*, const cuuint64_t*, const cuuint64_t*,
                             const cuuint32_t*, const cuuint32_t*, CUtensorMapInterleave, CUtensorMapSwizzle,
                             CUtensorMapL2promotion, CUtensorMapFloatOOBfill);

void make_map(EncodeFn enc, CUtensorMap* m, const void* ptr, int rank, const uint64_t* dims, const uint32_t* box) {
  cuuint64_t gd[3], gs[2];
  cuuint32_t bx[3], es[3] = {1, 1, 1};
  uint64_t stride = 2;
  for (int i = 0; i < rank; i++) {
    gd[i] = dims[i]; bx[i] = box[i];
    stride *= dims[i];
    if (i < rank - 1) gs[i] = stride;
  }
  enc(m, CU_TENSOR_MAP_DATA_TYPE_BFLOAT16, rank, const_cast<void*>(ptr), gd, gs, bx, es, CU_TENSOR_MAP_INTERLEAVE_NONE,
      CU_TENSOR_MAP_SWIZZLE_128B, CU_TENSOR_MAP_L2_PROMOTION_L2_256B, CU_TENSOR_MAP_FLOAT_OOB_FILL_NONE);
}

}

extern "C" void kernel_launch(void* const* d_in, const int* in_sizes, int n_in, void* d_out, int out_size) {
  (void)in_sizes; (void)n_in; (void)out_size;
  EncodeFn enc = nullptr;
  cudaDriverEntryPointQueryResult qres;
  cudaGetDriverEntryPoint("cuTensorMapEncodeTiled", (void**)&enc, cudaEnableDefault, &qres);
  void *p_x1, *p_qkv, *p_wf;
  cudaGetSymbolAddress(&p_wf, g_wf);
  cudaGetSymbolAddress(&p_x1, g_x1);
  cudaGetSymbolAddress(&p_qkv, g_qkv);
  cudaFuncSetAttribute(kernelA, cudaFuncAttributeMaxDynamicSharedMemorySize, A_SMEM);
  cudaFuncSetAttribute(kernelB, cudaFuncAttributeMaxDynamicSharedMemorySize, B_SMEM);

  CUtensorMap tm_x, tm_wqkvt, tm_wot, tm_wqkvs, tm_x1s, tm_qkvs, tm_q, tm_kv, tm_wos, tm_x1l, tm_out, tm_wf;
  const uint64_t d_act[3] = {192, 1296, 7}, d_qkv[3] = {576, 1296, 7}, d_w3[2] = {576, 192}, d_w1[2] = {192, 192}, d_wf[2] = {384, 384};
  const uint32_t b_a[3] = {64, 9, 7}, b_w[2] = {64, 192}, b_q[3] = {64, 128, 1}, b_kv[3] = {64, 144, 1}, b_o[3] = {64, 64, 1}, b_w64[2] = {64, 64};
  make_map(enc, &tm_x, d_in[0], 3, d_act, b_a);
  make_map(enc, &tm_wqkvt, d_in[1], 2, d_w3, b_w64);
  make_map(enc, &tm_wot, d_in[2], 2, d_w1, b_w);
  make_map(enc, &tm_wqkvs, d_in[3], 2, d_w3, b_w64);
  make_map(enc, &tm_wos, d_in[4], 2, d_w1, b_w);
  make_map(enc, &tm_wf, p_wf, 2, d_wf, b_w);
  make_map(enc, &tm_x1s, p_x1, 3, d_act, b_a);
  make_map(enc, &tm_qkvs, p_qkv, 3, d_qkv, b_a);
  make_map(enc, &tm_q, p_qkv, 3, d_qkv, b_q);
  make_map(enc, &tm_kv, p_qkv, 3, d_qkv, b_kv);
  make_map(enc, &tm_x1l, p_x1, 3, d_act, b_q);
  make_map(enc, &tm_out, d_out, 3, d_act, b_o);

  kernelA<<<72 + A_FOLD, 384, A_SMEM, cudaStreamPerThread>>>(tm_x, tm_wqkvt, tm_wot, tm_wqkvs, tm_wos, tm_wf, tm_x1s, tm_qkvs);
  cudaLaunchConfig_t cfg = {};
  cfg.gridDim = dim3(B_GRID); cfg.blockDim = dim3(384); cfg.dynamicSmemBytes = B_SMEM; cfg.stream = cudaStreamPerThread;
  cudaLaunchAttribute at[1];
  at[0].id = cudaLaunchAttributeProgrammaticStreamSerialization;
  at[0].val.programmaticStreamSerializationAllowed = 1;
  cfg.attrs = at; cfg.numAttrs = 1;
  cudaLaunchKernelEx(&cfg, kernelB, tm_q, tm_kv, tm_x1l, tm_out);
}
```

```cpp
#include <cuda_runtime.h>
#include <cuda_bf16.h>
#include <cuda.h>
#include <stdint.h>

namespace {

constexpr int TT = 7, NL = 1296, CC = 192;

__device__ __align__(1024) __nv_bfloat16 g_x1[TT * NL * CC];
__device__ __align__(1024) __nv_bfloat16 g_qkv[TT * NL * 3 * CC];
__device__ __align__(1024) __nv_bfloat16 g_wf[2 * CC * 2 * CC];
__device__ __align__(1024) uint4 g_part[110 * 2 * 13 * 128];
__device__ unsigned int g_flag[128];
__device__ unsigned int g_wflag[4];

#define TS(k, i)

__device__ __forceinline__ uint32_t smem_u32(const void* p) { return (uint32_t)__cvta_generic_to_shared(p); }
__device__ __forceinline__ void mbar_init(uint32_t bar, uint32_t cnt) {
  asm volatile("mbarrier.init.shared::cta.b64 [%0], %1;" ::"r"(bar), "r"(cnt));
}
__device__ __forceinline__ void mbar_expect_tx(uint32_t bar, uint32_t bytes) {
  asm volatile("mbarrier.arrive.expect_tx.shared::cta.b64 _, [%0], %1;" ::"r"(bar), "r"(bytes) : "memory");
}
__device__ __forceinline__ void mbar_arrive(uint32_t bar) {
  asm volatile("mbarrier.arrive.shared::cta.b64 _, [%0];" ::"r"(bar) : "memory");
}
__device__ __forceinline__ bool mbar_try(uint32_t bar, uint32_t parity) {
  uint32_t ok;
  asm volatile("{\n.reg .pred p;\nmbarrier.try_wait.parity.shared::cta.b64 p, [%1], %2;\nselp.u32 %0, 1, 0, p;\n}"
               : "=r"(ok) : "r"(bar), "r"(parity) : "memory");
  return ok != 0;
}
__device__ __forceinline__ void mbar_wait(uint32_t bar, uint32_t parity) {
  if (mbar_try(bar, parity)) return;
  uint32_t n = 0;
  while (!mbar_try(bar, parity)) {
    if (++n > (1u << 22)) break;
  }
}
__device__ __forceinline__ void tma_load_2d(uint32_t dst, const CUtensorMap* m, uint32_t bar, int c0, int c1) {
  asm volatile("cp.async.bulk.tensor.2d.shared::cluster.global.mbarrier::complete_tx::bytes [%0], [%1, {%3, %4}], [%2];"
               ::"r"(dst), "l"(m), "r"(bar), "r"(c0), "r"(c1) : "memory");
}
__device__ __forceinline__ void tma_load_3d(uint32_t dst, const CUtensorMap* m, uint32_t bar, int c0, int c1, int c2) {
  asm volatile("cp.async.bulk.tensor.3d.shared::cluster.global.mbarrier::complete_tx::bytes [%0], [%1, {%3, %4, %5}], [%2];"
               ::"r"(dst), "l"(m), "r"(bar), "r"(c0), "r"(c1), "r"(c2) : "memory");
}
__device__ __forceinline__ void tma_store_3d(const CUtensorMap* m, uint32_t src, int c0, int c1, int c2) {
  asm volatile("cp.async.bulk.tensor.3d.global.shared::cta.bulk_group [%0, {%2, %3, %4}], [%1];"
               ::"l"(m), "r"(src), "r"(c0), "r"(c1), "r"(c2) : "memory");
}
__device__ __forceinline__ void bulk_commit() { asm volatile("cp.async.bulk.commit_group;" ::: "memory"); }
__device__ __forceinline__ void bulk_wait_read0() { asm volatile("cp.async.bulk.wait_group.read 0;" ::: "memory"); }
__device__ __forceinline__ void bulk_wait_read1() { asm volatile("cp.async.bulk.wait_group.read 1;" ::: "memory"); }
__device__ __forceinline__ void bulk_wait0() { asm volatile("cp.async.bulk.wait_group 0;" ::: "memory"); }
__device__ __forceinline__ void fence_proxy_async() { asm volatile("fence.proxy.async.shared::cta;" ::: "memory"); }
__device__ __forceinline__ void prefetch_tmap(const CUtensorMap* m) {
  asm volatile("prefetch.tensormap [%0];" ::"l"(m) : "memory");
}
__device__ __forceinline__ void wg_fence() { asm volatile("wgmma.fence.sync.aligned;" ::: "memory"); }
__device__ __forceinline__ void wg_commit() { asm volatile("wgmma.commit_group.sync.aligned;" ::: "memory"); }
template <int N> __device__ __forceinline__ void wg_wait() { asm volatile("wgmma.wait_group.sync.aligned %0;" ::"n"(N) : "memory"); }
__device__ __forceinline__ void named_bar(int id, int nthreads) {
  asm volatile("bar.sync %0, %1;" ::"r"(id), "r"(nthreads) : "memory");
}
__device__ __forceinline__ void ldsm_x4(uint32_t (&r)[4], uint32_t addr) {
  asm volatile("ldmatrix.sync.aligned.m8n8.x4.shared.b16 {%0,%1,%2,%3}, [%4];"
               : "=r"(r[0]), "=r"(r[1]), "=r"(r[2]), "=r"(r[3]) : "r"(addr) : "memory");
}
__device__ __forceinline__ void stsm_x4(uint32_t addr, const uint32_t (&r)[4]) {
  asm volatile("stmatrix.sync.aligned.m8n8.x4.shared.b16 [%0], {%1,%2,%3,%4};"
               ::"r"(addr), "r"(r[0]), "r"(r[1]), "r"(r[2]), "r"(r[3]) : "memory");
}
__device__ __forceinline__ uint32_t pack_bf16(float lo, float hi) {
  uint32_t r;
  asm("cvt.rn.bf16x2.f32 %0, %1, %2;" : "=r"(r) : "f"(hi), "f"(lo));
  return r;
}
__device__ __forceinline__ float bf_lo(uint32_t v) { return __uint_as_float(v << 16); }
__device__ __forceinline__ float bf_hi(uint32_t v) { return __uint_as_float(v & 0xffff0000u); }
__device__ __forceinline__ float ex2(float x) {
  float y;
  asm("ex2.approx.ftz.f32 %0, %1;" : "=f"(y) : "f"(x));
  return y;
}
__device__ __forceinline__ uint64_t mk_desc(uint32_t addr, uint32_t lbo, uint32_t sbo) {
  return (uint64_t)((addr & 0x3FFFF) >> 4) | ((uint64_t)((lbo & 0x3FFFF) >> 4) << 16) |
         ((uint64_t)((sbo & 0x3FFFF) >> 4) << 32) | (1ull << 62);
}
__device__ __forceinline__ uint64_t mk_desc_o(uint32_t addr, uint32_t lbo, uint32_t sbo) {
  asm volatile("" : "+r"(addr));
  return mk_desc(addr, lbo, sbo);
}
template <int N> __device__ __forceinline__ void reg_fence(uint32_t (&d)[N]) {
#pragma unroll
  for (int i = 0; i < N; i++) asm volatile("" : "+r"(d[i])::"memory");
}
template <int N> __device__ __forceinline__ void reg_fence(float (&d)[N]) {
#pragma unroll
  for (int i = 0; i < N; i++) asm volatile("" : "+f"(d[i])::"memory");
}

template<int TB> __device__ __forceinline__ void wgmma_n144_ss(float (&d)[72], uint64_t da, uint64_t db, int sc) {
  asm volatile("{\n.reg .pred p;\nsetp.ne.b32 p, %74, 0;\n"
    "wgmma.mma_async.sync.aligned.m64n144k16.f32.bf16.bf16 {%0, %1, %2, %3, %4, %5, %6, %7, %8, %9, %10, %11, %12, %13, %14, %15, %16, %17, %18, %19, %20, %21, %22, %23, %24, %25, %26, %27, %28, %29, %30, %31, %32, %33, %34, %35, %36, %37, %38, %39, %40, %41, %42, %43, %44, %45, %46, %47, %48, %49, %50, %51, %52, %53, %54, %55, %56, %57, %58, %59, %60, %61, %62, %63, %64, %65, %66, %67, %68, %69, %70, %71}, %72, %73, p, 1, 1, 0, %75;\n}\n"
    : "+f"(d[0]), "+f"(d[1]), "+f"(d[2]), "+f"(d[3]), "+f"(d[4]), "+f"(d[5]), "+f"(d[6]), "+f"(d[7]), "+f"(d[8]), "+f"(d[9]), "+f"(d[10]), "+f"(d[11]), "+f"(d[12]), "+f"(d[13]), "+f"(d[14]), "+f"(d[15]), "+f"(d[16]), "+f"(d[17]), "+f"(d[18]), "+f"(d[19]), "+f"(d[20]), "+f"(d[21]), "+f"(d[22]), "+f"(d[23]), "+f"(d[24]), "+f"(d[25]), "+f"(d[26]), "+f"(d[27]), "+f"(d[28]), "+f"(d[29]), "+f"(d[30]), "+f"(d[31]), "+f"(d[32]), "+f"(d[33]), "+f"(d[34]), "+f"(d[35]), "+f"(d[36]), "+f"(d[37]), "+f"(d[38]), "+f"(d[39]), "+f"(d[40]), "+f"(d[41]), "+f"(d[42]), "+f"(d[43]), "+f"(d[44]), "+f"(d[45]), "+f"(d[46]), "+f"(d[47]), "+f"(d[48]), "+f"(d[49]), "+f"(d[50]), "+f"(d[51]), "+f"(d[52]), "+f"(d[53]), "+f"(d[54]), "+f"(d[55]), "+f"(d[56]), "+f"(d[57]), "+f"(d[58]), "+f"(d[59]), "+f"(d[60]), "+f"(d[61]), "+f"(d[62]), "+f"(d[63]), "+f"(d[64]), "+f"(d[65]), "+f"(d[66]), "+f"(d[67]), "+f"(d[68]), "+f"(d[69]), "+f"(d[70]), "+f"(d[71])
    : "l"(da), "l"(db), "r"(sc), "n"(TB));
}
template<int TB> __device__ __forceinline__ void wgmma_n192_rs(float (&d)[96], const uint32_t (&a)[4], uint64_t db, int sc) {
  asm volatile("{\n.reg .pred p;\nsetp.ne.b32 p, %101, 0;\n"
    "wgmma.mma_async.sync.aligned.m64n192k16.f32.bf16.bf16 {%0, %1, %2, %3, %4, %5, %6, %7, %8, %9, %10, %11, %12, %13, %14, %15, %16, %17, %18, %19, %20, %21, %22, %23, %24, %25, %26, %27, %28, %29, %30, %31, %32, %33, %34, %35, %36, %37, %38, %39, %40, %41, %42, %43, %44, %45, %46, %47, %48, %49, %50, %51, %52, %53, %54, %55, %56, %57, %58, %59, %60, %61, %62, %63, %64, %65, %66, %67, %68, %69, %70, %71, %72, %73, %74, %75, %76, %77, %78, %79, %80, %81, %82, %83, %84, %85, %86, %87, %88, %89, %90, %91, %92, %93, %94, %95}, {%96, %97, %98, %99}, %100, p, 1, 1, %102;\n}\n"
    : "+f"(d[0]), "+f"(d[1]), "+f"(d[2]), "+f"(d[3]), "+f"(d[4]), "+f"(d[5]), "+f"(d[6]), "+f"(d[7]), "+f"(d[8]), "+f"(d[9]), "+f"(d[10]), "+f"(d[11]), "+f"(d[12]), "+f"(d[13]), "+f"(d[14]), "+f"(d[15]), "+f"(d[16]), "+f"(d[17]), "+f"(d[18]), "+f"(d[19]), "+f"(d[20]), "+f"(d[21]), "+f"(d[22]), "+f"(d[23]), "+f"(d[24]), "+f"(d[25]), "+f"(d[26]), "+f"(d[27]), "+f"(d[28]), "+f"(d[29]), "+f"(d[30]), "+f"(d[31]), "+f"(d[32]), "+f"(d[33]), "+f"(d[34]), "+f"(d[35]), "+f"(d[36]), "+f"(d[37]), "+f"(d[38]), "+f"(d[39]), "+f"(d[40]), "+f"(d[41]), "+f"(d[42]), "+f"(d[43]), "+f"(d[44]), "+f"(d[45]), "+f"(d[46]), "+f"(d[47]), "+f"(d[48]), "+f"(d[49]), "+f"(d[50]), "+f"(d[51]), "+f"(d[52]), "+f"(d[53]), "+f"(d[54]), "+f"(d[55]), "+f"(d[56]), "+f"(d[57]), "+f"(d[58]), "+f"(d[59]), "+f"(d[60]), "+f"(d[61]), "+f"(d[62]), "+f"(d[63]), "+f"(d[64]), "+f"(d[65]), "+f"(d[66]), "+f"(d[67]), "+f"(d[68]), "+f"(d[69]), "+f"(d[70]), "+f"(d[71]), "+f"(d[72]), "+f"(d[73]), "+f"(d[74]), "+f"(d[75]), "+f"(d[76]), "+f"(d[77]), "+f"(d[78]), "+f"(d[79]), "+f"(d[80]), "+f"(d[81]), "+f"(d[82]), "+f"(d[83]), "+f"(d[84]), "+f"(d[85]), "+f"(d[86]), "+f"(d[87]), "+f"(d[88]), "+f"(d[89]), "+f"(d[90]), "+f"(d[91]), "+f"(d[92]), "+f"(d[93]), "+f"(d[94]), "+f"(d[95])
    : "r"(a[0]), "r"(a[1]), "r"(a[2]), "r"(a[3]), "l"(db), "r"(sc), "n"(TB));
}
template<int TB> __device__ __forceinline__ void wgmma_n64_rs(float (&d)[32], const uint32_t (&a)[4], uint64_t db, int sc) {
  asm volatile("{\n.reg .pred p;\nsetp.ne.b32 p, %37, 0;\n"
    "wgmma.mma_async.sync.aligned.m64n64k16.f32.bf16.bf16 {%0, %1, %2, %3, %4, %5, %6, %7, %8, %9, %10, %11, %12, %13, %14, %15, %16, %17, %18, %19, %20, %21, %22, %23, %24, %25, %26, %27, %28, %29, %30, %31}, {%32, %33, %34, %35}, %36, p, 1, 1, %38;\n}\n"
    : "+f"(d[0]), "+f"(d[1]), "+f"(d[2]), "+f"(d[3]), "+f"(d[4]), "+f"(d[5]), "+f"(d[6]), "+f"(d[7]), "+f"(d[8]), "+f"(d[9]), "+f"(d[10]), "+f"(d[11]), "+f"(d[12]), "+f"(d[13]), "+f"(d[14]), "+f"(d[15]), "+f"(d[16]), "+f"(d[17]), "+f"(d[18]), "+f"(d[19]), "+f"(d[20]), "+f"(d[21]), "+f"(d[22]), "+f"(d[23]), "+f"(d[24]), "+f"(d[25]), "+f"(d[26]), "+f"(d[27]), "+f"(d[28]), "+f"(d[29]), "+f"(d[30]), "+f"(d[31])
    : "r"(a[0]), "r"(a[1]), "r"(a[2]), "r"(a[3]), "l"(db), "r"(sc), "n"(TB));
}
template<int TB> __device__ __forceinline__ void wgmma_n64_ss(float (&d)[32], uint64_t da, uint64_t db, int sc) {
  asm volatile("{\n.reg .pred p;\nsetp.ne.b32 p, %34, 0;\n"
    "wgmma.mma_async.sync.aligned.m64n64k16.f32.bf16.bf16 {%0, %1, %2, %3, %4, %5, %6, %7, %8, %9, %10, %11, %12, %13, %14, %15, %16, %17, %18, %19, %20, %21, %22, %23, %24, %25, %26, %27, %28, %29, %30, %31}, %32, %33, p, 1, 1, 0, %35;\n}\n"
    : "+f"(d[0]), "+f"(d[1]), "+f"(d[2]), "+f"(d[3]), "+f"(d[4]), "+f"(d[5]), "+f"(d[6]), "+f"(d[7]), "+f"(d[8]), "+f"(d[9]), "+f"(d[10]), "+f"(d[11]), "+f"(d[12]), "+f"(d[13]), "+f"(d[14]), "+f"(d[15]), "+f"(d[16]), "+f"(d[17]), "+f"(d[18]), "+f"(d[19]), "+f"(d[20]), "+f"(d[21]), "+f"(d[22]), "+f"(d[23]), "+f"(d[24]), "+f"(d[25]), "+f"(d[26]), "+f"(d[27]), "+f"(d[28]), "+f"(d[29]), "+f"(d[30]), "+f"(d[31])
    : "l"(da), "l"(db), "r"(sc), "n"(TB));
}

struct FragAddr {
  uint32_t rowoff;
  uint32_t rx;
  uint32_t hi;
  __device__ __forceinline__ FragAddr(int warp_in_wg, int lane) {
    int row = 16 * warp_in_wg + (lane & 7) + ((lane >> 3) & 1) * 8;
    rowoff = row * 128;
    rx = row & 7;
    hi = lane >> 4;
  }
  __device__ __forceinline__ uint32_t at(uint32_t chunk_base, int kk4) const {
    return chunk_base + rowoff + ((((uint32_t)kk4 * 2 + hi) ^ rx) << 4);
  }
};

__device__ __forceinline__ void layernorm_frags(uint32_t (&f)[12][4]) {
  float s0[2] = {0.f, 0.f}, s1[2] = {0.f, 0.f}, q0[2] = {0.f, 0.f}, q1[2] = {0.f, 0.f};
#pragma unroll
  for (int k = 0; k < 12; k++) {
#pragma unroll
    for (int hf = 0; hf < 2; hf++) {
      const float a = bf_lo(f[k][2 * hf]), b = bf_hi(f[k][2 * hf]);
      const float c = bf_lo(f[k][2 * hf + 1]), d = bf_hi(f[k][2 * hf + 1]);
      s0[hf] += a + b; q0[hf] = fmaf(a, a, fmaf(b, b, q0[hf]));
      s1[hf] += c + d; q1[hf] = fmaf(c, c, fmaf(d, d, q1[hf]));
    }
  }
  float sa = s0[0] + s0[1], sb_ = s1[0] + s1[1], qa = q0[0] + q0[1], qb_ = q1[0] + q1[1];
  sa += __shfl_xor_sync(0xffffffffu, sa, 1); sb_ += __shfl_xor_sync(0xffffffffu, sb_, 1);
  qa += __shfl_xor_sync(0xffffffffu, qa, 1); qb_ += __shfl_xor_sync(0xffffffffu, qb_, 1);
  sa += __shfl_xor_sync(0xffffffffu, sa, 2); sb_ += __shfl_xor_sync(0xffffffffu, sb_, 2);
  qa += __shfl_xor_sync(0xffffffffu, qa, 2); qb_ += __shfl_xor_sync(0xffffffffu, qb_, 2);
  const float m0 = sa * (1.f / 192.f), m1 = sb_ * (1.f / 192.f);
  const float v0 = fmaxf(fmaf(-m0, m0, qa * (1.f / 192.f)), 0.f), v1 = fmaxf(fmaf(-m1, m1, qb_ * (1.f / 192.f)), 0.f);
  const float r0 = rsqrtf(v0 + 1e-5f), r1 = rsqrtf(v1 + 1e-5f);
  const float c0 = -m0 * r0, c1 = -m1 * r1;
#pragma unroll
  for (int k = 0; k < 12; k++) {
    f[k][0] = pack_bf16(fmaf(bf_lo(f[k][0]), r0, c0), fmaf(bf_hi(f[k][0]), r0, c0));
    f[k][2] = pack_bf16(fmaf(bf_lo(f[k][2]), r0, c0), fmaf(bf_hi(f[k][2]), r0, c0));
    f[k][1] = pack_bf16(fmaf(bf_lo(f[k][1]), r1, c1), fmaf(bf_hi(f[k][1]), r1, c1));
    f[k][3] = pack_bf16(fmaf(bf_lo(f[k][3]), r1, c1), fmaf(bf_hi(f[k][3]), r1, c1));
  }
}

#define XDELAY 800
constexpr int A_NST = 5;
constexpr int A_XS = 0;
constexpr int A_VB = 49152;
constexpr int A_W = 98304;
constexpr int A_BAR = A_W + A_NST * 24576;
constexpr int A_SMEM = A_BAR + 256 + 1024;
constexpr int A_FOLD = 36;

__device__ __forceinline__ void a_issue(float (&acc)[32], const uint32_t (&af)[12][4], uint32_t sb, int s) {
  const int st = s % A_NST;
  mbar_wait(sb + A_BAR + st * 8, (s / A_NST) & 1);
  const uint64_t wd = mk_desc_o(sb + A_W + st * 24576, 8192, 1024);
  wg_fence();
#pragma unroll
  for (int kk = 0; kk < 12; kk++) wgmma_n64_rs<1>(acc, af[kk], wd + kk * 128, kk > 0);
  wg_commit();
}
__device__ __forceinline__ void a_release(uint32_t sb, int s, int lane) {
  if (lane == 0) mbar_arrive(sb + A_BAR + 64 + (s % A_NST) * 8);
}
__device__ __forceinline__ void cvt_frags(uint32_t (*dst)[4], const float (&acc)[32]) {
#pragma unroll
  for (int k = 0; k < 4; k++) {
    dst[k][0] = pack_bf16(acc[8 * k + 0], acc[8 * k + 1]);
    dst[k][1] = pack_bf16(acc[8 * k + 2], acc[8 * k + 3]);
    dst[k][2] = pack_bf16(acc[8 * k + 4], acc[8 * k + 5]);
    dst[k][3] = pack_bf16(acc[8 * k + 6], acc[8 * k + 7]);
  }
}
__device__ __forceinline__ void store_chunk(const float (&acc)[32], uint32_t chunk_base, const FragAddr& fa) {
  uint32_t t[4][4];
  cvt_frags(t, acc);
#pragma unroll
  for (int k = 0; k < 4; k++) stsm_x4(fa.at(chunk_base, k), t[k]);
}
__device__ __forceinline__ void resid_chunk(uint32_t (*dst)[4], const float* acc, float s0, float s1, uint32_t chunk_base,
                                            const FragAddr& fa) {
#pragma unroll
  for (int k = 0; k < 4; k++) {
    uint32_t x[4];
    ldsm_x4(x, fa.at(chunk_base, k));
    uint32_t o[4];
    o[0] = pack_bf16(fmaf(acc[8 * k + 0], s0, bf_lo(x[0])), fmaf(acc[8 * k + 1], s0, bf_hi(x[0])));
    o[1] = pack_bf16(fmaf(acc[8 * k + 2], s1, bf_lo(x[1])), fmaf(acc[8 * k + 3], s1, bf_hi(x[1])));
    o[2] = pack_bf16(fmaf(acc[8 * k + 4], s0, bf_lo(x[2])), fmaf(acc[8 * k + 5], s0, bf_hi(x[2])));
    o[3] = pack_bf16(fmaf(acc[8 * k + 6], s1, bf_lo(x[3])), fmaf(acc[8 * k + 7], s1, bf_hi(x[3])));
    stsm_x4(fa.at(chunk_base, k), o);
    if (dst) { dst[k][0] = o[0]; dst[k][1] = o[1]; dst[k][2] = o[2]; dst[k][3] = o[3]; }
  }
}

__global__ void __launch_bounds__(384, 1)
kernelA(const __grid_constant__ CUtensorMap tm_x, const __grid_constant__ CUtensorMap tm_wq64t,
        const __grid_constant__ CUtensorMap tm_wot, const __grid_constant__ CUtensorMap tm_wq64s,
        const __grid_constant__ CUtensorMap tm_wos, const __grid_constant__ CUtensorMap tm_wf,
        const __grid_constant__ CUtensorMap tm_x1, const __grid_constant__ CUtensorMap tm_qkv) {
  extern __shared__ uint8_t smem_raw[];
  const uint32_t sb = (smem_u32(smem_raw) + 1023) & ~1023u;
  const int tid = threadIdx.x, warp = tid >> 5, lane = tid & 31;
  const bool is_fold = blockIdx.x < A_FOLD;
  const int blk = blockIdx.x - A_FOLD;
  if (tid == 256) {
    for (int i = 0; i < A_NST; i++) { mbar_init(sb + A_BAR + i * 8, 1); mbar_init(sb + A_BAR + 64 + i * 8, 8); }
    mbar_init(sb + A_BAR + 128, 1); mbar_init(sb + A_BAR + 136, 1);
    asm volatile("fence.mbarrier_init.release.cluster;" ::: "memory");
    if (!is_fold) {
      __nanosleep(XDELAY);
      for (int w = 0; w < 2; w++) {
        const uint32_t bar = sb + A_BAR + 128 + w * 8;
        mbar_expect_tx(bar, 3 * 63 * 128);
        for (int c = 0; c < 3; c++)
          tma_load_3d(sb + A_XS + w * 24576 + c * 8192, &tm_x, bar, c * 64, (blk * 2 + w) * 9, 0);
      }
    } else {
      const int mat = blockIdx.x / 9, rs = (blockIdx.x % 9) / 3, cs = blockIdx.x % 3;
      const CUtensorMap* mq = (mat < 2) ? &tm_wq64t : &tm_wq64s;
      const CUtensorMap* mo = (mat < 2) ? &tm_wot : &tm_wos;
      const uint32_t bar = sb + A_BAR + 128;
      mbar_expect_tx(bar, 2 * 24576);
      for (int c = 0; c < 3; c++) tma_load_2d(sb + c * 8192, mq, bar, ((mat & 1) ? 384 : 0) + c * 64, rs * 64);
      if (mat & 1) tma_load_2d(sb + 24576, mo, bar, cs * 64, 0);
      else for (int c = 0; c < 3; c++) tma_load_2d(sb + 24576 + c * 8192, mq, bar, 192 + c * 64, cs * 64);
    }
  }
  asm volatile("griddepcontrol.launch_dependents;" ::: "memory");
  if (blockIdx.x == 0 && tid < 128) g_flag[tid] = 0;
  if (!is_fold && tid < 48) {
    uint32_t a = sb + A_XS + (tid >> 3) * 8192 + 63 * 128 + (tid & 7) * 16;
    asm volatile("st.shared.v4.b32 [%0], {%1,%1,%1,%1};" ::"r"(a), "r"(0) : "memory");
  }
  __syncthreads();

  if (warp >= 8) {
    asm volatile("setmaxnreg.dec.sync.aligned.u32 24;");
    if (warp == 8 && lane == 0 && !is_fold) {
      for (int s = 0; s < 12; s++) {
        const int st = s % A_NST;
        const int g = s / 3;
        const int mat = (g == 0) ? 1 : (g == 1) ? 0 : g;
        if (s % 3 == 0) {
          uint32_t n = 0, v;
          do {
            asm volatile("ld.acquire.gpu.global.u32 %0, [%1];" : "=r"(v) : "l"(&g_wflag[mat]) : "memory");
          } while (v < 9u && ++n < (1u << 22));
          asm volatile("fence.proxy.async;" ::: "memory");
        }
        if (s >= A_NST) mbar_wait(sb + A_BAR + 64 + st * 8, ((s / A_NST) - 1) & 1);
        mbar_expect_tx(sb + A_BAR + st * 8, 24576);
        tma_load_2d(sb + A_W + st * 24576, &tm_wf, sb + A_BAR + st * 8, (mat & 1) * 192 + (s % 3) * 64, (mat >> 1) * 192);
      }
    }
    return;
  }

  asm volatile("setmaxnreg.inc.sync.aligned.u32 240;");
  const int wg = warp >> 2, wq = warp & 3;

  if (is_fold) {
    if (wg == 0) {
      const int mat = blockIdx.x / 9, rs = (blockIdx.x % 9) / 3, cs = blockIdx.x % 3;
      float d[32];
      mbar_wait(sb + A_BAR + 128, 0);
      const uint64_t ad = mk_desc_o(sb, 16, 1024);
      if (mat & 1) {
        const uint64_t bd = mk_desc_o(sb + 24576, 8192, 1024);
        wg_fence();
#pragma unroll
        for (int kk = 0; kk < 12; kk++) wgmma_n64_ss<1>(d, ad + (kk >> 2) * 512 + (kk & 3) * 2, bd + kk * 128, kk > 0);
        wg_commit();
      } else {
        const uint64_t bd = mk_desc_o(sb + 24576, 16, 1024);
        wg_fence();
#pragma unroll
        for (int kk = 0; kk < 12; kk++)
          wgmma_n64_ss<0>(d, ad + (kk >> 2) * 512 + (kk & 3) * 2, bd + (kk >> 2) * 512 + (kk & 3) * 2, kk > 0);
        wg_commit();
      }
      wg_wait<0>(); reg_fence(d);
      const int r0 = rs * 64 + wq * 16 + (lane >> 2);
      uint32_t* dst = reinterpret_cast<uint32_t*>(g_wf + ((size_t)(mat >> 1) * 192 + r0) * 384 + (mat & 1) * 192 + cs * 64 + (lane & 3) * 2);
#pragma unroll
      for (int j = 0; j < 8; j++) {
        dst[j * 4] = pack_bf16(d[4 * j], d[4 * j + 1]);
        dst[8 * 192 + j * 4] = pack_bf16(d[4 * j + 2], d[4 * j + 3]);
      }
      asm volatile("fence.proxy.async;" ::: "memory");
      named_bar(1, 128);
      if (tid == 0) { __threadfence(); atomicAdd(&g_wflag[mat], 1u); }
    }
    return;
  }

  const int n0 = (blk * 2 + wg) * 9;
  const FragAddr fa(wq, lane);
  const uint32_t xs = sb + A_XS + wg * 24576, vb = sb + A_VB + wg * 24576;
  const int barid = 1 + wg;
  const bool elected = (tid & 127) == 0;

  uint32_t h[12][4];
  TS(0, 0);
  mbar_wait(sb + A_BAR + 128 + wg * 8, 0);
  TS(0, 1);
#pragma unroll
  for (int k = 0; k < 12; k++) ldsm_x4(h[k], fa.at(xs + (k >> 2) * 8192, k & 3));
  layernorm_frags(h);
#pragma unroll
  for (int k = 0; k < 12; k++) stsm_x4(fa.at(xs + (k >> 2) * 8192, k & 3), h[k]);

  float acc0[32], acc1[32];
  uint32_t qf[12][4];
  TS(0, 2);
  a_issue(acc0, h, sb, 0);
  TS(0, 3);
  a_issue(acc1, h, sb, 1); wg_wait<1>(); reg_fence(acc0); a_release(sb, 0, lane); store_chunk(acc0, vb, fa);
  a_issue(acc0, h, sb, 2); wg_wait<1>(); reg_fence(acc1); a_release(sb, 1, lane); store_chunk(acc1, vb + 8192, fa);
  a_issue(acc1, h, sb, 3); wg_wait<1>(); reg_fence(acc0); a_release(sb, 2, lane); store_chunk(acc0, vb + 16384, fa);
  fence_proxy_async();
  named_bar(barid, 128);
  a_issue(acc0, h, sb, 4); wg_wait<1>(); reg_fence(acc1); a_release(sb, 3, lane); cvt_frags(&qf[0], acc1);
  a_issue(acc1, h, sb, 5); wg_wait<1>(); reg_fence(acc0); a_release(sb, 4, lane); cvt_frags(&qf[4], acc0);
  wg_wait<0>(); reg_fence(acc1); a_release(sb, 5, lane); cvt_frags(&qf[8], acc1);
  TS(0, 4);
  {
    const uint64_t kd = mk_desc_o(xs, 16, 1024);
    wg_fence();
#pragma unroll
    for (int kk = 0; kk < 12; kk++) wgmma_n64_rs<0>(acc0, qf[kk], kd + (kk >> 2) * 512 + (kk & 3) * 2, kk > 0);
    wg_commit();
    wg_wait<0>(); reg_fence(acc0);
  }
  named_bar(barid, 128);
  if (elected) {
    const uint32_t bar = sb + A_BAR + 128 + wg * 8;
    mbar_expect_tx(bar, 3 * 63 * 128);
    for (int c = 0; c < 3; c++) tma_load_3d(xs + c * 8192, &tm_x, bar, c * 64, n0, 0);
  }
  uint32_t pf[4][4];
  {
    const int r0 = 16 * wq + (lane >> 2), r1 = r0 + 8;
    const unsigned long long MB = 0x0040201008040201ull;
    const unsigned long long mk0 = (MB << (r0 % 9)) >> (2 * (lane & 3));
    const unsigned long long mk1 = (MB << (r1 % 9)) >> (2 * (lane & 3));
    const float cs = 0.07216878364870322f * 1.4426950408889634f;
    float mx0 = -INFINITY, mx1 = -INFINITY;
#pragma unroll
    for (int j = 0; j < 8; j++) {
#pragma unroll
      for (int e = 0; e < 2; e++) {
        bool v0 = (mk0 >> (8 * j + e)) & 1, v1 = (mk1 >> (8 * j + e)) & 1;
        acc0[4 * j + e] = v0 ? acc0[4 * j + e] * cs : -INFINITY;
        acc0[4 * j + 2 + e] = v1 ? acc0[4 * j + 2 + e] * cs : -INFINITY;
        mx0 = fmaxf(mx0, acc0[4 * j + e]);
        mx1 = fmaxf(mx1, acc0[4 * j + 2 + e]);
      }
    }
    mx0 = fmaxf(mx0, __shfl_xor_sync(0xffffffffu, mx0, 1)); mx0 = fmaxf(mx0, __shfl_xor_sync(0xffffffffu, mx0, 2));
    mx1 = fmaxf(mx1, __shfl_xor_sync(0xffffffffu, mx1, 1)); mx1 = fmaxf(mx1, __shfl_xor_sync(0xffffffffu, mx1, 2));
    float l0 = 0.f, l1 = 0.f;
#pragma unroll
    for (int j = 0; j < 8; j++) {
#pragma unroll
      for (int e = 0; e < 2; e++) {
        acc0[4 * j + e] = ex2(acc0[4 * j + e] - mx0); l0 += acc0[4 * j + e];
        acc0[4 * j + 2 + e] = ex2(acc0[4 * j + 2 + e] - mx1); l1 += acc0[4 * j + 2 + e];
      }
    }
    l0 += __shfl_xor_sync(0xffffffffu, l0, 1); l0 += __shfl_xor_sync(0xffffffffu, l0, 2);
    l1 += __shfl_xor_sync(0xffffffffu, l1, 1); l1 += __shfl_xor_sync(0xffffffffu, l1, 2);
    const float i0 = 1.f / l0, i1 = 1.f / l1;
#pragma unroll
    for (int j = 0; j < 8; j++) {
      acc0[4 * j] *= i0; acc0[4 * j + 1] *= i0; acc0[4 * j + 2] *= i1; acc0[4 * j + 3] *= i1;
    }
    cvt_frags(pf, acc0);
  }
  TS(0, 5);
  {
    float oacc[96];
    const uint64_t vd = mk_desc_o(vb, 8192, 1024);
    wg_fence();
#pragma unroll
    for (int kk = 0; kk < 4; kk++) wgmma_n192_rs<1>(oacc, pf[kk], vd + kk * 128, kk > 0);
    wg_commit();
    wg_wait<0>(); reg_fence(oacc);
    TS(0, 6);
    mbar_wait(sb + A_BAR + 128 + wg * 8, 1);
#pragma unroll
    for (int c = 0; c < 3; c++) resid_chunk(&h[4 * c], &oacc[32 * c], 1.f, 1.f, xs + c * 8192, fa);
  }
  TS(0, 7);
  fence_proxy_async();
  named_bar(barid, 128);
  if (elected) {
    for (int c = 0; c < 3; c++) tma_store_3d(&tm_x1, xs + c * 8192, c * 64, n0, 0);
    bulk_commit();
  }
  layernorm_frags(h);
#pragma unroll
  for (int k = 0; k < 12; k++) stsm_x4(fa.at(vb + (k >> 2) * 8192, k & 3), h[k]);
  TS(0, 8);
  a_issue(acc0, h, sb, 6);
  a_issue(acc1, h, sb, 7);
  fence_proxy_async();
  if (elected) bulk_wait_read0();
  named_bar(barid, 128);
  if (elected) {
    for (int c = 0; c < 3; c++) tma_store_3d(&tm_qkv, vb + c * 8192, 192 + c * 64, n0, 0);
    bulk_commit();
  }
  wg_wait<1>(); reg_fence(acc0); a_release(sb, 6, lane); store_chunk(acc0, xs, fa);
  a_issue(acc0, h, sb, 8); wg_wait<1>(); reg_fence(acc1); store_chunk(acc1, xs + 8192, fa);
  a_issue(acc1, h, sb, 9); wg_wait<1>(); reg_fence(acc0); store_chunk(acc0, xs + 16384, fa);
  a_issue(acc0, h, sb, 10);
  fence_proxy_async();
  if (elected) bulk_wait_read0();
  named_bar(barid, 128);
  if (elected) {
    for (int c = 0; c < 3; c++) tma_store_3d(&tm_qkv, xs + c * 8192, c * 64, n0, 0);
    bulk_commit();
  }
  {
    const int rr = wq * 16 + (lane >> 3);
    __nv_bfloat16* gdst = g_qkv + 384 + (lane & 7) * 8;
    auto flush = [&](uint32_t cb, int c) {
      __syncwarp();
#pragma unroll
      for (int i = 0; i < 4; i++) {
        const int r = rr + 4 * i;
        uint4 v;
        asm volatile("ld.shared.v4.b32 {%0,%1,%2,%3}, [%4];" : "=r"(v.x), "=r"(v.y), "=r"(v.z), "=r"(v.w)
                     : "r"(cb + r * 128 + (((lane & 7) ^ (r & 7)) << 4)) : "memory");
        const int t = r / 9, loc = r - t * 9;
        if (r < 63) *reinterpret_cast<uint4*>(gdst + ((size_t)t * NL + n0 + loc) * 576 + c * 64) = v;
      }
    };
    wg_wait<1>(); reg_fence(acc1); store_chunk(acc1, vb, fa);
    a_issue(acc1, h, sb, 11);
    flush(vb, 0);
    wg_wait<1>(); reg_fence(acc0); store_chunk(acc0, vb + 8192, fa);
    flush(vb + 8192, 1);
    wg_wait<0>(); reg_fence(acc1); store_chunk(acc1, vb + 16384, fa);
    flush(vb + 16384, 2);
  }
  TS(0, 9);
  if (elected) bulk_wait_read0();
  TS(0, 10);
}

constexpr int B_GRID = 132;
constexpr int B_SLOT = 55296;
constexpr int B_Q = 0;
constexpr int B_KV = 49152;
constexpr int B_BAR = B_KV + 3 * B_SLOT;
constexpr int B_SMEM = B_BAR + 256 + 1024;

__device__ __forceinline__ void bar_arrive(int id, int nthreads) {
  asm volatile("bar.arrive %0, %1;" ::"r"(id), "r"(nthreads) : "memory");
}
__device__ __forceinline__ void b_segment(int sg, int& tile, int& k0, int& k1) {
  const int grp = blockIdx.x / 12, ci = blockIdx.x - grp * 12;
  if (ci < 7) { tile = grp * 7 + ci; k0 = 3; k1 = 9; }
  else {
    const int hh = ci - 7;
    tile = grp * 7 + ((0x54210 >> (4 * hh)) & 15) + sg;
    k0 = sg ? 0 : ((0x10210 >> (4 * hh)) & 15);
    k1 = sg ? ((0x31321 >> (4 * hh)) & 15) : 3;
  }
}

__global__ void __launch_bounds__(384, 1)
kernelB(const __grid_constant__ CUtensorMap tm_q, const __grid_constant__ CUtensorMap tm_kv,
        const __grid_constant__ CUtensorMap tm_x1, const __grid_constant__ CUtensorMap tm_out) {
  extern __shared__ uint8_t smem_raw[];
  const uint32_t sb = (smem_u32(smem_raw) + 1023) & ~1023u;
  const int tid = threadIdx.x, warp = tid >> 5, lane = tid & 31;
  const uint32_t bF = sb + B_BAR, bE = sb + B_BAR + 32, bQF = sb + B_BAR + 64, bQE = sb + B_BAR + 72;
  if (tid == 0) {
    for (int i = 0; i < 3; i++) { mbar_init(bF + i * 8, 1); mbar_init(bE + i * 8, 8); }
    mbar_init(bQF, 1); mbar_init(bQE, 8);
    asm volatile("fence.mbarrier_init.release.cluster;" ::: "memory");
    prefetch_tmap(&tm_q); prefetch_tmap(&tm_kv); prefetch_tmap(&tm_x1); prefetch_tmap(&tm_out);
  }
  __syncthreads();
  asm volatile("griddepcontrol.wait;" ::: "memory");
  const int grp = blockIdx.x / 12, ci = blockIdx.x - grp * 12;
  const bool owner = ci < 7;
  const int nseg = owner ? 1 : 2;

  if (warp >= 8) {
    asm volatile("setmaxnreg.dec.sync.aligned.u32 24;");
    if (warp == 8 && lane == 0) {
      if (blockIdx.x == 0) { g_wflag[0] = 0; g_wflag[1] = 0; g_wflag[2] = 0; g_wflag[3] = 0; }
      int it = 0;
      for (int sg = 0; sg < nseg; sg++) {
        int tile, k0, k1;
        b_segment(sg, tile, k0, k1);
        const int t = tile / 11, qt = tile - t * 11;
        if (sg > 0) mbar_wait(bQE, 0);
        mbar_expect_tx(bQF, 49152);
        for (int c = 0; c < 3; c++) tma_load_3d(sb + B_Q + c * 16384, &tm_q, bQF, c * 64, qt * 128, t);
        const int n = k1 - k0;
        for (int e = 0; e < 2 * n; e++) {
          const int sl = it % 3;
          if (it >= 3) mbar_wait(bE + sl * 8, ((it / 3) - 1) & 1);
          mbar_expect_tx(bF + sl * 8, B_SLOT);
          for (int c = 0; c < 3; c++)
            tma_load_3d(sb + B_KV + sl * B_SLOT + c * 18432, &tm_kv, bF + sl * 8, 192 + (e & 1) * 192 + c * 64, (k0 + (e >> 1)) * 144, t);
          it++;
        }
      }
      if (owner) {
        const int tile = grp * 7 + ci;
        const int t = tile / 11, qt = tile - t * 11;
        mbar_wait(bQE, 0);
        mbar_expect_tx(bQF, 49152);
        for (int c = 0; c < 3; c++) tma_load_3d(sb + B_Q + c * 16384, &tm_x1, bQF, c * 64, qt * 128, t);
      }
    } else if ((warp == 9 || warp == 10) && !owner) {
      for (int sg = 0; sg < 2; sg++) {
        named_bar(5 + (warp - 9), 160);
        if (lane == 0) {
          __threadfence();
          atomicAdd(&g_flag[(grp * 5 + (ci - 7)) * 2 + sg], 1u);
        }
        __syncwarp();
      }
    }
    return;
  }

  asm volatile("setmaxnreg.inc.sync.aligned.u32 240;");
  const int wg = warp >> 2, wq = warp & 3;
  const int wtid = tid & 127;
  const float cs = 0.07216878364870322f * 1.4426950408889634f;
  float oacc[96], sacc[72];
  uint32_t pf[9][4];
  float m0, m1, l0, l1;
  int it = 0;
  const uint32_t qb = sb + B_Q + wg * 8192;
  if (wg == 1) bar_arrive(3, 256);
  TS(1, 0);
  int tsi = 1;

  auto issue_qk = [&](int slot) {
    const uint64_t kd = mk_desc_o(sb + B_KV + slot * B_SLOT, 16, 1024);
    const uint64_t qd = mk_desc_o(qb, 16, 1024);
#pragma unroll
    for (int kk = 0; kk < 12; kk++)
      wgmma_n144_ss<0>(sacc, qd + (kk >> 2) * 1024 + (kk & 3) * 2, kd + (kk >> 2) * 1152 + (kk & 3) * 2, kk > 0);
    wg_commit();
  };
  auto issue_pv = [&](int slot, int accum) {
    const uint64_t vd = mk_desc_o(sb + B_KV + slot * B_SLOT, 18432, 1024);
#pragma unroll
    for (int kk = 0; kk < 9; kk++) wgmma_n192_rs<1>(oacc, pf[kk], vd + kk * 128, kk > 0 ? 1 : accum);
    wg_commit();
  };
  auto softmax = [&](bool rescale) {
    float t0[4], t1[4];
#pragma unroll
    for (int q = 0; q < 4; q++) {
      t0[q] = fmaxf(sacc[4 * q], sacc[4 * q + 1]);
      t1[q] = fmaxf(sacc[4 * q + 2], sacc[4 * q + 3]);
    }
#pragma unroll
    for (int j = 4; j < 18; j++) {
      t0[j & 3] = fmaxf(t0[j & 3], fmaxf(sacc[4 * j], sacc[4 * j + 1]));
      t1[j & 3] = fmaxf(t1[j & 3], fmaxf(sacc[4 * j + 2], sacc[4 * j + 3]));
    }
    float mx0 = fmaxf(fmaxf(t0[0], t0[1]), fmaxf(fmaxf(t0[2], t0[3]), m0));
    float mx1 = fmaxf(fmaxf(t1[0], t1[1]), fmaxf(fmaxf(t1[2], t1[3]), m1));
    mx0 = fmaxf(mx0, __shfl_xor_sync(0xffffffffu, mx0, 1)); mx1 = fmaxf(mx1, __shfl_xor_sync(0xffffffffu, mx1, 1));
    mx0 = fmaxf(mx0, __shfl_xor_sync(0xffffffffu, mx0, 2)); mx1 = fmaxf(mx1, __shfl_xor_sync(0xffffffffu, mx1, 2));
    const float a0 = ex2((m0 - mx0) * cs), a1 = ex2((m1 - mx1) * cs);
    m0 = mx0; m1 = mx1;
    const float mc0 = mx0 * cs, mc1 = mx1 * cs;
#pragma unroll
    for (int q = 0; q < 4; q++) { t0[q] = 0.f; t1[q] = 0.f; }
#pragma unroll
    for (int k = 0; k < 9; k++) {
      float p[8];
#pragma unroll
      for (int e = 0; e < 8; e++) p[e] = ex2(fmaf(sacc[8 * k + e], cs, (e & 2) ? -mc1 : -mc0));
      t0[0] += p[0]; t0[1] += p[1]; t0[2] += p[4]; t0[3] += p[5];
      t1[0] += p[2]; t1[1] += p[3]; t1[2] += p[6]; t1[3] += p[7];
      pf[k][0] = pack_bf16(p[0], p[1]); pf[k][1] = pack_bf16(p[2], p[3]);
      pf[k][2] = pack_bf16(p[4], p[5]); pf[k][3] = pack_bf16(p[6], p[7]);
    }
    l0 = l0 * a0 + ((t0[0] + t0[1]) + (t0[2] + t0[3]));
    l1 = l1 * a1 + ((t1[0] + t1[1]) + (t1[2] + t1[3]));
    if (rescale) {
#pragma unroll
      for (int i = 0; i < 24; i++) {
        oacc[4 * i] *= a0; oacc[4 * i + 1] *= a0; oacc[4 * i + 2] *= a1; oacc[4 * i + 3] *= a1;
      }
    }
  };

  for (int sg = 0; sg < nseg; sg++) {
    int n;
    { int tile, k0, k1; b_segment(sg, tile, k0, k1); n = k1 - k0; }
    m0 = m1 = -INFINITY; l0 = l1 = 0.f;
    mbar_wait(bQF, sg & 1);
    {
      const int sl = it % 3;
      mbar_wait(bF + sl * 8, (it / 3) & 1);
      named_bar(3 + wg, 256);
      wg_fence();
      issue_qk(sl);
      bar_arrive(3 + (wg ^ 1), 256);
      wg_wait<0>(); reg_fence(sacc);
      if (lane == 0) { mbar_arrive(bE + sl * 8); if (n == 1) mbar_arrive(bQE); }
      it++;
      softmax(false);
    }
    TS(1, tsi); tsi++;
    for (int j = 1; j < n; j++) {
      const int slv = it % 3, slk = (it + 1) % 3;
      mbar_wait(bF + slv * 8, (it / 3) & 1);
      named_bar(3 + wg, 256);
      wg_fence();
      issue_pv(slv, j > 1);
      mbar_wait(bF + slk * 8, ((it + 1) / 3) & 1);
      issue_qk(slk);
      bar_arrive(3 + (wg ^ 1), 256);
      wg_wait<1>(); reg_fence(oacc);
      if (lane == 0) mbar_arrive(bE + slv * 8);
      wg_wait<0>(); reg_fence(sacc);
      if (lane == 0) { mbar_arrive(bE + slk * 8); if (j == n - 1) mbar_arrive(bQE); }
      it += 2;
      softmax(true);
      TS(1, tsi); tsi++;
    }
    {
      const int sl = it % 3;
      mbar_wait(bF + sl * 8, (it / 3) & 1);
      named_bar(3 + wg, 256);
      wg_fence();
      issue_pv(sl, n > 1);
      if (!(wg == 1 && sg == nseg - 1)) bar_arrive(3 + (wg ^ 1), 256);
      wg_wait<0>(); reg_fence(oacc);
      if (lane == 0) mbar_arrive(bE + sl * 8);
      it++;
    }
    TS(1, tsi); tsi++;
    if (!owner) {
      const int slot = (grp * 5 + (ci - 7)) * 2 + sg;
      uint4* dst = g_part + (size_t)(slot * 2 + wg) * 13 * 128 + wtid;
#pragma unroll
      for (int i = 0; i < 12; i++)
        dst[i * 128] = make_uint4(pack_bf16(oacc[8 * i], oacc[8 * i + 1]), pack_bf16(oacc[8 * i + 2], oacc[8 * i + 3]),
                                  pack_bf16(oacc[8 * i + 4], oacc[8 * i + 5]), pack_bf16(oacc[8 * i + 6], oacc[8 * i + 7]));
      dst[12 * 128] = make_uint4(__float_as_uint(m0), __float_as_uint(m1), __float_as_uint(l0), __float_as_uint(l1));
      bar_arrive(5 + wg, 160);
      TS(1, tsi); tsi++;
    }
  }
  if (!owner) return;

  {
    const int first = (0x9765310 >> (4 * ci)) & 15, cnt = (0x1211221 >> (4 * ci)) & 15;
    const int slot0 = grp * 10 + first;
    if (wtid < cnt) {
      uint32_t n = 0, v;
      do {
        asm volatile("ld.acquire.gpu.global.u32 %0, [%1];" : "=r"(v) : "l"(&g_flag[slot0 + wtid]) : "memory");
      } while (v < 2u && ++n < (1u << 22));
    }
    named_bar(1 + wg, 128);
    uint4 pv[2][13];
#pragma unroll
    for (int q = 0; q < 2; q++) {
      if (q < cnt) {
        const uint4* src = g_part + (size_t)((slot0 + q) * 2 + wg) * 13 * 128 + wtid;
#pragma unroll
        for (int i = 0; i < 13; i++) pv[q][i] = __ldcg(src + i * 128);
      }
    }
#pragma unroll
    for (int q = 0; q < 2; q++) {
      if (q < cnt) {
        const float pm0 = __uint_as_float(pv[q][12].x), pm1 = __uint_as_float(pv[q][12].y);
        const float mx0 = fmaxf(m0, pm0), mx1 = fmaxf(m1, pm1);
        const float a0 = ex2((m0 - mx0) * cs), a1 = ex2((m1 - mx1) * cs);
        const float b0 = ex2((pm0 - mx0) * cs), b1 = ex2((pm1 - mx1) * cs);
        m0 = mx0; m1 = mx1;
        l0 = l0 * a0 + __uint_as_float(pv[q][12].z) * b0; l1 = l1 * a1 + __uint_as_float(pv[q][12].w) * b1;
#pragma unroll
        for (int i = 0; i < 12; i++) {
          const uint4 v = pv[q][i];
          oacc[8 * i + 0] = oacc[8 * i + 0] * a0 + bf_lo(v.x) * b0; oacc[8 * i + 1] = oacc[8 * i + 1] * a0 + bf_hi(v.x) * b0;
          oacc[8 * i + 2] = oacc[8 * i + 2] * a1 + bf_lo(v.y) * b1; oacc[8 * i + 3] = oacc[8 * i + 3] * a1 + bf_hi(v.y) * b1;
          oacc[8 * i + 4] = oacc[8 * i + 4] * a0 + bf_lo(v.z) * b0; oacc[8 * i + 5] = oacc[8 * i + 5] * a0 + bf_hi(v.z) * b0;
          oacc[8 * i + 6] = oacc[8 * i + 6] * a1 + bf_lo(v.w) * b1; oacc[8 * i + 7] = oacc[8 * i + 7] * a1 + bf_hi(v.w) * b1;
        }
      }
    }
  }
  TS(1, 21);
  l0 += __shfl_xor_sync(0xffffffffu, l0, 1); l0 += __shfl_xor_sync(0xffffffffu, l0, 2);
  l1 += __shfl_xor_sync(0xffffffffu, l1, 1); l1 += __shfl_xor_sync(0xffffffffu, l1, 2);
  const float i0 = 1.f / l0, i1 = 1.f / l1;
  mbar_wait(bQF, 1);
  const FragAddr fa(wq, lane);
#pragma unroll
  for (int c = 0; c < 3; c++) resid_chunk(nullptr, &oacc[32 * c], i0, i1, qb + c * 16384, fa);
  fence_proxy_async();
  named_bar(1 + wg, 128);
  TS(1, 22);
  if (wtid == 0) {
    const int tile = grp * 7 + ci;
    const int t = tile / 11, qt = tile - t * 11;
    if (qt * 128 + wg * 64 < NL) {
      for (int c = 0; c < 3; c++) tma_store_3d(&tm_out, qb + c * 16384, c * 64, qt * 128 + wg * 64, t);
      bulk_commit();
      bulk_wait_read0();
    }
  }
  TS(1, 23);
}

typedef CUresult (*EncodeFn)(CUtensorMap*, CUtensorMapDataType, cuuint32_t, void*, const cuuint64_t*, const cuuint64_t*,
                             const cuuint32_t*, const cuuint32_t*, CUtensorMapInterleave, CUtensorMapSwizzle,
                             CUtensorMapL2promotion, CUtensorMapFloatOOBfill);

void make_map(EncodeFn enc, CUtensorMap* m, const void* ptr, int rank, const uint64_t* dims, const uint32_t* box) {
  cuuint64_t gd[3], gs[2];
  cuuint32_t bx[3], es[3] = {1, 1, 1};
  uint64_t stride = 2;
  for (int i = 0; i < rank; i++) {
    gd[i] = dims[i]; bx[i] = box[i];
    stride *= dims[i];
    if (i < rank - 1) gs[i] = stride;
  }
  enc(m, CU_TENSOR_MAP_DATA_TYPE_BFLOAT16, rank, const_cast<void*>(ptr), gd, gs, bx, es, CU_TENSOR_MAP_INTERLEAVE_NONE,
      CU_TENSOR_MAP_SWIZZLE_128B, CU_TENSOR_MAP_L2_PROMOTION_L2_256B, CU_TENSOR_MAP_FLOAT_OOB_FILL_NONE);
}

}

extern "C" void kernel_launch(void* const* d_in, const int* in_sizes, int n_in, void* d_out, int out_size) {
  (void)in_sizes; (void)n_in; (void)out_size;
  EncodeFn enc = nullptr;
  cudaDriverEntryPointQueryResult qres;
  cudaGetDriverEntryPoint("cuTensorMapEncodeTiled", (void**)&enc, cudaEnableDefault, &qres);
  void *p_x1, *p_qkv, *p_wf;
  cudaGetSymbolAddress(&p_wf, g_wf);
  cudaGetSymbolAddress(&p_x1, g_x1);
  cudaGetSymbolAddress(&p_qkv, g_qkv);
  cudaFuncSetAttribute(kernelA, cudaFuncAttributeMaxDynamicSharedMemorySize, A_SMEM);
  cudaFuncSetAttribute(kernelB, cudaFuncAttributeMaxDynamicSharedMemorySize, B_SMEM);

  CUtensorMap tm_x, tm_wqkvt, tm_wot, tm_wqkvs, tm_x1s, tm_qkvs, tm_q, tm_kv, tm_wos, tm_x1l, tm_out, tm_wf;
  const uint64_t d_act[3] = {192, 1296, 7}, d_qkv[3] = {576, 1296, 7}, d_w3[2] = {576, 192}, d_w1[2] = {192, 192}, d_wf[2] = {384, 384};
  const uint32_t b_a[3] = {64, 9, 7}, b_w[2] = {64, 192}, b_q[3] = {64, 128, 1}, b_kv[3] = {64, 144, 1}, b_o[3] = {64, 64, 1}, b_w64[2] = {64, 64};
  make_map(enc, &tm_x, d_in[0], 3, d_act, b_a);
  make_map(enc, &tm_wqkvt, d_in[1], 2, d_w3, b_w64);
  make_map(enc, &tm_wot, d_in[2], 2, d_w1, b_w);
  make_map(enc, &tm_wqkvs, d_in[3], 2, d_w3, b_w64);
  make_map(enc, &tm_wos, d_in[4], 2, d_w1, b_w);
  make_map(enc, &tm_wf, p_wf, 2, d_wf, b_w);
  make_map(enc, &tm_x1s, p_x1, 3, d_act, b_a);
  make_map(enc, &tm_qkvs, p_qkv, 3, d_qkv, b_a);
  make_map(enc, &tm_q, p_qkv, 3, d_qkv, b_q);
  make_map(enc, &tm_kv, p_qkv, 3, d_qkv, b_kv);
  make_map(enc, &tm_x1l, p_x1, 3, d_act, b_q);
  make_map(enc, &tm_out, d_out, 3, d_act, b_o);

  kernelA<<<72 + A_FOLD, 384, A_SMEM, cudaStreamPerThread>>>(tm_x, tm_wqkvt, tm_wot, tm_wqkvs, tm_wos, tm_wf, tm_x1s, tm_qkvs);
  cudaLaunchConfig_t cfg = {};
  cfg.gridDim = dim3(B_GRID); cfg.blockDim = dim3(384); cfg.dynamicSmemBytes = B_SMEM; cfg.stream = cudaStreamPerThread;
  cudaLaunchAttribute at[1];
  at[0].id = cudaLaunchAttributeProgrammaticStreamSerialization;
  at[0].val.programmaticStreamSerializationAllowed = 1;
  cfg.attrs = at; cfg.numAttrs = 1;
  cudaLaunchKernelEx(&cfg, kernelB, tm_q, tm_kv, tm_x1l, tm_out);
}
```

```cpp
#include <cuda_runtime.h>
#include <cuda_bf16.h>
#include <cuda.h>
#include <stdint.h>

namespace {

constexpr int TT = 7, NL = 1296, CC = 192;

__device__ __align__(1024) __nv_bfloat16 g_x1[TT * NL * CC];
__device__ __align__(1024) __nv_bfloat16 g_qkv[TT * NL * 3 * CC];
__device__ __align__(1024) __nv_bfloat16 g_wf[2 * CC * 2 * CC];
__device__ __align__(1024) uint4 g_part[121 * 2 * 13 * 128];
__device__ unsigned int g_flag[128];
__device__ unsigned int g_wflag[4];

#define TS(k, i)

__device__ __forceinline__ uint32_t smem_u32(const void* p) { return (uint32_t)__cvta_generic_to_shared(p); }
__device__ __forceinline__ void mbar_init(uint32_t bar, uint32_t cnt) {
  asm volatile("mbarrier.init.shared::cta.b64 [%0], %1;" ::"r"(bar), "r"(cnt));
}
__device__ __forceinline__ void mbar_expect_tx(uint32_t bar, uint32_t bytes) {
  asm volatile("mbarrier.arrive.expect_tx.shared::cta.b64 _, [%0], %1;" ::"r"(bar), "r"(bytes) : "memory");
}
__device__ __forceinline__ void mbar_arrive(uint32_t bar) {
  asm volatile("mbarrier.arrive.shared::cta.b64 _, [%0];" ::"r"(bar) : "memory");
}
__device__ __forceinline__ bool mbar_try(uint32_t bar, uint32_t parity) {
  uint32_t ok;
  asm volatile("{\n.reg .pred p;\nmbarrier.try_wait.parity.shared::cta.b64 p, [%1], %2;\nselp.u32 %0, 1, 0, p;\n}"
               : "=r"(ok) : "r"(bar), "r"(parity) : "memory");
  return ok != 0;
}
__device__ __forceinline__ void mbar_wait(uint32_t bar, uint32_t parity) {
  if (mbar_try(bar, parity)) return;
  uint32_t n = 0;
  while (!mbar_try(bar, parity)) {
    if (++n > (1u << 22)) break;
  }
}
__device__ __forceinline__ void tma_load_2d(uint32_t dst, const CUtensorMap* m, uint32_t bar, int c0, int c1) {
  asm volatile("cp.async.bulk.tensor.2d.shared::cluster.global.mbarrier::complete_tx::bytes [%0], [%1, {%3, %4}], [%2];"
               ::"r"(dst), "l"(m), "r"(bar), "r"(c0), "r"(c1) : "memory");
}
__device__ __forceinline__ void tma_load_3d(uint32_t dst, const CUtensorMap* m, uint32_t bar, int c0, int c1, int c2) {
  asm volatile("cp.async.bulk.tensor.3d.shared::cluster.global.mbarrier::complete_tx::bytes [%0], [%1, {%3, %4, %5}], [%2];"
               ::"r"(dst), "l"(m), "r"(bar), "r"(c0), "r"(c1), "r"(c2) : "memory");
}
__device__ __forceinline__ void tma_store_3d(const CUtensorMap* m, uint32_t src, int c0, int c1, int c2) {
  asm volatile("cp.async.bulk.tensor.3d.global.shared::cta.bulk_group [%0, {%2, %3, %4}], [%1];"
               ::"l"(m), "r"(src), "r"(c0), "r"(c1), "r"(c2) : "memory");
}
__device__ __forceinline__ void bulk_commit() { asm volatile("cp.async.bulk.commit_group;" ::: "memory"); }
__device__ __forceinline__ void bulk_wait_read0() { asm volatile("cp.async.bulk.wait_group.read 0;" ::: "memory"); }
__device__ __forceinline__ void bulk_wait_read1() { asm volatile("cp.async.bulk.wait_group.read 1;" ::: "memory"); }
__device__ __forceinline__ void bulk_wait0() { asm volatile("cp.async.bulk.wait_group 0;" ::: "memory"); }
__device__ __forceinline__ void fence_proxy_async() { asm volatile("fence.proxy.async.shared::cta;" ::: "memory"); }
__device__ __forceinline__ void prefetch_tmap(const CUtensorMap* m) {
  asm volatile("prefetch.tensormap [%0];" ::"l"(m) : "memory");
}
__device__ __forceinline__ void wg_fence() { asm volatile("wgmma.fence.sync.aligned;" ::: "memory"); }
__device__ __forceinline__ void wg_commit() { asm volatile("wgmma.commit_group.sync.aligned;" ::: "memory"); }
template <int N> __device__ __forceinline__ void wg_wait() { asm volatile("wgmma.wait_group.sync.aligned %0;" ::"n"(N) : "memory"); }
__device__ __forceinline__ void named_bar(int id, int nthreads) {
  asm volatile("bar.sync %0, %1;" ::"r"(id), "r"(nthreads) : "memory");
}
__device__ __forceinline__ void ldsm_x4(uint32_t (&r)[4], uint32_t addr) {
  asm volatile("ldmatrix.sync.aligned.m8n8.x4.shared.b16 {%0,%1,%2,%3}, [%4];"
               : "=r"(r[0]), "=r"(r[1]), "=r"(r[2]), "=r"(r[3]) : "r"(addr) : "memory");
}
__device__ __forceinline__ void stsm_x4(uint32_t addr, const uint32_t (&r)[4]) {
  asm volatile("stmatrix.sync.aligned.m8n8.x4.shared.b16 [%0], {%1,%2,%3,%4};"
               ::"r"(addr), "r"(r[0]), "r"(r[1]), "r"(r[2]), "r"(r[3]) : "memory");
}
__device__ __forceinline__ uint32_t pack_bf16(float lo, float hi) {
  uint32_t r;
  asm("cvt.rn.bf16x2.f32 %0, %1, %2;" : "=r"(r) : "f"(hi), "f"(lo));
  return r;
}
__device__ __forceinline__ float bf_lo(uint32_t v) { return __uint_as_float(v << 16); }
__device__ __forceinline__ float bf_hi(uint32_t v) { return __uint_as_float(v & 0xffff0000u); }
__device__ __forceinline__ float ex2(float x) {
  float y;
  asm("ex2.approx.ftz.f32 %0, %1;" : "=f"(y) : "f"(x));
  return y;
}
__device__ __forceinline__ uint64_t mk_desc(uint32_t addr, uint32_t lbo, uint32_t sbo) {
  return (uint64_t)((addr & 0x3FFFF) >> 4) | ((uint64_t)((lbo & 0x3FFFF) >> 4) << 16) |
         ((uint64_t)((sbo & 0x3FFFF) >> 4) << 32) | (1ull << 62);
}
__device__ __forceinline__ uint64_t mk_desc_o(uint32_t addr, uint32_t lbo, uint32_t sbo) {
  asm volatile("" : "+r"(addr));
  return mk_desc(addr, lbo, sbo);
}
template <int N> __device__ __forceinline__ void reg_fence(uint32_t (&d)[N]) {
#pragma unroll
  for (int i = 0; i < N; i++) asm volatile("" : "+r"(d[i])::"memory");
}
template <int N> __device__ __forceinline__ void reg_fence(float (&d)[N]) {
#pragma unroll
  for (int i = 0; i < N; i++) asm volatile("" : "+f"(d[i])::"memory");
}

template<int TB> __device__ __forceinline__ void wgmma_n192_rs(float (&d)[96], const uint32_t (&a)[4], uint64_t db, int sc) {
  asm volatile("{\n.reg .pred p;\nsetp.ne.b32 p, %101, 0;\n"
    "wgmma.mma_async.sync.aligned.m64n192k16.f32.bf16.bf16 {%0, %1, %2, %3, %4, %5, %6, %7, %8, %9, %10, %11, %12, %13, %14, %15, %16, %17, %18, %19, %20, %21, %22, %23, %24, %25, %26, %27, %28, %29, %30, %31, %32, %33, %34, %35, %36, %37, %38, %39, %40, %41, %42, %43, %44, %45, %46, %47, %48, %49, %50, %51, %52, %53, %54, %55, %56, %57, %58, %59, %60, %61, %62, %63, %64, %65, %66, %67, %68, %69, %70, %71, %72, %73, %74, %75, %76, %77, %78, %79, %80, %81, %82, %83, %84, %85, %86, %87, %88, %89, %90, %91, %92, %93, %94, %95}, {%96, %97, %98, %99}, %100, p, 1, 1, %102;\n}\n"
    : "+f"(d[0]), "+f"(d[1]), "+f"(d[2]), "+f"(d[3]), "+f"(d[4]), "+f"(d[5]), "+f"(d[6]), "+f"(d[7]), "+f"(d[8]), "+f"(d[9]), "+f"(d[10]), "+f"(d[11]), "+f"(d[12]), "+f"(d[13]), "+f"(d[14]), "+f"(d[15]), "+f"(d[16]), "+f"(d[17]), "+f"(d[18]), "+f"(d[19]), "+f"(d[20]), "+f"(d[21]), "+f"(d[22]), "+f"(d[23]), "+f"(d[24]), "+f"(d[25]), "+f"(d[26]), "+f"(d[27]), "+f"(d[28]), "+f"(d[29]), "+f"(d[30]), "+f"(d[31]), "+f"(d[32]), "+f"(d[33]), "+f"(d[34]), "+f"(d[35]), "+f"(d[36]), "+f"(d[37]), "+f"(d[38]), "+f"(d[39]), "+f"(d[40]), "+f"(d[41]), "+f"(d[42]), "+f"(d[43]), "+f"(d[44]), "+f"(d[45]), "+f"(d[46]), "+f"(d[47]), "+f"(d[48]), "+f"(d[49]), "+f"(d[50]), "+f"(d[51]), "+f"(d[52]), "+f"(d[53]), "+f"(d[54]), "+f"(d[55]), "+f"(d[56]), "+f"(d[57]), "+f"(d[58]), "+f"(d[59]), "+f"(d[60]), "+f"(d[61]), "+f"(d[62]), "+f"(d[63]), "+f"(d[64]), "+f"(d[65]), "+f"(d[66]), "+f"(d[67]), "+f"(d[68]), "+f"(d[69]), "+f"(d[70]), "+f"(d[71]), "+f"(d[72]), "+f"(d[73]), "+f"(d[74]), "+f"(d[75]), "+f"(d[76]), "+f"(d[77]), "+f"(d[78]), "+f"(d[79]), "+f"(d[80]), "+f"(d[81]), "+f"(d[82]), "+f"(d[83]), "+f"(d[84]), "+f"(d[85]), "+f"(d[86]), "+f"(d[87]), "+f"(d[88]), "+f"(d[89]), "+f"(d[90]), "+f"(d[91]), "+f"(d[92]), "+f"(d[93]), "+f"(d[94]), "+f"(d[95])
    : "r"(a[0]), "r"(a[1]), "r"(a[2]), "r"(a[3]), "l"(db), "r"(sc), "n"(TB));
}
template<int TB> __device__ __forceinline__ void wgmma_n64_rs(float (&d)[32], const uint32_t (&a)[4], uint64_t db, int sc) {
  asm volatile("{\n.reg .pred p;\nsetp.ne.b32 p, %37, 0;\n"
    "wgmma.mma_async.sync.aligned.m64n64k16.f32.bf16.bf16 {%0, %1, %2, %3, %4, %5, %6, %7, %8, %9, %10, %11, %12, %13, %14, %15, %16, %17, %18, %19, %20, %21, %22, %23, %24, %25, %26, %27, %28, %29, %30, %31}, {%32, %33, %34, %35}, %36, p, 1, 1, %38;\n}\n"
    : "+f"(d[0]), "+f"(d[1]), "+f"(d[2]), "+f"(d[3]), "+f"(d[4]), "+f"(d[5]), "+f"(d[6]), "+f"(d[7]), "+f"(d[8]), "+f"(d[9]), "+f"(d[10]), "+f"(d[11]), "+f"(d[12]), "+f"(d[13]), "+f"(d[14]), "+f"(d[15]), "+f"(d[16]), "+f"(d[17]), "+f"(d[18]), "+f"(d[19]), "+f"(d[20]), "+f"(d[21]), "+f"(d[22]), "+f"(d[23]), "+f"(d[24]), "+f"(d[25]), "+f"(d[26]), "+f"(d[27]), "+f"(d[28]), "+f"(d[29]), "+f"(d[30]), "+f"(d[31])
    : "r"(a[0]), "r"(a[1]), "r"(a[2]), "r"(a[3]), "l"(db), "r"(sc), "n"(TB));
}
template<int TB> __device__ __forceinline__ void wgmma_n64_ss(float (&d)[32], uint64_t da, uint64_t db, int sc) {
  asm volatile("{\n.reg .pred p;\nsetp.ne.b32 p, %34, 0;\n"
    "wgmma.mma_async.sync.aligned.m64n64k16.f32.bf16.bf16 {%0, %1, %2, %3, %4, %5, %6, %7, %8, %9, %10, %11, %12, %13, %14, %15, %16, %17, %18, %19, %20, %21, %22, %23, %24, %25, %26, %27, %28, %29, %30, %31}, %32, %33, p, 1, 1, 0, %35;\n}\n"
    : "+f"(d[0]), "+f"(d[1]), "+f"(d[2]), "+f"(d[3]), "+f"(d[4]), "+f"(d[5]), "+f"(d[6]), "+f"(d[7]), "+f"(d[8]), "+f"(d[9]), "+f"(d[10]), "+f"(d[11]), "+f"(d[12]), "+f"(d[13]), "+f"(d[14]), "+f"(d[15]), "+f"(d[16]), "+f"(d[17]), "+f"(d[18]), "+f"(d[19]), "+f"(d[20]), "+f"(d[21]), "+f"(d[22]), "+f"(d[23]), "+f"(d[24]), "+f"(d[25]), "+f"(d[26]), "+f"(d[27]), "+f"(d[28]), "+f"(d[29]), "+f"(d[30]), "+f"(d[31])
    : "l"(da), "l"(db), "r"(sc), "n"(TB));
}
template<int TB> __device__ __forceinline__ void wgmma_n96_rs(float (&d)[48], const uint32_t (&a)[4], uint64_t db, int sc) {
  asm volatile("{\n.reg .pred p;\nsetp.ne.b32 p, %53, 0;\n"
    "wgmma.mma_async.sync.aligned.m64n96k16.f32.bf16.bf16 {%0, %1, %2, %3, %4, %5, %6, %7, %8, %9, %10, %11, %12, %13, %14, %15, %16, %17, %18, %19, %20, %21, %22, %23, %24, %25, %26, %27, %28, %29, %30, %31, %32, %33, %34, %35, %36, %37, %38, %39, %40, %41, %42, %43, %44, %45, %46, %47}, {%48, %49, %50, %51}, %52, p, 1, 1, %54;\n}\n"
    : "+f"(d[0]), "+f"(d[1]), "+f"(d[2]), "+f"(d[3]), "+f"(d[4]), "+f"(d[5]), "+f"(d[6]), "+f"(d[7]), "+f"(d[8]), "+f"(d[9]), "+f"(d[10]), "+f"(d[11]), "+f"(d[12]), "+f"(d[13]), "+f"(d[14]), "+f"(d[15]), "+f"(d[16]), "+f"(d[17]), "+f"(d[18]), "+f"(d[19]), "+f"(d[20]), "+f"(d[21]), "+f"(d[22]), "+f"(d[23]), "+f"(d[24]), "+f"(d[25]), "+f"(d[26]), "+f"(d[27]), "+f"(d[28]), "+f"(d[29]), "+f"(d[30]), "+f"(d[31]), "+f"(d[32]), "+f"(d[33]), "+f"(d[34]), "+f"(d[35]), "+f"(d[36]), "+f"(d[37]), "+f"(d[38]), "+f"(d[39]), "+f"(d[40]), "+f"(d[41]), "+f"(d[42]), "+f"(d[43]), "+f"(d[44]), "+f"(d[45]), "+f"(d[46]), "+f"(d[47])
    : "r"(a[0]), "r"(a[1]), "r"(a[2]), "r"(a[3]), "l"(db), "r"(sc), "n"(TB));
}
template<int TB> __device__ __forceinline__ void wgmma_n96_ss(float (&d)[48], uint64_t da, uint64_t db, int sc) {
  asm volatile("{\n.reg .pred p;\nsetp.ne.b32 p, %50, 0;\n"
    "wgmma.mma_async.sync.aligned.m64n96k16.f32.bf16.bf16 {%0, %1, %2, %3, %4, %5, %6, %7, %8, %9, %10, %11, %12, %13, %14, %15, %16, %17, %18, %19, %20, %21, %22, %23, %24, %25, %26, %27, %28, %29, %30, %31, %32, %33, %34, %35, %36, %37, %38, %39, %40, %41, %42, %43, %44, %45, %46, %47}, %48, %49, p, 1, 1, 0, %51;\n}\n"
    : "+f"(d[0]), "+f"(d[1]), "+f"(d[2]), "+f"(d[3]), "+f"(d[4]), "+f"(d[5]), "+f"(d[6]), "+f"(d[7]), "+f"(d[8]), "+f"(d[9]), "+f"(d[10]), "+f"(d[11]), "+f"(d[12]), "+f"(d[13]), "+f"(d[14]), "+f"(d[15]), "+f"(d[16]), "+f"(d[17]), "+f"(d[18]), "+f"(d[19]), "+f"(d[20]), "+f"(d[21]), "+f"(d[22]), "+f"(d[23]), "+f"(d[24]), "+f"(d[25]), "+f"(d[26]), "+f"(d[27]), "+f"(d[28]), "+f"(d[29]), "+f"(d[30]), "+f"(d[31]), "+f"(d[32]), "+f"(d[33]), "+f"(d[34]), "+f"(d[35]), "+f"(d[36]), "+f"(d[37]), "+f"(d[38]), "+f"(d[39]), "+f"(d[40]), "+f"(d[41]), "+f"(d[42]), "+f"(d[43]), "+f"(d[44]), "+f"(d[45]), "+f"(d[46]), "+f"(d[47])
    : "l"(da), "l"(db), "r"(sc), "n"(TB));
}

struct FragAddr {
  uint32_t rowoff;
  uint32_t rx;
  uint32_t hi;
  __device__ __forceinline__ FragAddr(int warp_in_wg, int lane) {
    int row = 16 * warp_in_wg + (lane & 7) + ((lane >> 3) & 1) * 8;
    rowoff = row * 128;
    rx = row & 7;
    hi = lane >> 4;
  }
  __device__ __forceinline__ uint32_t at(uint32_t chunk_base, int kk4) const {
    return chunk_base + rowoff + ((((uint32_t)kk4 * 2 + hi) ^ rx) << 4);
  }
};

__device__ __forceinline__ void layernorm_frags(uint32_t (&f)[12][4]) {
  float s0[2] = {0.f, 0.f}, s1[2] = {0.f, 0.f}, q0[2] = {0.f, 0.f}, q1[2] = {0.f, 0.f};
#pragma unroll
  for (int k = 0; k < 12; k++) {
#pragma unroll
    for (int hf = 0; hf < 2; hf++) {
      const float a = bf_lo(f[k][2 * hf]), b = bf_hi(f[k][2 * hf]);
      const float c = bf_lo(f[k][2 * hf + 1]), d = bf_hi(f[k][2 * hf + 1]);
      s0[hf] += a + b; q0[hf] = fmaf(a, a, fmaf(b, b, q0[hf]));
      s1[hf] += c + d; q1[hf] = fmaf(c, c, fmaf(d, d, q1[hf]));
    }
  }
  float sa = s0[0] + s0[1], sb_ = s1[0] + s1[1], qa = q0[0] + q0[1], qb_ = q1[0] + q1[1];
  sa += __shfl_xor_sync(0xffffffffu, sa, 1); sb_ += __shfl_xor_sync(0xffffffffu, sb_, 1);
  qa += __shfl_xor_sync(0xffffffffu, qa, 1); qb_ += __shfl_xor_sync(0xffffffffu, qb_, 1);
  sa += __shfl_xor_sync(0xffffffffu, sa, 2); sb_ += __shfl_xor_sync(0xffffffffu, sb_, 2);
  qa += __shfl_xor_sync(0xffffffffu, qa, 2); qb_ += __shfl_xor_sync(0xffffffffu, qb_, 2);
  const float m0 = sa * (1.f / 192.f), m1 = sb_ * (1.f / 192.f);
  const float v0 = fmaxf(fmaf(-m0, m0, qa * (1.f / 192.f)), 0.f), v1 = fmaxf(fmaf(-m1, m1, qb_ * (1.f / 192.f)), 0.f);
  const float r0 = rsqrtf(v0 + 1e-5f), r1 = rsqrtf(v1 + 1e-5f);
  const float c0 = -m0 * r0, c1 = -m1 * r1;
#pragma unroll
  for (int k = 0; k < 12; k++) {
    f[k][0] = pack_bf16(fmaf(bf_lo(f[k][0]), r0, c0), fmaf(bf_hi(f[k][0]), r0, c0));
    f[k][2] = pack_bf16(fmaf(bf_lo(f[k][2]), r0, c0), fmaf(bf_hi(f[k][2]), r0, c0));
    f[k][1] = pack_bf16(fmaf(bf_lo(f[k][1]), r1, c1), fmaf(bf_hi(f[k][1]), r1, c1));
    f[k][3] = pack_bf16(fmaf(bf_lo(f[k][3]), r1, c1), fmaf(bf_hi(f[k][3]), r1, c1));
  }
}

#define XDELAY 800
constexpr int A_NST = 5;
constexpr int A_XS = 0;
constexpr int A_VB = 49152;
constexpr int A_W = 98304;
constexpr int A_BAR = A_W + A_NST * 24576;
constexpr int A_SMEM = A_BAR + 256 + 1024;
constexpr int A_FOLD = 36;

__device__ __forceinline__ void a_issue(float (&acc)[32], const uint32_t (&af)[12][4], uint32_t sb, int s) {
  const int st = s % A_NST;
  mbar_wait(sb + A_BAR + st * 8, (s / A_NST) & 1);
  const uint64_t wd = mk_desc_o(sb + A_W + st * 24576, 8192, 1024);
  wg_fence();
#pragma unroll
  for (int kk = 0; kk < 12; kk++) wgmma_n64_rs<1>(acc, af[kk], wd + kk * 128, kk > 0);
  wg_commit();
}
__device__ __forceinline__ void a_release(uint32_t sb, int s, int lane) {
  if (lane == 0) mbar_arrive(sb + A_BAR + 64 + (s % A_NST) * 8);
}
__device__ __forceinline__ void cvt_frags(uint32_t (*dst)[4], const float (&acc)[32]) {
#pragma unroll
  for (int k = 0; k < 4; k++) {
    dst[k][0] = pack_bf16(acc[8 * k + 0], acc[8 * k + 1]);
    dst[k][1] = pack_bf16(acc[8 * k + 2], acc[8 * k + 3]);
    dst[k][2] = pack_bf16(acc[8 * k + 4], acc[8 * k + 5]);
    dst[k][3] = pack_bf16(acc[8 * k + 6], acc[8 * k + 7]);
  }
}
__device__ __forceinline__ void store_chunk(const float (&acc)[32], uint32_t chunk_base, const FragAddr& fa) {
  uint32_t t[4][4];
  cvt_frags(t, acc);
#pragma unroll
  for (int k = 0; k < 4; k++) stsm_x4(fa.at(chunk_base, k), t[k]);
}
__device__ __forceinline__ void resid_chunk(uint32_t (*dst)[4], const float* acc, float s0, float s1, uint32_t chunk_base,
                                            const FragAddr& fa) {
#pragma unroll
  for (int k = 0; k < 4; k++) {
    uint32_t x[4];
    ldsm_x4(x, fa.at(chunk_base, k));
    uint32_t o[4];
    o[0] = pack_bf16(fmaf(acc[8 * k + 0], s0, bf_lo(x[0])), fmaf(acc[8 * k + 1], s0, bf_hi(x[0])));
    o[1] = pack_bf16(fmaf(acc[8 * k + 2], s1, bf_lo(x[1])), fmaf(acc[8 * k + 3], s1, bf_hi(x[1])));
    o[2] = pack_bf16(fmaf(acc[8 * k + 4], s0, bf_lo(x[2])), fmaf(acc[8 * k + 5], s0, bf_hi(x[2])));
    o[3] = pack_bf16(fmaf(acc[8 * k + 6], s1, bf_lo(x[3])), fmaf(acc[8 * k + 7], s1, bf_hi(x[3])));
    stsm_x4(fa.at(chunk_base, k), o);
    if (dst) { dst[k][0] = o[0]; dst[k][1] = o[1]; dst[k][2] = o[2]; dst[k][3] = o[3]; }
  }
}

__global__ void __launch_bounds__(384, 1)
kernelA(const __grid_constant__ CUtensorMap tm_x, const __grid_constant__ CUtensorMap tm_wq64t,
        const __grid_constant__ CUtensorMap tm_wot, const __grid_constant__ CUtensorMap tm_wq64s,
        const __grid_constant__ CUtensorMap tm_wos, const __grid_constant__ CUtensorMap tm_wf,
        const __grid_constant__ CUtensorMap tm_x1, const __grid_constant__ CUtensorMap tm_qkv) {
  extern __shared__ uint8_t smem_raw[];
  const uint32_t sb = (smem_u32(smem_raw) + 1023) & ~1023u;
  const int tid = threadIdx.x, warp = tid >> 5, lane = tid & 31;
  const bool is_fold = blockIdx.x < A_FOLD;
  const int blk = blockIdx.x - A_FOLD;
  if (tid == 256) {
    for (int i = 0; i < A_NST; i++) { mbar_init(sb + A_BAR + i * 8, 1); mbar_init(sb + A_BAR + 64 + i * 8, 8); }
    mbar_init(sb + A_BAR + 128, 1); mbar_init(sb + A_BAR + 136, 1);
    asm volatile("fence.mbarrier_init.release.cluster;" ::: "memory");
    if (!is_fold) {
      __nanosleep(XDELAY);
      for (int w = 0; w < 2; w++) {
        const uint32_t bar = sb + A_BAR + 128 + w * 8;
        mbar_expect_tx(bar, 3 * 63 * 128);
        for (int c = 0; c < 3; c++)
          tma_load_3d(sb + A_XS + w * 24576 + c * 8192, &tm_x, bar, c * 64, (blk * 2 + w) * 9, 0);
      }
    } else {
      const int mat = blockIdx.x / 9, rs = (blockIdx.x % 9) / 3, cs = blockIdx.x % 3;
      const CUtensorMap* mq = (mat < 2) ? &tm_wq64t : &tm_wq64s;
      const CUtensorMap* mo = (mat < 2) ? &tm_wot : &tm_wos;
      const uint32_t bar = sb + A_BAR + 128;
      mbar_expect_tx(bar, 2 * 24576);
      for (int c = 0; c < 3; c++) tma_load_2d(sb + c * 8192, mq, bar, ((mat & 1) ? 384 : 0) + c * 64, rs * 64);
      if (mat & 1) tma_load_2d(sb + 24576, mo, bar, cs * 64, 0);
      else for (int c = 0; c < 3; c++) tma_load_2d(sb + 24576 + c * 8192, mq, bar, 192 + c * 64, cs * 64);
    }
  }
  asm volatile("griddepcontrol.launch_dependents;" ::: "memory");
  if (blockIdx.x == 0 && tid < 128) g_flag[tid] = 0;
  if (!is_fold && tid < 48) {
    uint32_t a = sb + A_XS + (tid >> 3) * 8192 + 63 * 128 + (tid & 7) * 16;
    asm volatile("st.shared.v4.b32 [%0], {%1,%1,%1,%1};" ::"r"(a), "r"(0) : "memory");
  }
  __syncthreads();

  if (warp >= 8) {
    asm volatile("setmaxnreg.dec.sync.aligned.u32 24;");
    if (warp == 8 && lane == 0 && !is_fold) {
      for (int s = 0; s < 12; s++) {
        const int st = s % A_NST;
        const int g = s / 3;
        const int mat = (g == 0) ? 1 : (g == 1) ? 0 : g;
        if (s % 3 == 0) {
          uint32_t n = 0, v;
          do {
            asm volatile("ld.acquire.gpu.global.u32 %0, [%1];" : "=r"(v) : "l"(&g_wflag[mat]) : "memory");
          } while (v < 9u && ++n < (1u << 22));
          asm volatile("fence.proxy.async;" ::: "memory");
        }
        if (s >= A_NST) mbar_wait(sb + A_BAR + 64 + st * 8, ((s / A_NST) - 1) & 1);
        mbar_expect_tx(sb + A_BAR + st * 8, 24576);
        tma_load_2d(sb + A_W + st * 24576, &tm_wf, sb + A_BAR + st * 8, (mat & 1) * 192 + (s % 3) * 64, (mat >> 1) * 192);
      }
    }
    return;
  }

  asm volatile("setmaxnreg.inc.sync.aligned.u32 240;");
  const int wg = warp >> 2, wq = warp & 3;

  if (is_fold) {
    if (wg == 0) {
      const int mat = blockIdx.x / 9, rs = (blockIdx.x % 9) / 3, cs = blockIdx.x % 3;
      float d[32];
      mbar_wait(sb + A_BAR + 128, 0);
      const uint64_t ad = mk_desc_o(sb, 16, 1024);
      if (mat & 1) {
        const uint64_t bd = mk_desc_o(sb + 24576, 8192, 1024);
        wg_fence();
#pragma unroll
        for (int kk = 0; kk < 12; kk++) wgmma_n64_ss<1>(d, ad + (kk >> 2) * 512 + (kk & 3) * 2, bd + kk * 128, kk > 0);
        wg_commit();
      } else {
        const uint64_t bd = mk_desc_o(sb + 24576, 16, 1024);
        wg_fence();
#pragma unroll
        for (int kk = 0; kk < 12; kk++)
          wgmma_n64_ss<0>(d, ad + (kk >> 2) * 512 + (kk & 3) * 2, bd + (kk >> 2) * 512 + (kk & 3) * 2, kk > 0);
        wg_commit();
      }
      wg_wait<0>(); reg_fence(d);
      const int r0 = rs * 64 + wq * 16 + (lane >> 2);
      uint32_t* dst = reinterpret_cast<uint32_t*>(g_wf + ((size_t)(mat >> 1) * 192 + r0) * 384 + (mat & 1) * 192 + cs * 64 + (lane & 3) * 2);
#pragma unroll
      for (int j = 0; j < 8; j++) {
        dst[j * 4] = pack_bf16(d[4 * j], d[4 * j + 1]);
        dst[8 * 192 + j * 4] = pack_bf16(d[4 * j + 2], d[4 * j + 3]);
      }
      asm volatile("fence.proxy.async;" ::: "memory");
      named_bar(1, 128);
      if (tid == 0) { __threadfence(); atomicAdd(&g_wflag[mat], 1u); }
    }
    return;
  }

  const int n0 = (blk * 2 + wg) * 9;
  const FragAddr fa(wq, lane);
  const uint32_t xs = sb + A_XS + wg * 24576, vb = sb + A_VB + wg * 24576;
  const int barid = 1 + wg;
  const bool elected = (tid & 127) == 0;

  uint32_t h[12][4];
  TS(0, 0);
  mbar_wait(sb + A_BAR + 128 + wg * 8, 0);
  TS(0, 1);
#pragma unroll
  for (int k = 0; k < 12; k++) ldsm_x4(h[k], fa.at(xs + (k >> 2) * 8192, k & 3));
  layernorm_frags(h);
#pragma unroll
  for (int k = 0; k < 12; k++) stsm_x4(fa.at(xs + (k >> 2) * 8192, k & 3), h[k]);

  float acc0[32], acc1[32];
  uint32_t qf[12][4];
  TS(0, 2);
  a_issue(acc0, h, sb, 0);
  TS(0, 3);
  a_issue(acc1, h, sb, 1); wg_wait<1>(); reg_fence(acc0); a_release(sb, 0, lane); store_chunk(acc0, vb, fa);
  a_issue(acc0, h, sb, 2); wg_wait<1>(); reg_fence(acc1); a_release(sb, 1, lane); store_chunk(acc1, vb + 8192, fa);
  a_issue(acc1, h, sb, 3); wg_wait<1>(); reg_fence(acc0); a_release(sb, 2, lane); store_chunk(acc0, vb + 16384, fa);
  fence_proxy_async();
  named_bar(barid, 128);
  a_issue(acc0, h, sb, 4); wg_wait<1>(); reg_fence(acc1); a_release(sb, 3, lane); cvt_frags(&qf[0], acc1);
  a_issue(acc1, h, sb, 5); wg_wait<1>(); reg_fence(acc0); a_release(sb, 4, lane); cvt_frags(&qf[4], acc0);
  wg_wait<0>(); reg_fence(acc1); a_release(sb, 5, lane); cvt_frags(&qf[8], acc1);
  TS(0, 4);
  {
    const uint64_t kd = mk_desc_o(xs, 16, 1024);
    wg_fence();
#pragma unroll
    for (int kk = 0; kk < 12; kk++) wgmma_n64_rs<0>(acc0, qf[kk], kd + (kk >> 2) * 512 + (kk & 3) * 2, kk > 0);
    wg_commit();
    wg_wait<0>(); reg_fence(acc0);
  }
  named_bar(barid, 128);
  if (elected) {
    const uint32_t bar = sb + A_BAR + 128 + wg * 8;
    mbar_expect_tx(bar, 3 * 63 * 128);
    for (int c = 0; c < 3; c++) tma_load_3d(xs + c * 8192, &tm_x, bar, c * 64, n0, 0);
  }
  uint32_t pf[4][4];
  {
    const int r0 = 16 * wq + (lane >> 2), r1 = r0 + 8;
    const unsigned long long MB = 0x0040201008040201ull;
    const unsigned long long mk0 = (MB << (r0 % 9)) >> (2 * (lane & 3));
    const unsigned long long mk1 = (MB << (r1 % 9)) >> (2 * (lane & 3));
    const float cs = 0.07216878364870322f * 1.4426950408889634f;
    float mx0 = -INFINITY, mx1 = -INFINITY;
#pragma unroll
    for (int j = 0; j < 8; j++) {
#pragma unroll
      for (int e = 0; e < 2; e++) {
        bool v0 = (mk0 >> (8 * j + e)) & 1, v1 = (mk1 >> (8 * j + e)) & 1;
        acc0[4 * j + e] = v0 ? acc0[4 * j + e] * cs : -INFINITY;
        acc0[4 * j + 2 + e] = v1 ? acc0[4 * j + 2 + e] * cs : -INFINITY;
        mx0 = fmaxf(mx0, acc0[4 * j + e]);
        mx1 = fmaxf(mx1, acc0[4 * j + 2 + e]);
      }
    }
    mx0 = fmaxf(mx0, __shfl_xor_sync(0xffffffffu, mx0, 1)); mx0 = fmaxf(mx0, __shfl_xor_sync(0xffffffffu, mx0, 2));
    mx1 = fmaxf(mx1, __shfl_xor_sync(0xffffffffu, mx1, 1)); mx1 = fmaxf(mx1, __shfl_xor_sync(0xffffffffu, mx1, 2));
    float l0 = 0.f, l1 = 0.f;
#pragma unroll
    for (int j = 0; j < 8; j++) {
#pragma unroll
      for (int e = 0; e < 2; e++) {
        acc0[4 * j + e] = ex2(acc0[4 * j + e] - mx0); l0 += acc0[4 * j + e];
        acc0[4 * j + 2 + e] = ex2(acc0[4 * j + 2 + e] - mx1); l1 += acc0[4 * j + 2 + e];
      }
    }
    l0 += __shfl_xor_sync(0xffffffffu, l0, 1); l0 += __shfl_xor_sync(0xffffffffu, l0, 2);
    l1 += __shfl_xor_sync(0xffffffffu, l1, 1); l1 += __shfl_xor_sync(0xffffffffu, l1, 2);
    const float i0 = 1.f / l0, i1 = 1.f / l1;
#pragma unroll
    for (int j = 0; j < 8; j++) {
      acc0[4 * j] *= i0; acc0[4 * j + 1] *= i0; acc0[4 * j + 2] *= i1; acc0[4 * j + 3] *= i1;
    }
    cvt_frags(pf, acc0);
  }
  TS(0, 5);
  {
    float oacc[96];
    const uint64_t vd = mk_desc_o(vb, 8192, 1024);
    wg_fence();
#pragma unroll
    for (int kk = 0; kk < 4; kk++) wgmma_n192_rs<1>(oacc, pf[kk], vd + kk * 128, kk > 0);
    wg_commit();
    wg_wait<0>(); reg_fence(oacc);
    TS(0, 6);
    mbar_wait(sb + A_BAR + 128 + wg * 8, 1);
#pragma unroll
    for (int c = 0; c < 3; c++) resid_chunk(&h[4 * c], &oacc[32 * c], 1.f, 1.f, xs + c * 8192, fa);
  }
  TS(0, 7);
  fence_proxy_async();
  named_bar(barid, 128);
  if (elected) {
    for (int c = 0; c < 3; c++) tma_store_3d(&tm_x1, xs + c * 8192, c * 64, n0, 0);
    bulk_commit();
  }
  layernorm_frags(h);
#pragma unroll
  for (int k = 0; k < 12; k++) stsm_x4(fa.at(vb + (k >> 2) * 8192, k & 3), h[k]);
  TS(0, 8);
  a_issue(acc0, h, sb, 6);
  a_issue(acc1, h, sb, 7);
  fence_proxy_async();
  if (elected) bulk_wait_read0();
  named_bar(barid, 128);
  if (elected) {
    for (int c = 0; c < 3; c++) tma_store_3d(&tm_qkv, vb + c * 8192, 192 + c * 64, n0, 0);
    bulk_commit();
  }
  wg_wait<1>(); reg_fence(acc0); a_release(sb, 6, lane); store_chunk(acc0, xs, fa);
  a_issue(acc0, h, sb, 8); wg_wait<1>(); reg_fence(acc1); store_chunk(acc1, xs + 8192, fa);
  a_issue(acc1, h, sb, 9); wg_wait<1>(); reg_fence(acc0); store_chunk(acc0, xs + 16384, fa);
  a_issue(acc0, h, sb, 10);
  fence_proxy_async();
  if (elected) bulk_wait_read0();
  named_bar(barid, 128);
  if (elected) {
    for (int c = 0; c < 3; c++) tma_store_3d(&tm_qkv, xs + c * 8192, c * 64, n0, 0);
    bulk_commit();
  }
  {
    const int rr = wq * 16 + (lane >> 3);
    __nv_bfloat16* gdst = g_qkv + 384 + (lane & 7) * 8;
    auto flush = [&](uint32_t cb, int c) {
      __syncwarp();
#pragma unroll
      for (int i = 0; i < 4; i++) {
        const int r = rr + 4 * i;
        uint4 v;
        asm volatile("ld.shared.v4.b32 {%0,%1,%2,%3}, [%4];" : "=r"(v.x), "=r"(v.y), "=r"(v.z), "=r"(v.w)
                     : "r"(cb + r * 128 + (((lane & 7) ^ (r & 7)) << 4)) : "memory");
        const int t = r / 9, loc = r - t * 9;
        if (r < 63) *reinterpret_cast<uint4*>(gdst + ((size_t)t * NL + n0 + loc) * 576 + c * 64) = v;
      }
    };
    wg_wait<1>(); reg_fence(acc1); store_chunk(acc1, vb, fa);
    a_issue(acc1, h, sb, 11);
    flush(vb, 0);
    wg_wait<1>(); reg_fence(acc0); store_chunk(acc0, vb + 8192, fa);
    flush(vb + 8192, 1);
    wg_wait<0>(); reg_fence(acc1); store_chunk(acc1, vb + 16384, fa);
    flush(vb + 16384, 2);
  }
  TS(0, 9);
  if (elected) bulk_wait_read0();
  TS(0, 10);
}

constexpr int B_GRID = 132;
constexpr int B_NS = 5;
constexpr int B_SLOT = 36864;
constexpr int B_Q2 = B_NS * B_SLOT;
constexpr int B_BAR = B_Q2 + 16384;
constexpr int B_SMEM = B_BAR + 256 + 1024;

__device__ __forceinline__ void bar_arrive(int id, int nthreads) {
  asm volatile("bar.arrive %0, %1;" ::"r"(id), "r"(nthreads) : "memory");
}
__device__ __forceinline__ int b_nseg() {
  const int ci = blockIdx.x % 12;
  return ci < 7 ? 1 : (ci == 9 ? 3 : 2);
}
__device__ __forceinline__ void b_segment(int sg, int& tile, int& u0, int& u1) {
  const int grp = blockIdx.x / 12, ci = blockIdx.x - grp * 12;
  if (ci < 7) { tile = grp * 7 + ci; u0 = 9; u1 = 27; }
  else {
    const int hh = ci - 7;
    tile = grp * 7 + ((0x54210 >> (4 * hh)) & 15) + sg;
    u0 = sg ? 0 : ((0x62840 >> (4 * hh)) & 15);
    u1 = (sg == 0) ? 9 : (sg == 1) ? ((0x96984 >> (4 * hh)) & 15) : 2;
  }
}

__global__ void __launch_bounds__(384, 1)
kernelB(const __grid_constant__ CUtensorMap tm_q, const __grid_constant__ CUtensorMap tm_kv,
        const __grid_constant__ CUtensorMap tm_x1, const __grid_constant__ CUtensorMap tm_out) {
  extern __shared__ uint8_t smem_raw[];
  const uint32_t sb = (smem_u32(smem_raw) + 1023) & ~1023u;
  const int tid = threadIdx.x, warp = tid >> 5, lane = tid & 31;
  const uint32_t bF = sb + B_BAR, bE = sb + B_BAR + 64, bQF = sb + B_BAR + 112, bQE = sb + B_BAR + 120;
  if (tid == 0) {
    for (int i = 0; i < B_NS; i++) { mbar_init(bF + i * 8, 1); mbar_init(bE + i * 8, 8); }
    mbar_init(bQF, 1); mbar_init(bQE, 8);
    asm volatile("fence.mbarrier_init.release.cluster;" ::: "memory");
    prefetch_tmap(&tm_q); prefetch_tmap(&tm_kv); prefetch_tmap(&tm_x1); prefetch_tmap(&tm_out);
  }
  __syncthreads();
  asm volatile("griddepcontrol.wait;" ::: "memory");
  const int grp = blockIdx.x / 12, ci = blockIdx.x - grp * 12;
  const bool owner = ci < 7;
  const int nseg = b_nseg();

  if (warp >= 8) {
    asm volatile("setmaxnreg.dec.sync.aligned.u32 24;");
    if (warp == 8 && lane == 0) {
      if (blockIdx.x == 0) { g_wflag[0] = 0; g_wflag[1] = 0; g_wflag[2] = 0; g_wflag[3] = 0; }
      int it = 0;
      for (int sg = 0; sg < nseg + (owner ? 1 : 0); sg++) {
        int tile, u0, u1;
        b_segment(sg < nseg ? sg : 0, tile, u0, u1);
        const int t = tile / 11, qt = tile - t * 11;
        const int n = (sg < nseg) ? ((u1 - u0 + 1) >> 1) : 0;
        for (int e = -1; e < 2 * n; e++) {
          const int sl = it % B_NS;
          if (it >= B_NS) mbar_wait(bE + sl * 8, ((it / B_NS) - 1) & 1);
          if (e < 0) {
            const CUtensorMap* m = sg < nseg ? &tm_q : &tm_x1;
            mbar_expect_tx(bF + sl * 8, 32768);
            for (int c = 0; c < 2; c++) tma_load_3d(sb + sl * B_SLOT + c * 16384, m, bF + sl * 8, c * 64, qt * 128, t);
            if (sg > 0) mbar_wait(bQE, (sg - 1) & 1);
            mbar_expect_tx(bQF, 16384);
            tma_load_3d(sb + B_Q2, m, bQF, 128, qt * 128, t);
          } else {
            int isv, kbi;
            if (e == 0) { isv = 0; kbi = 0; }
            else if (e == 2 * n - 1) { isv = 1; kbi = n - 1; }
            else { isv = (e & 1) ^ 1; kbi = isv ? (e >> 1) - 1 : (e + 1) >> 1; }
            mbar_expect_tx(bF + sl * 8, B_SLOT);
            for (int c = 0; c < 3; c++)
              tma_load_3d(sb + sl * B_SLOT + c * 12288, &tm_kv, bF + sl * 8, 192 + isv * 192 + c * 64, u0 * 48 + kbi * 96, t);
          }
          it++;
        }
      }
    } else if ((warp == 9 || warp == 10) && !owner) {
      const int sbase = grp * 11 + ((0x97420 >> (4 * (ci - 7))) & 15);
      for (int sg = 0; sg < nseg; sg++) {
        named_bar(5 + (warp - 9), 160);
        if (lane == 0) {
          __threadfence();
          atomicAdd(&g_flag[sbase + sg], 1u);
        }
        __syncwarp();
      }
    }
    return;
  }

  asm volatile("setmaxnreg.inc.sync.aligned.u32 240;");
  const int wg = warp >> 2, wq = warp & 3;
  const int wtid = tid & 127;
  const float cs = 0.07216878364870322f * 1.4426950408889634f;
  float oacc[96], sacc[48];
  uint32_t pf[6][4], qf[8][4];
  float m0, m1, l0, l1;
  int it = 0;
  if (wg == 1) bar_arrive(3, 256);
  TS(1, 0);
  int tsi = 1;

  auto issue_qk = [&](int slot) {
    const uint64_t kd = mk_desc_o(sb + slot * B_SLOT, 16, 1024);
    const uint64_t qd = mk_desc_o(sb + B_Q2 + wg * 8192, 16, 1024);
#pragma unroll
    for (int kk = 0; kk < 8; kk++) wgmma_n96_rs<0>(sacc, qf[kk], kd + (kk >> 2) * 768 + (kk & 3) * 2, kk > 0);
#pragma unroll
    for (int kk = 8; kk < 12; kk++) wgmma_n96_ss<0>(sacc, qd + (kk & 3) * 2, kd + 2 * 768 + (kk & 3) * 2, 1);
    wg_commit();
  };
  auto issue_pv = [&](int slot, int accum) {
    const uint64_t vd = mk_desc_o(sb + slot * B_SLOT, 12288, 1024);
#pragma unroll
    for (int kk = 0; kk < 6; kk++) wgmma_n192_rs<1>(oacc, pf[kk], vd + kk * 128, kk > 0 ? 1 : accum);
    wg_commit();
  };
  auto softmax1 = [&](bool half, float& a0, float& a1) {
    if (half) {
#pragma unroll
      for (int i = 24; i < 48; i++) sacc[i] = -INFINITY;
    }
    float t0[2], t1[2];
    t0[0] = fmaxf(m0, fmaxf(sacc[0], sacc[1])); t1[0] = fmaxf(m1, fmaxf(sacc[2], sacc[3]));
    t0[1] = fmaxf(sacc[4], sacc[5]); t1[1] = fmaxf(sacc[6], sacc[7]);
#pragma unroll
    for (int j = 2; j < 12; j++) {
      t0[j & 1] = fmaxf(t0[j & 1], fmaxf(sacc[4 * j], sacc[4 * j + 1]));
      t1[j & 1] = fmaxf(t1[j & 1], fmaxf(sacc[4 * j + 2], sacc[4 * j + 3]));
    }
    float mx0 = fmaxf(t0[0], t0[1]), mx1 = fmaxf(t1[0], t1[1]);
    mx0 = fmaxf(mx0, __shfl_xor_sync(0xffffffffu, mx0, 1)); mx1 = fmaxf(mx1, __shfl_xor_sync(0xffffffffu, mx1, 1));
    mx0 = fmaxf(mx0, __shfl_xor_sync(0xffffffffu, mx0, 2)); mx1 = fmaxf(mx1, __shfl_xor_sync(0xffffffffu, mx1, 2));
    a0 = ex2((m0 - mx0) * cs); a1 = ex2((m1 - mx1) * cs);
    m0 = mx0; m1 = mx1;
    const float mc0 = mx0 * cs, mc1 = mx1 * cs;
    l0 *= a0; l1 *= a1;
    t0[0] = 0.f; t1[0] = 0.f;
#pragma unroll
    for (int j = 0; j < 12; j++) {
      sacc[4 * j] = ex2(fmaf(sacc[4 * j], cs, -mc0)); sacc[4 * j + 1] = ex2(fmaf(sacc[4 * j + 1], cs, -mc0));
      sacc[4 * j + 2] = ex2(fmaf(sacc[4 * j + 2], cs, -mc1)); sacc[4 * j + 3] = ex2(fmaf(sacc[4 * j + 3], cs, -mc1));
      l0 += sacc[4 * j]; t0[0] += sacc[4 * j + 1];
      l1 += sacc[4 * j + 2]; t1[0] += sacc[4 * j + 3];
    }
    l0 += t0[0]; l1 += t1[0];
  };
  auto cvt_p = [&]() {
#pragma unroll
    for (int k = 0; k < 6; k++) {
      pf[k][0] = pack_bf16(sacc[8 * k + 0], sacc[8 * k + 1]); pf[k][1] = pack_bf16(sacc[8 * k + 2], sacc[8 * k + 3]);
      pf[k][2] = pack_bf16(sacc[8 * k + 4], sacc[8 * k + 5]); pf[k][3] = pack_bf16(sacc[8 * k + 6], sacc[8 * k + 7]);
    }
  };

  for (int sg = 0; sg < nseg; sg++) {
    int n; bool odd;
    { int tile, u0, u1; b_segment(sg, tile, u0, u1); n = (u1 - u0 + 1) >> 1; odd = (u1 - u0) & 1; }
    m0 = m1 = -INFINITY; l0 = l1 = 0.f;
    {
      const int sl = it % B_NS;
      mbar_wait(bF + sl * 8, (it / B_NS) & 1);
      const uint32_t qb = sb + sl * B_SLOT + wg * 8192;
      const FragAddr fa(wq, lane);
#pragma unroll
      for (int k = 0; k < 8; k++) ldsm_x4(qf[k], fa.at(qb + (k >> 2) * 16384, k & 3));
      __syncwarp();
      if (lane == 0) mbar_arrive(bE + sl * 8);
      it++;
      mbar_wait(bQF, sg & 1);
    }
    {
      const int sl = it % B_NS;
      mbar_wait(bF + sl * 8, (it / B_NS) & 1);
      named_bar(3 + wg, 256);
      wg_fence();
      issue_qk(sl);
      bar_arrive(3 + (wg ^ 1), 256);
      wg_wait<0>(); reg_fence(sacc);
      if (lane == 0) { mbar_arrive(bE + sl * 8); if (n == 1) mbar_arrive(bQE); }
      it++;
      float a0, a1;
      softmax1(odd && n == 1, a0, a1);
      cvt_p();
    }
    TS(1, tsi); tsi++;
    for (int j = 1; j < n; j++) {
      const int slk = it % B_NS, slv = (it + 1) % B_NS;
      mbar_wait(bF + slk * 8, (it / B_NS) & 1);
      mbar_wait(bF + slv * 8, ((it + 1) / B_NS) & 1);
      named_bar(3 + wg, 256);
      wg_fence();
      issue_qk(slk);
      issue_pv(slv, j > 1);
      bar_arrive(3 + (wg ^ 1), 256);
      wg_wait<1>(); reg_fence(sacc);
      if (lane == 0) { mbar_arrive(bE + slk * 8); if (j == n - 1) mbar_arrive(bQE); }
      float a0, a1;
      softmax1(odd && j == n - 1, a0, a1);
      if (!(l0 + l1 >= 0.f)) asm volatile("st.shared.u32 [%0], %1;" ::"r"(sb + B_BAR + 128), "r"(0) : "memory");
      wg_wait<0>(); reg_fence(oacc);
      if (lane == 0) mbar_arrive(bE + slv * 8);
      it += 2;
#pragma unroll
      for (int i = 0; i < 24; i++) {
        oacc[4 * i] *= a0; oacc[4 * i + 1] *= a0; oacc[4 * i + 2] *= a1; oacc[4 * i + 3] *= a1;
      }
      cvt_p();
      TS(1, tsi); tsi++;
    }
    {
      const int sl = it % B_NS;
      mbar_wait(bF + sl * 8, (it / B_NS) & 1);
      named_bar(3 + wg, 256);
      wg_fence();
      issue_pv(sl, n > 1);
      if (!(wg == 1 && sg == nseg - 1)) bar_arrive(3 + (wg ^ 1), 256);
      wg_wait<0>(); reg_fence(oacc);
      if (lane == 0) mbar_arrive(bE + sl * 8);
      it++;
    }
    TS(1, tsi); tsi++;
    if (!owner) {
      const int slot = grp * 11 + ((0x97420 >> (4 * (ci - 7))) & 15) + sg;
      uint4* dst = g_part + (size_t)(slot * 2 + wg) * 13 * 128 + wtid;
#pragma unroll
      for (int i = 0; i < 12; i++)
        dst[i * 128] = make_uint4(pack_bf16(oacc[8 * i], oacc[8 * i + 1]), pack_bf16(oacc[8 * i + 2], oacc[8 * i + 3]),
                                  pack_bf16(oacc[8 * i + 4], oacc[8 * i + 5]), pack_bf16(oacc[8 * i + 6], oacc[8 * i + 7]));
      dst[12 * 128] = make_uint4(__float_as_uint(m0), __float_as_uint(m1), __float_as_uint(l0), __float_as_uint(l1));
      bar_arrive(5 + wg, 160);
      TS(1, tsi); tsi++;
    }
  }
  if (!owner) return;

  {
    const int first = (0xA865310 >> (4 * ci)) & 15, cnt = (0x1221221 >> (4 * ci)) & 15;
    const int slot0 = grp * 11 + first;
    if (wtid < cnt) {
      uint32_t n = 0, v;
      do {
        asm volatile("ld.acquire.gpu.global.u32 %0, [%1];" : "=r"(v) : "l"(&g_flag[slot0 + wtid]) : "memory");
      } while (v < 2u && ++n < (1u << 22));
    }
    named_bar(1 + wg, 128);
    uint4 pv[2][13];
#pragma unroll
    for (int q = 0; q < 2; q++) {
      if (q < cnt) {
        const uint4* src = g_part + (size_t)((slot0 + q) * 2 + wg) * 13 * 128 + wtid;
#pragma unroll
        for (int i = 0; i < 13; i++) pv[q][i] = __ldcg(src + i * 128);
      }
    }
#pragma unroll
    for (int q = 0; q < 2; q++) {
      if (q < cnt) {
        const float pm0 = __uint_as_float(pv[q][12].x), pm1 = __uint_as_float(pv[q][12].y);
        const float mx0 = fmaxf(m0, pm0), mx1 = fmaxf(m1, pm1);
        const float a0 = ex2((m0 - mx0) * cs), a1 = ex2((m1 - mx1) * cs);
        const float b0 = ex2((pm0 - mx0) * cs), b1 = ex2((pm1 - mx1) * cs);
        m0 = mx0; m1 = mx1;
        l0 = l0 * a0 + __uint_as_float(pv[q][12].z) * b0; l1 = l1 * a1 + __uint_as_float(pv[q][12].w) * b1;
#pragma unroll
        for (int i = 0; i < 12; i++) {
          const uint4 v = pv[q][i];
          oacc[8 * i + 0] = oacc[8 * i + 0] * a0 + bf_lo(v.x) * b0; oacc[8 * i + 1] = oacc[8 * i + 1] * a0 + bf_hi(v.x) * b0;
          oacc[8 * i + 2] = oacc[8 * i + 2] * a1 + bf_lo(v.y) * b1; oacc[8 * i + 3] = oacc[8 * i + 3] * a1 + bf_hi(v.y) * b1;
          oacc[8 * i + 4] = oacc[8 * i + 4] * a0 + bf_lo(v.z) * b0; oacc[8 * i + 5] = oacc[8 * i + 5] * a0 + bf_hi(v.z) * b0;
          oacc[8 * i + 6] = oacc[8 * i + 6] * a1 + bf_lo(v.w) * b1; oacc[8 * i + 7] = oacc[8 * i + 7] * a1 + bf_hi(v.w) * b1;
        }
      }
    }
  }
  TS(1, 21);
  l0 += __shfl_xor_sync(0xffffffffu, l0, 1); l0 += __shfl_xor_sync(0xffffffffu, l0, 2);
  l1 += __shfl_xor_sync(0xffffffffu, l1, 1); l1 += __shfl_xor_sync(0xffffffffu, l1, 2);
  const float i0 = 1.f / l0, i1 = 1.f / l1;
  const int sl = it % B_NS;
  mbar_wait(bF + sl * 8, (it / B_NS) & 1);
  mbar_wait(bQF, 1);
  const uint32_t xb0 = sb + sl * B_SLOT + wg * 8192, xb2 = sb + B_Q2 + wg * 8192;
  const FragAddr fa(wq, lane);
  resid_chunk(nullptr, &oacc[0], i0, i1, xb0, fa);
  resid_chunk(nullptr, &oacc[32], i0, i1, xb0 + 16384, fa);
  resid_chunk(nullptr, &oacc[64], i0, i1, xb2, fa);
  fence_proxy_async();
  named_bar(1 + wg, 128);
  TS(1, 22);
  if (wtid == 0) {
    const int tile = grp * 7 + ci;
    const int t = tile / 11, qt = tile - t * 11;
    if (qt * 128 + wg * 64 < NL) {
      tma_store_3d(&tm_out, xb0, 0, qt * 128 + wg * 64, t);
      tma_store_3d(&tm_out, xb0 + 16384, 64, qt * 128 + wg * 64, t);
      tma_store_3d(&tm_out, xb2, 128, qt * 128 + wg * 64, t);
      bulk_commit();
      bulk_wait_read0();
    }
  }
  TS(1, 23);
}

typedef CUresult (*EncodeFn)(CUtensorMap*, CUtensorMapDataType, cuuint32_t, void*, const cuuint64_t*, const cuuint64_t*,
                             const cuuint32_t*, const cuuint32_t*, CUtensorMapInterleave, CUtensorMapSwizzle,
                             CUtensorMapL2promotion, CUtensorMapFloatOOBfill);

void make_map(EncodeFn enc, CUtensorMap* m, const void* ptr, int rank, const uint64_t* dims, const uint32_t* box) {
  cuuint64_t gd[3], gs[2];
  cuuint32_t bx[3], es[3] = {1, 1, 1};
  uint64_t stride = 2;
  for (int i = 0; i < rank; i++) {
    gd[i] = dims[i]; bx[i] = box[i];
    stride *= dims[i];
    if (i < rank - 1) gs[i] = stride;
  }
  enc(m, CU_TENSOR_MAP_DATA_TYPE_BFLOAT16, rank, const_cast<void*>(ptr), gd, gs, bx, es, CU_TENSOR_MAP_INTERLEAVE_NONE,
      CU_TENSOR_MAP_SWIZZLE_128B, CU_TENSOR_MAP_L2_PROMOTION_L2_256B, CU_TENSOR_MAP_FLOAT_OOB_FILL_NONE);
}

}

extern "C" void kernel_launch(void* const* d_in, const int* in_sizes, int n_in, void* d_out, int out_size) {
  (void)in_sizes; (void)n_in; (void)out_size;
  EncodeFn enc = nullptr;
  cudaDriverEntryPointQueryResult qres;
  cudaGetDriverEntryPoint("cuTensorMapEncodeTiled", (void**)&enc, cudaEnableDefault, &qres);
  void *p_x1, *p_qkv, *p_wf;
  cudaGetSymbolAddress(&p_wf, g_wf);
  cudaGetSymbolAddress(&p_x1, g_x1);
  cudaGetSymbolAddress(&p_qkv, g_qkv);
  cudaFuncSetAttribute(kernelA, cudaFuncAttributeMaxDynamicSharedMemorySize, A_SMEM);
  cudaFuncSetAttribute(kernelB, cudaFuncAttributeMaxDynamicSharedMemorySize, B_SMEM);

  CUtensorMap tm_x, tm_wqkvt, tm_wot, tm_wqkvs, tm_x1s, tm_qkvs, tm_q, tm_kv, tm_wos, tm_x1l, tm_out, tm_wf;
  const uint64_t d_act[3] = {192, 1296, 7}, d_qkv[3] = {576, 1296, 7}, d_w3[2] = {576, 192}, d_w1[2] = {192, 192}, d_wf[2] = {384, 384};
  const uint32_t b_a[3] = {64, 9, 7}, b_w[2] = {64, 192}, b_q[3] = {64, 128, 1}, b_kv[3] = {64, 96, 1}, b_o[3] = {64, 64, 1}, b_w64[2] = {64, 64};
  make_map(enc, &tm_x, d_in[0], 3, d_act, b_a);
  make_map(enc, &tm_wqkvt, d_in[1], 2, d_w3, b_w64);
  make_map(enc, &tm_wot, d_in[2], 2, d_w1, b_w);
  make_map(enc, &tm_wqkvs, d_in[3], 2, d_w3, b_w64);
  make_map(enc, &tm_wos, d_in[4], 2, d_w1, b_w);
  make_map(enc, &tm_wf, p_wf, 2, d_wf, b_w);
  make_map(enc, &tm_x1s, p_x1, 3, d_act, b_a);
  make_map(enc, &tm_qkvs, p_qkv, 3, d_qkv, b_a);
  make_map(enc, &tm_q, p_qkv, 3, d_qkv, b_q);
  make_map(enc, &tm_kv, p_qkv, 3, d_qkv, b_kv);
  make_map(enc, &tm_x1l, p_x1, 3, d_act, b_q);
  make_map(enc, &tm_out, d_out, 3, d_act, b_o);

  kernelA<<<72 + A_FOLD, 384, A_SMEM, cudaStreamPerThread>>>(tm_x, tm_wqkvt, tm_wot, tm_wqkvs, tm_wos, tm_wf, tm_x1s, tm_qkvs);
  cudaLaunchConfig_t cfg = {};
  cfg.gridDim = dim3(B_GRID); cfg.blockDim = dim3(384); cfg.dynamicSmemBytes = B_SMEM; cfg.stream = cudaStreamPerThread;
  cudaLaunchAttribute at[1];
  at[0].id = cudaLaunchAttributeProgrammaticStreamSerialization;
  at[0].val.programmaticStreamSerializationAllowed = 1;
  cfg.attrs = at; cfg.numAttrs = 1;
  cudaLaunchKernelEx(&cfg, kernelB, tm_q, tm_kv, tm_x1l, tm_out);
}
```

```cpp
#include <cuda_runtime.h>
#include <cuda_bf16.h>
#include <cuda.h>
#include <stdint.h>

namespace {

constexpr int TT = 7, NL = 1296, CC = 192;

__device__ __align__(1024) __nv_bfloat16 g_x1[TT * NL * CC];
__device__ __align__(1024) __nv_bfloat16 g_qkv[TT * NL * 3 * CC];
__device__ __align__(1024) __nv_bfloat16 g_wf[2 * CC * 2 * CC];
__device__ __align__(1024) uint4 g_part[121 * 2 * 13 * 128];
__device__ unsigned int g_flag[128];
__device__ unsigned int g_wflag[4];

#define TS(k, i)

__device__ __forceinline__ uint32_t smem_u32(const void* p) { return (uint32_t)__cvta_generic_to_shared(p); }
__device__ __forceinline__ void mbar_init(uint32_t bar, uint32_t cnt) {
  asm volatile("mbarrier.init.shared::cta.b64 [%0], %1;" ::"r"(bar), "r"(cnt));
}
__device__ __forceinline__ void mbar_expect_tx(uint32_t bar, uint32_t bytes) {
  asm volatile("mbarrier.arrive.expect_tx.shared::cta.b64 _, [%0], %1;" ::"r"(bar), "r"(bytes) : "memory");
}
__device__ __forceinline__ void mbar_arrive(uint32_t bar) {
  asm volatile("mbarrier.arrive.shared::cta.b64 _, [%0];" ::"r"(bar) : "memory");
}
__device__ __forceinline__ bool mbar_try(uint32_t bar, uint32_t parity) {
  uint32_t ok;
  asm volatile("{\n.reg .pred p;\nmbarrier.try_wait.parity.shared::cta.b64 p, [%1], %2;\nselp.u32 %0, 1, 0, p;\n}"
               : "=r"(ok) : "r"(bar), "r"(parity) : "memory");
  return ok != 0;
}
__device__ __forceinline__ void mbar_wait(uint32_t bar, uint32_t parity) {
  if (mbar_try(bar, parity)) return;
  uint32_t n = 0;
  while (!mbar_try(bar, parity)) {
    if (++n > (1u << 22)) break;
  }
}
__device__ __forceinline__ void tma_load_2d(uint32_t dst, const CUtensorMap* m, uint32_t bar, int c0, int c1) {
  asm volatile("cp.async.bulk.tensor.2d.shared::cluster.global.mbarrier::complete_tx::bytes [%0], [%1, {%3, %4}], [%2];"
               ::"r"(dst), "l"(m), "r"(bar), "r"(c0), "r"(c1) : "memory");
}
__device__ __forceinline__ void tma_load_3d(uint32_t dst, const CUtensorMap* m, uint32_t bar, int c0, int c1, int c2) {
  asm volatile("cp.async.bulk.tensor.3d.shared::cluster.global.mbarrier::complete_tx::bytes [%0], [%1, {%3, %4, %5}], [%2];"
               ::"r"(dst), "l"(m), "r"(bar), "r"(c0), "r"(c1), "r"(c2) : "memory");
}
__device__ __forceinline__ void tma_store_3d(const CUtensorMap* m, uint32_t src, int c0, int c1, int c2) {
  asm volatile("cp.async.bulk.tensor.3d.global.shared::cta.bulk_group [%0, {%2, %3, %4}], [%1];"
               ::"l"(m), "r"(src), "r"(c0), "r"(c1), "r"(c2) : "memory");
}
__device__ __forceinline__ void bulk_commit() { asm volatile("cp.async.bulk.commit_group;" ::: "memory"); }
__device__ __forceinline__ void bulk_wait_read0() { asm volatile("cp.async.bulk.wait_group.read 0;" ::: "memory"); }
__device__ __forceinline__ void bulk_wait_read1() { asm volatile("cp.async.bulk.wait_group.read 1;" ::: "memory"); }
__device__ __forceinline__ void bulk_wait0() { asm volatile("cp.async.bulk.wait_group 0;" ::: "memory"); }
__device__ __forceinline__ void fence_proxy_async() { asm volatile("fence.proxy.async.shared::cta;" ::: "memory"); }
__device__ __forceinline__ void prefetch_tmap(const CUtensorMap* m) {
  asm volatile("prefetch.tensormap [%0];" ::"l"(m) : "memory");
}
__device__ __forceinline__ void wg_fence() { asm volatile("wgmma.fence.sync.aligned;" ::: "memory"); }
__device__ __forceinline__ void wg_commit() { asm volatile("wgmma.commit_group.sync.aligned;" ::: "memory"); }
template <int N> __device__ __forceinline__ void wg_wait() { asm volatile("wgmma.wait_group.sync.aligned %0;" ::"n"(N) : "memory"); }
__device__ __forceinline__ void named_bar(int id, int nthreads) {
  asm volatile("bar.sync %0, %1;" ::"r"(id), "r"(nthreads) : "memory");
}
__device__ __forceinline__ void ldsm_x4(uint32_t (&r)[4], uint32_t addr) {
  asm volatile("ldmatrix.sync.aligned.m8n8.x4.shared.b16 {%0,%1,%2,%3}, [%4];"
               : "=r"(r[0]), "=r"(r[1]), "=r"(r[2]), "=r"(r[3]) : "r"(addr) : "memory");
}
__device__ __forceinline__ void stsm_x4(uint32_t addr, const uint32_t (&r)[4]) {
  asm volatile("stmatrix.sync.aligned.m8n8.x4.shared.b16 [%0], {%1,%2,%3,%4};"
               ::"r"(addr), "r"(r[0]), "r"(r[1]), "r"(r[2]), "r"(r[3]) : "memory");
}
__device__ __forceinline__ uint32_t pack_bf16(float lo, float hi) {
  uint32_t r;
  asm("cvt.rn.bf16x2.f32 %0, %1, %2;" : "=r"(r) : "f"(hi), "f"(lo));
  return r;
}
__device__ __forceinline__ float bf_lo(uint32_t v) { return __uint_as_float(v << 16); }
__device__ __forceinline__ float bf_hi(uint32_t v) { return __uint_as_float(v & 0xffff0000u); }
__device__ __forceinline__ float ex2(float x) {
  float y;
  asm("ex2.approx.ftz.f32 %0, %1;" : "=f"(y) : "f"(x));
  return y;
}
__device__ __forceinline__ uint64_t mk_desc(uint32_t addr, uint32_t lbo, uint32_t sbo) {
  return (uint64_t)((addr & 0x3FFFF) >> 4) | ((uint64_t)((lbo & 0x3FFFF) >> 4) << 16) |
         ((uint64_t)((sbo & 0x3FFFF) >> 4) << 32) | (1ull << 62);
}
__device__ __forceinline__ uint64_t mk_desc_o(uint32_t addr, uint32_t lbo, uint32_t sbo) {
  asm volatile("" : "+r"(addr));
  return mk_desc(addr, lbo, sbo);
}
template <int N> __device__ __forceinline__ void reg_fence(uint32_t (&d)[N]) {
#pragma unroll
  for (int i = 0; i < N; i++) asm volatile("" : "+r"(d[i])::"memory");
}
template <int N> __device__ __forceinline__ void reg_fence(float (&d)[N]) {
#pragma unroll
  for (int i = 0; i < N; i++) asm volatile("" : "+f"(d[i])::"memory");
}

template<int TB> __device__ __forceinline__ void wgmma_n144_ss(float (&d)[72], uint64_t da, uint64_t db, int sc) {
  asm volatile("{\n.reg .pred p;\nsetp.ne.b32 p, %74, 0;\n"
    "wgmma.mma_async.sync.aligned.m64n144k16.f32.bf16.bf16 {%0, %1, %2, %3, %4, %5, %6, %7, %8, %9, %10, %11, %12, %13, %14, %15, %16, %17, %18, %19, %20, %21, %22, %23, %24, %25, %26, %27, %28, %29, %30, %31, %32, %33, %34, %35, %36, %37, %38, %39, %40, %41, %42, %43, %44, %45, %46, %47, %48, %49, %50, %51, %52, %53, %54, %55, %56, %57, %58, %59, %60, %61, %62, %63, %64, %65, %66, %67, %68, %69, %70, %71}, %72, %73, p, 1, 1, 0, %75;\n}\n"
    : "+f"(d[0]), "+f"(d[1]), "+f"(d[2]), "+f"(d[3]), "+f"(d[4]), "+f"(d[5]), "+f"(d[6]), "+f"(d[7]), "+f"(d[8]), "+f"(d[9]), "+f"(d[10]), "+f"(d[11]), "+f"(d[12]), "+f"(d[13]), "+f"(d[14]), "+f"(d[15]), "+f"(d[16]), "+f"(d[17]), "+f"(d[18]), "+f"(d[19]), "+f"(d[20]), "+f"(d[21]), "+f"(d[22]), "+f"(d[23]), "+f"(d[24]), "+f"(d[25]), "+f"(d[26]), "+f"(d[27]), "+f"(d[28]), "+f"(d[29]), "+f"(d[30]), "+f"(d[31]), "+f"(d[32]), "+f"(d[33]), "+f"(d[34]), "+f"(d[35]), "+f"(d[36]), "+f"(d[37]), "+f"(d[38]), "+f"(d[39]), "+f"(d[40]), "+f"(d[41]), "+f"(d[42]), "+f"(d[43]), "+f"(d[44]), "+f"(d[45]), "+f"(d[46]), "+f"(d[47]), "+f"(d[48]), "+f"(d[49]), "+f"(d[50]), "+f"(d[51]), "+f"(d[52]), "+f"(d[53]), "+f"(d[54]), "+f"(d[55]), "+f"(d[56]), "+f"(d[57]), "+f"(d[58]), "+f"(d[59]), "+f"(d[60]), "+f"(d[61]), "+f"(d[62]), "+f"(d[63]), "+f"(d[64]), "+f"(d[65]), "+f"(d[66]), "+f"(d[67]), "+f"(d[68]), "+f"(d[69]), "+f"(d[70]), "+f"(d[71])
    : "l"(da), "l"(db), "r"(sc), "n"(TB));
}
template<int TB> __device__ __forceinline__ void wgmma_n192_rs(float (&d)[96], const uint32_t (&a)[4], uint64_t db, int sc) {
  asm volatile("{\n.reg .pred p;\nsetp.ne.b32 p, %101, 0;\n"
    "wgmma.mma_async.sync.aligned.m64n192k16.f32.bf16.bf16 {%0, %1, %2, %3, %4, %5, %6, %7, %8, %9, %10, %11, %12, %13, %14, %15, %16, %17, %18, %19, %20, %21, %22, %23, %24, %25, %26, %27, %28, %29, %30, %31, %32, %33, %34, %35, %36, %37, %38, %39, %40, %41, %42, %43, %44, %45, %46, %47, %48, %49, %50, %51, %52, %53, %54, %55, %56, %57, %58, %59, %60, %61, %62, %63, %64, %65, %66, %67, %68, %69, %70, %71, %72, %73, %74, %75, %76, %77, %78, %79, %80, %81, %82, %83, %84, %85, %86, %87, %88, %89, %90, %91, %92, %93, %94, %95}, {%96, %97, %98, %99}, %100, p, 1, 1, %102;\n}\n"
    : "+f"(d[0]), "+f"(d[1]), "+f"(d[2]), "+f"(d[3]), "+f"(d[4]), "+f"(d[5]), "+f"(d[6]), "+f"(d[7]), "+f"(d[8]), "+f"(d[9]), "+f"(d[10]), "+f"(d[11]), "+f"(d[12]), "+f"(d[13]), "+f"(d[14]), "+f"(d[15]), "+f"(d[16]), "+f"(d[17]), "+f"(d[18]), "+f"(d[19]), "+f"(d[20]), "+f"(d[21]), "+f"(d[22]), "+f"(d[23]), "+f"(d[24]), "+f"(d[25]), "+f"(d[26]), "+f"(d[27]), "+f"(d[28]), "+f"(d[29]), "+f"(d[30]), "+f"(d[31]), "+f"(d[32]), "+f"(d[33]), "+f"(d[34]), "+f"(d[35]), "+f"(d[36]), "+f"(d[37]), "+f"(d[38]), "+f"(d[39]), "+f"(d[40]), "+f"(d[41]), "+f"(d[42]), "+f"(d[43]), "+f"(d[44]), "+f"(d[45]), "+f"(d[46]), "+f"(d[47]), "+f"(d[48]), "+f"(d[49]), "+f"(d[50]), "+f"(d[51]), "+f"(d[52]), "+f"(d[53]), "+f"(d[54]), "+f"(d[55]), "+f"(d[56]), "+f"(d[57]), "+f"(d[58]), "+f"(d[59]), "+f"(d[60]), "+f"(d[61]), "+f"(d[62]), "+f"(d[63]), "+f"(d[64]), "+f"(d[65]), "+f"(d[66]), "+f"(d[67]), "+f"(d[68]), "+f"(d[69]), "+f"(d[70]), "+f"(d[71]), "+f"(d[72]), "+f"(d[73]), "+f"(d[74]), "+f"(d[75]), "+f"(d[76]), "+f"(d[77]), "+f"(d[78]), "+f"(d[79]), "+f"(d[80]), "+f"(d[81]), "+f"(d[82]), "+f"(d[83]), "+f"(d[84]), "+f"(d[85]), "+f"(d[86]), "+f"(d[87]), "+f"(d[88]), "+f"(d[89]), "+f"(d[90]), "+f"(d[91]), "+f"(d[92]), "+f"(d[93]), "+f"(d[94]), "+f"(d[95])
    : "r"(a[0]), "r"(a[1]), "r"(a[2]), "r"(a[3]), "l"(db), "r"(sc), "n"(TB));
}
template<int TB> __device__ __forceinline__ void wgmma_n64_rs(float (&d)[32], const uint32_t (&a)[4], uint64_t db, int sc) {
  asm volatile("{\n.reg .pred p;\nsetp.ne.b32 p, %37, 0;\n"
    "wgmma.mma_async.sync.aligned.m64n64k16.f32.bf16.bf16 {%0, %1, %2, %3, %4, %5, %6, %7, %8, %9, %10, %11, %12, %13, %14, %15, %16, %17, %18, %19, %20, %21, %22, %23, %24, %25, %26, %27, %28, %29, %30, %31}, {%32, %33, %34, %35}, %36, p, 1, 1, %38;\n}\n"
    : "+f"(d[0]), "+f"(d[1]), "+f"(d[2]), "+f"(d[3]), "+f"(d[4]), "+f"(d[5]), "+f"(d[6]), "+f"(d[7]), "+f"(d[8]), "+f"(d[9]), "+f"(d[10]), "+f"(d[11]), "+f"(d[12]), "+f"(d[13]), "+f"(d[14]), "+f"(d[15]), "+f"(d[16]), "+f"(d[17]), "+f"(d[18]), "+f"(d[19]), "+f"(d[20]), "+f"(d[21]), "+f"(d[22]), "+f"(d[23]), "+f"(d[24]), "+f"(d[25]), "+f"(d[26]), "+f"(d[27]), "+f"(d[28]), "+f"(d[29]), "+f"(d[30]), "+f"(d[31])
    : "r"(a[0]), "r"(a[1]), "r"(a[2]), "r"(a[3]), "l"(db), "r"(sc), "n"(TB));
}
template<int TB> __device__ __forceinline__ void wgmma_n64_ss(float (&d)[32], uint64_t da, uint64_t db, int sc) {
  asm volatile("{\n.reg .pred p;\nsetp.ne.b32 p, %34, 0;\n"
    "wgmma.mma_async.sync.aligned.m64n64k16.f32.bf16.bf16 {%0, %1, %2, %3, %4, %5, %6, %7, %8, %9, %10, %11, %12, %13, %14, %15, %16, %17, %18, %19, %20, %21, %22, %23, %24, %25, %26, %27, %28, %29, %30, %31}, %32, %33, p, 1, 1, 0, %35;\n}\n"
    : "+f"(d[0]), "+f"(d[1]), "+f"(d[2]), "+f"(d[3]), "+f"(d[4]), "+f"(d[5]), "+f"(d[6]), "+f"(d[7]), "+f"(d[8]), "+f"(d[9]), "+f"(d[10]), "+f"(d[11]), "+f"(d[12]), "+f"(d[13]), "+f"(d[14]), "+f"(d[15]), "+f"(d[16]), "+f"(d[17]), "+f"(d[18]), "+f"(d[19]), "+f"(d[20]), "+f"(d[21]), "+f"(d[22]), "+f"(d[23]), "+f"(d[24]), "+f"(d[25]), "+f"(d[26]), "+f"(d[27]), "+f"(d[28]), "+f"(d[29]), "+f"(d[30]), "+f"(d[31])
    : "l"(da), "l"(db), "r"(sc), "n"(TB));
}

struct FragAddr {
  uint32_t rowoff;
  uint32_t rx;
  uint32_t hi;
  __device__ __forceinline__ FragAddr(int warp_in_wg, int lane) {
    int row = 16 * warp_in_wg + (lane & 7) + ((lane >> 3) & 1) * 8;
    rowoff = row * 128;
    rx = row & 7;
    hi = lane >> 4;
  }
  __device__ __forceinline__ uint32_t at(uint32_t chunk_base, int kk4) const {
    return chunk_base + rowoff + ((((uint32_t)kk4 * 2 + hi) ^ rx) << 4);
  }
};

__device__ __forceinline__ void layernorm_frags(uint32_t (&f)[12][4]) {
  float s0[2] = {0.f, 0.f}, s1[2] = {0.f, 0.f}, q0[2] = {0.f, 0.f}, q1[2] = {0.f, 0.f};
#pragma unroll
  for (int k = 0; k < 12; k++) {
#pragma unroll
    for (int hf = 0; hf < 2; hf++) {
      const float a = bf_lo(f[k][2 * hf]), b = bf_hi(f[k][2 * hf]);
      const float c = bf_lo(f[k][2 * hf + 1]), d = bf_hi(f[k][2 * hf + 1]);
      s0[hf] += a + b; q0[hf] = fmaf(a, a, fmaf(b, b, q0[hf]));
      s1[hf] += c + d; q1[hf] = fmaf(c, c, fmaf(d, d, q1[hf]));
    }
  }
  float sa = s0[0] + s0[1], sb_ = s1[0] + s1[1], qa = q0[0] + q0[1], qb_ = q1[0] + q1[1];
  sa += __shfl_xor_sync(0xffffffffu, sa, 1); sb_ += __shfl_xor_sync(0xffffffffu, sb_, 1);
  qa += __shfl_xor_sync(0xffffffffu, qa, 1); qb_ += __shfl_xor_sync(0xffffffffu, qb_, 1);
  sa += __shfl_xor_sync(0xffffffffu, sa, 2); sb_ += __shfl_xor_sync(0xffffffffu, sb_, 2);
  qa += __shfl_xor_sync(0xffffffffu, qa, 2); qb_ += __shfl_xor_sync(0xffffffffu, qb_, 2);
  const float m0 = sa * (1.f / 192.f), m1 = sb_ * (1.f / 192.f);
  const float v0 = fmaxf(fmaf(-m0, m0, qa * (1.f / 192.f)), 0.f), v1 = fmaxf(fmaf(-m1, m1, qb_ * (1.f / 192.f)), 0.f);
  const float r0 = rsqrtf(v0 + 1e-5f), r1 = rsqrtf(v1 + 1e-5f);
  const float c0 = -m0 * r0, c1 = -m1 * r1;
#pragma unroll
  for (int k = 0; k < 12; k++) {
    f[k][0] = pack_bf16(fmaf(bf_lo(f[k][0]), r0, c0), fmaf(bf_hi(f[k][0]), r0, c0));
    f[k][2] = pack_bf16(fmaf(bf_lo(f[k][2]), r0, c0), fmaf(bf_hi(f[k][2]), r0, c0));
    f[k][1] = pack_bf16(fmaf(bf_lo(f[k][1]), r1, c1), fmaf(bf_hi(f[k][1]), r1, c1));
    f[k][3] = pack_bf16(fmaf(bf_lo(f[k][3]), r1, c1), fmaf(bf_hi(f[k][3]), r1, c1));
  }
}

#define XDELAY 800
constexpr int A_NST = 5;
constexpr int A_XS = 0;
constexpr int A_VB = 49152;
constexpr int A_W = 98304;
constexpr int A_BAR = A_W + A_NST * 24576;
constexpr int A_SMEM = A_BAR + 256 + 1024;
constexpr int A_FOLD = 36;

__device__ __forceinline__ void a_issue(float (&acc)[32], const uint32_t (&af)[12][4], uint32_t sb, int s) {
  const int st = s % A_NST;
  mbar_wait(sb + A_BAR + st * 8, (s / A_NST) & 1);
  const uint64_t wd = mk_desc_o(sb + A_W + st * 24576, 8192, 1024);
  wg_fence();
#pragma unroll
  for (int kk = 0; kk < 12; kk++) wgmma_n64_rs<1>(acc, af[kk], wd + kk * 128, kk > 0);
  wg_commit();
}
__device__ __forceinline__ void a_release(uint32_t sb, int s, int lane) {
  if (lane == 0) mbar_arrive(sb + A_BAR + 64 + (s % A_NST) * 8);
}
__device__ __forceinline__ void cvt_frags(uint32_t (*dst)[4], const float (&acc)[32]) {
#pragma unroll
  for (int k = 0; k < 4; k++) {
    dst[k][0] = pack_bf16(acc[8 * k + 0], acc[8 * k + 1]);
    dst[k][1] = pack_bf16(acc[8 * k + 2], acc[8 * k + 3]);
    dst[k][2] = pack_bf16(acc[8 * k + 4], acc[8 * k + 5]);
    dst[k][3] = pack_bf16(acc[8 * k + 6], acc[8 * k + 7]);
  }
}
__device__ __forceinline__ void store_chunk(const float (&acc)[32], uint32_t chunk_base, const FragAddr& fa) {
  uint32_t t[4][4];
  cvt_frags(t, acc);
#pragma unroll
  for (int k = 0; k < 4; k++) stsm_x4(fa.at(chunk_base, k), t[k]);
}
__device__ __forceinline__ void resid_chunk(uint32_t (*dst)[4], const float* acc, float s0, float s1, uint32_t chunk_base,
                                            const FragAddr& fa) {
#pragma unroll
  for (int k = 0; k < 4; k++) {
    uint32_t x[4];
    ldsm_x4(x, fa.at(chunk_base, k));
    uint32_t o[4];
    o[0] = pack_bf16(fmaf(acc[8 * k + 0], s0, bf_lo(x[0])), fmaf(acc[8 * k + 1], s0, bf_hi(x[0])));
    o[1] = pack_bf16(fmaf(acc[8 * k + 2], s1, bf_lo(x[1])), fmaf(acc[8 * k + 3], s1, bf_hi(x[1])));
    o[2] = pack_bf16(fmaf(acc[8 * k + 4], s0, bf_lo(x[2])), fmaf(acc[8 * k + 5], s0, bf_hi(x[2])));
    o[3] = pack_bf16(fmaf(acc[8 * k + 6], s1, bf_lo(x[3])), fmaf(acc[8 * k + 7], s1, bf_hi(x[3])));
    stsm_x4(fa.at(chunk_base, k), o);
    if (dst) { dst[k][0] = o[0]; dst[k][1] = o[1]; dst[k][2] = o[2]; dst[k][3] = o[3]; }
  }
}

__global__ void __launch_bounds__(384, 1)
kernelA(const __grid_constant__ CUtensorMap tm_x, const __grid_constant__ CUtensorMap tm_wq64t,
        const __grid_constant__ CUtensorMap tm_wot, const __grid_constant__ CUtensorMap tm_wq64s,
        const __grid_constant__ CUtensorMap tm_wos, const __grid_constant__ CUtensorMap tm_wf,
        const __grid_constant__ CUtensorMap tm_x1, const __grid_constant__ CUtensorMap tm_qkv) {
  extern __shared__ uint8_t smem_raw[];
  const uint32_t sb = (smem_u32(smem_raw) + 1023) & ~1023u;
  const int tid = threadIdx.x, warp = tid >> 5, lane = tid & 31;
  const bool is_fold = blockIdx.x < A_FOLD;
  const int blk = blockIdx.x - A_FOLD;
  if (tid == 256) {
    for (int i = 0; i < A_NST; i++) { mbar_init(sb + A_BAR + i * 8, 1); mbar_init(sb + A_BAR + 64 + i * 8, 8); }
    mbar_init(sb + A_BAR + 128, 1); mbar_init(sb + A_BAR + 136, 1);
    asm volatile("fence.mbarrier_init.release.cluster;" ::: "memory");
    if (!is_fold) {
      __nanosleep(XDELAY);
      for (int w = 0; w < 2; w++) {
        const uint32_t bar = sb + A_BAR + 128 + w * 8;
        mbar_expect_tx(bar, 3 * 63 * 128);
        for (int c = 0; c < 3; c++)
          tma_load_3d(sb + A_XS + w * 24576 + c * 8192, &tm_x, bar, c * 64, (blk * 2 + w) * 9, 0);
      }
    } else {
      const int mat = blockIdx.x / 9, rs = (blockIdx.x % 9) / 3, cs = blockIdx.x % 3;
      const CUtensorMap* mq = (mat < 2) ? &tm_wq64t : &tm_wq64s;
      const CUtensorMap* mo = (mat < 2) ? &tm_wot : &tm_wos;
      const uint32_t bar = sb + A_BAR + 128;
      mbar_expect_tx(bar, 2 * 24576);
      for (int c = 0; c < 3; c++) tma_load_2d(sb + c * 8192, mq, bar, ((mat & 1) ? 384 : 0) + c * 64, rs * 64);
      if (mat & 1) tma_load_2d(sb + 24576, mo, bar, cs * 64, 0);
      else for (int c = 0; c < 3; c++) tma_load_2d(sb + 24576 + c * 8192, mq, bar, 192 + c * 64, cs * 64);
    }
  }
  asm volatile("griddepcontrol.launch_dependents;" ::: "memory");
  if (blockIdx.x == 0 && tid < 128) g_flag[tid] = 0;
  if (!is_fold && tid < 48) {
    uint32_t a = sb + A_XS + (tid >> 3) * 8192 + 63 * 128 + (tid & 7) * 16;
    asm volatile("st.shared.v4.b32 [%0], {%1,%1,%1,%1};" ::"r"(a), "r"(0) : "memory");
  }
  __syncthreads();

  if (warp >= 8) {
    asm volatile("setmaxnreg.dec.sync.aligned.u32 24;");
    if (warp == 8 && lane == 0 && !is_fold) {
      for (int s = 0; s < 12; s++) {
        const int st = s % A_NST;
        const int g = s / 3;
        const int mat = (g == 0) ? 1 : (g == 1) ? 0 : g;
        if (s % 3 == 0) {
          uint32_t n = 0, v;
          do {
            asm volatile("ld.acquire.gpu.global.u32 %0, [%1];" : "=r"(v) : "l"(&g_wflag[mat]) : "memory");
          } while (v < 9u && ++n < (1u << 22));
          asm volatile("fence.proxy.async;" ::: "memory");
        }
        if (s >= A_NST) mbar_wait(sb + A_BAR + 64 + st * 8, ((s / A_NST) - 1) & 1);
        mbar_expect_tx(sb + A_BAR + st * 8, 24576);
        tma_load_2d(sb + A_W + st * 24576, &tm_wf, sb + A_BAR + st * 8, (mat & 1) * 192 + (s % 3) * 64, (mat >> 1) * 192);
      }
    }
    return;
  }

  asm volatile("setmaxnreg.inc.sync.aligned.u32 240;");
  const int wg = warp >> 2, wq = warp & 3;

  if (is_fold) {
    if (wg == 0) {
      const int mat = blockIdx.x / 9, rs = (blockIdx.x % 9) / 3, cs = blockIdx.x % 3;
      float d[32];
      mbar_wait(sb + A_BAR + 128, 0);
      const uint64_t ad = mk_desc_o(sb, 16, 1024);
      if (mat & 1) {
        const uint64_t bd = mk_desc_o(sb + 24576, 8192, 1024);
        wg_fence();
#pragma unroll
        for (int kk = 0; kk < 12; kk++) wgmma_n64_ss<1>(d, ad + (kk >> 2) * 512 + (kk & 3) * 2, bd + kk * 128, kk > 0);
        wg_commit();
      } else {
        const uint64_t bd = mk_desc_o(sb + 24576, 16, 1024);
        wg_fence();
#pragma unroll
        for (int kk = 0; kk < 12; kk++)
          wgmma_n64_ss<0>(d, ad + (kk >> 2) * 512 + (kk & 3) * 2, bd + (kk >> 2) * 512 + (kk & 3) * 2, kk > 0);
        wg_commit();
      }
      wg_wait<0>(); reg_fence(d);
      const int r0 = rs * 64 + wq * 16 + (lane >> 2);
      uint32_t* dst = reinterpret_cast<uint32_t*>(g_wf + ((size_t)(mat >> 1) * 192 + r0) * 384 + (mat & 1) * 192 + cs * 64 + (lane & 3) * 2);
#pragma unroll
      for (int j = 0; j < 8; j++) {
        dst[j * 4] = pack_bf16(d[4 * j], d[4 * j + 1]);
        dst[8 * 192 + j * 4] = pack_bf16(d[4 * j + 2], d[4 * j + 3]);
      }
      asm volatile("fence.proxy.async;" ::: "memory");
      named_bar(1, 128);
      if (tid == 0) { __threadfence(); atomicAdd(&g_wflag[mat], 1u); }
    }
    return;
  }

  const int n0 = (blk * 2 + wg) * 9;
  const FragAddr fa(wq, lane);
  const uint32_t xs = sb + A_XS + wg * 24576, vb = sb + A_VB + wg * 24576;
  const int barid = 1 + wg;
  const bool elected = (tid & 127) == 0;

  uint32_t h[12][4];
  TS(0, 0);
  mbar_wait(sb + A_BAR + 128 + wg * 8, 0);
  TS(0, 1);
#pragma unroll
  for (int k = 0; k < 12; k++) ldsm_x4(h[k], fa.at(xs + (k >> 2) * 8192, k & 3));
  layernorm_frags(h);
#pragma unroll
  for (int k = 0; k < 12; k++) stsm_x4(fa.at(xs + (k >> 2) * 8192, k & 3), h[k]);

  float acc0[32], acc1[32];
  uint32_t qf[12][4];
  TS(0, 2);
  a_issue(acc0, h, sb, 0);
  TS(0, 3);
  a_issue(acc1, h, sb, 1); wg_wait<1>(); reg_fence(acc0); a_release(sb, 0, lane); store_chunk(acc0, vb, fa);
  a_issue(acc0, h, sb, 2); wg_wait<1>(); reg_fence(acc1); a_release(sb, 1, lane); store_chunk(acc1, vb + 8192, fa);
  a_issue(acc1, h, sb, 3); wg_wait<1>(); reg_fence(acc0); a_release(sb, 2, lane); store_chunk(acc0, vb + 16384, fa);
  fence_proxy_async();
  named_bar(barid, 128);
  a_issue(acc0, h, sb, 4); wg_wait<1>(); reg_fence(acc1); a_release(sb, 3, lane); cvt_frags(&qf[0], acc1);
  a_issue(acc1, h, sb, 5); wg_wait<1>(); reg_fence(acc0); a_release(sb, 4, lane); cvt_frags(&qf[4], acc0);
  wg_wait<0>(); reg_fence(acc1); a_release(sb, 5, lane); cvt_frags(&qf[8], acc1);
  TS(0, 4);
  {
    const uint64_t kd = mk_desc_o(xs, 16, 1024);
    wg_fence();
#pragma unroll
    for (int kk = 0; kk < 12; kk++) wgmma_n64_rs<0>(acc0, qf[kk], kd + (kk >> 2) * 512 + (kk & 3) * 2, kk > 0);
    wg_commit();
    wg_wait<0>(); reg_fence(acc0);
  }
  named_bar(barid, 128);
  if (elected) {
    const uint32_t bar = sb + A_BAR + 128 + wg * 8;
    mbar_expect_tx(bar, 3 * 63 * 128);
    for (int c = 0; c < 3; c++) tma_load_3d(xs + c * 8192, &tm_x, bar, c * 64, n0, 0);
  }
  uint32_t pf[4][4];
  {
    const int r0 = 16 * wq + (lane >> 2), r1 = r0 + 8;
    const unsigned long long MB = 0x0040201008040201ull;
    const unsigned long long mk0 = (MB << (r0 % 9)) >> (2 * (lane & 3));
    const unsigned long long mk1 = (MB << (r1 % 9)) >> (2 * (lane & 3));
    const float cs = 0.07216878364870322f * 1.4426950408889634f;
    float mx0 = -INFINITY, mx1 = -INFINITY;
#pragma unroll
    for (int j = 0; j < 8; j++) {
#pragma unroll
      for (int e = 0; e < 2; e++) {
        bool v0 = (mk0 >> (8 * j + e)) & 1, v1 = (mk1 >> (8 * j + e)) & 1;
        acc0[4 * j + e] = v0 ? acc0[4 * j + e] * cs : -INFINITY;
        acc0[4 * j + 2 + e] = v1 ? acc0[4 * j + 2 + e] * cs : -INFINITY;
        mx0 = fmaxf(mx0, acc0[4 * j + e]);
        mx1 = fmaxf(mx1, acc0[4 * j + 2 + e]);
      }
    }
    mx0 = fmaxf(mx0, __shfl_xor_sync(0xffffffffu, mx0, 1)); mx0 = fmaxf(mx0, __shfl_xor_sync(0xffffffffu, mx0, 2));
    mx1 = fmaxf(mx1, __shfl_xor_sync(0xffffffffu, mx1, 1)); mx1 = fmaxf(mx1, __shfl_xor_sync(0xffffffffu, mx1, 2));
    float l0 = 0.f, l1 = 0.f;
#pragma unroll
    for (int j = 0; j < 8; j++) {
#pragma unroll
      for (int e = 0; e < 2; e++) {
        acc0[4 * j + e] = ex2(acc0[4 * j + e] - mx0); l0 += acc0[4 * j + e];
        acc0[4 * j + 2 + e] = ex2(acc0[4 * j + 2 + e] - mx1); l1 += acc0[4 * j + 2 + e];
      }
    }
    l0 += __shfl_xor_sync(0xffffffffu, l0, 1); l0 += __shfl_xor_sync(0xffffffffu, l0, 2);
    l1 += __shfl_xor_sync(0xffffffffu, l1, 1); l1 += __shfl_xor_sync(0xffffffffu, l1, 2);
    const float i0 = 1.f / l0, i1 = 1.f / l1;
#pragma unroll
    for (int j = 0; j < 8; j++) {
      acc0[4 * j] *= i0; acc0[4 * j + 1] *= i0; acc0[4 * j + 2] *= i1; acc0[4 * j + 3] *= i1;
    }
    cvt_frags(pf, acc0);
  }
  TS(0, 5);
  {
    float oacc[96];
    const uint64_t vd = mk_desc_o(vb, 8192, 1024);
    wg_fence();
#pragma unroll
    for (int kk = 0; kk < 4; kk++) wgmma_n192_rs<1>(oacc, pf[kk], vd + kk * 128, kk > 0);
    wg_commit();
    wg_wait<0>(); reg_fence(oacc);
    TS(0, 6);
    mbar_wait(sb + A_BAR + 128 + wg * 8, 1);
#pragma unroll
    for (int c = 0; c < 3; c++) resid_chunk(&h[4 * c], &oacc[32 * c], 1.f, 1.f, xs + c * 8192, fa);
  }
  TS(0, 7);
  fence_proxy_async();
  named_bar(barid, 128);
  if (elected) {
    for (int c = 0; c < 3; c++) tma_store_3d(&tm_x1, xs + c * 8192, c * 64, n0, 0);
    bulk_commit();
  }
  layernorm_frags(h);
#pragma unroll
  for (int k = 0; k < 12; k++) stsm_x4(fa.at(vb + (k >> 2) * 8192, k & 3), h[k]);
  TS(0, 8);
  a_issue(acc0, h, sb, 6);
  a_issue(acc1, h, sb, 7);
  fence_proxy_async();
  if (elected) bulk_wait_read0();
  named_bar(barid, 128);
  if (elected) {
    for (int c = 0; c < 3; c++) tma_store_3d(&tm_qkv, vb + c * 8192, 192 + c * 64, n0, 0);
    bulk_commit();
  }
  wg_wait<1>(); reg_fence(acc0); a_release(sb, 6, lane); store_chunk(acc0, xs, fa);
  a_issue(acc0, h, sb, 8); wg_wait<1>(); reg_fence(acc1); store_chunk(acc1, xs + 8192, fa);
  a_issue(acc1, h, sb, 9); wg_wait<1>(); reg_fence(acc0); store_chunk(acc0, xs + 16384, fa);
  a_issue(acc0, h, sb, 10);
  fence_proxy_async();
  if (elected) bulk_wait_read0();
  named_bar(barid, 128);
  if (elected) {
    for (int c = 0; c < 3; c++) tma_store_3d(&tm_qkv, xs + c * 8192, c * 64, n0, 0);
    bulk_commit();
  }
  {
    const int rr = wq * 16 + (lane >> 3);
    __nv_bfloat16* gdst = g_qkv + 384 + (lane & 7) * 8;
    auto flush = [&](uint32_t cb, int c) {
      __syncwarp();
#pragma unroll
      for (int i = 0; i < 4; i++) {
        const int r = rr + 4 * i;
        uint4 v;
        asm volatile("ld.shared.v4.b32 {%0,%1,%2,%3}, [%4];" : "=r"(v.x), "=r"(v.y), "=r"(v.z), "=r"(v.w)
                     : "r"(cb + r * 128 + (((lane & 7) ^ (r & 7)) << 4)) : "memory");
        const int t = r / 9, loc = r - t * 9;
        if (r < 63) *reinterpret_cast<uint4*>(gdst + ((size_t)t * NL + n0 + loc) * 576 + c * 64) = v;
      }
    };
    wg_wait<1>(); reg_fence(acc1); store_chunk(acc1, vb, fa);
    a_issue(acc1, h, sb, 11);
    flush(vb, 0);
    wg_wait<1>(); reg_fence(acc0); store_chunk(acc0, vb + 8192, fa);
    flush(vb + 8192, 1);
    wg_wait<0>(); reg_fence(acc1); store_chunk(acc1, vb + 16384, fa);
    flush(vb + 16384, 2);
  }
  TS(0, 9);
  if (elected) bulk_wait_read0();
  TS(0, 10);
}

constexpr int B_GRID = 132;
constexpr int B_SLOT = 55296;
constexpr int B_Q = 0;
constexpr int B_KV = 49152;
constexpr int B_BAR = B_KV + 3 * B_SLOT;
constexpr int B_SMEM = B_BAR + 256 + 1024;

__device__ __forceinline__ void bar_arrive(int id, int nthreads) {
  asm volatile("bar.arrive %0, %1;" ::"r"(id), "r"(nthreads) : "memory");
}
__device__ __forceinline__ void b_segment(int sg, int& tile, int& k0, int& k1) {
  const int grp = blockIdx.x / 12, ci = blockIdx.x - grp * 12;
  if (ci < 7) { tile = grp * 7 + ci; k0 = 3; k1 = 9; }
  else {
    const int hh = ci - 7;
    tile = grp * 7 + ((0x54210 >> (4 * hh)) & 15) + sg;
    k0 = sg ? 0 : ((0x10210 >> (4 * hh)) & 15);
    k1 = sg ? ((0x31321 >> (4 * hh)) & 15) : 3;
  }
}

__global__ void __launch_bounds__(384, 1)
kernelB(const __grid_constant__ CUtensorMap tm_q, const __grid_constant__ CUtensorMap tm_kv,
        const __grid_constant__ CUtensorMap tm_x1, const __grid_constant__ CUtensorMap tm_out) {
  extern __shared__ uint8_t smem_raw[];
  const uint32_t sb = (smem_u32(smem_raw) + 1023) & ~1023u;
  const int tid = threadIdx.x, warp = tid >> 5, lane = tid & 31;
  const uint32_t bF = sb + B_BAR, bE = sb + B_BAR + 32, bQF = sb + B_BAR + 64, bQE = sb + B_BAR + 72;
  if (tid == 0) {
    for (int i = 0; i < 3; i++) { mbar_init(bF + i * 8, 1); mbar_init(bE + i * 8, 8); }
    mbar_init(bQF, 1); mbar_init(bQE, 8);
    asm volatile("fence.mbarrier_init.release.cluster;" ::: "memory");
    prefetch_tmap(&tm_q); prefetch_tmap(&tm_kv); prefetch_tmap(&tm_x1); prefetch_tmap(&tm_out);
  }
  __syncthreads();
  asm volatile("griddepcontrol.wait;" ::: "memory");
  const int grp = blockIdx.x / 12, ci = blockIdx.x - grp * 12;
  const bool owner = ci < 7;
  const int nseg = owner ? 1 : 2;

  if (warp >= 8) {
    asm volatile("setmaxnreg.dec.sync.aligned.u32 24;");
    if (warp == 8 && lane == 0) {
      if (blockIdx.x == 0) { g_wflag[0] = 0; g_wflag[1] = 0; g_wflag[2] = 0; g_wflag[3] = 0; }
      int it = 0;
      for (int sg = 0; sg < nseg; sg++) {
        int tile, k0, k1;
        b_segment(sg, tile, k0, k1);
        const int t = tile / 11, qt = tile - t * 11;
        if (sg > 0) mbar_wait(bQE, 0);
        mbar_expect_tx(bQF, 49152);
        for (int c = 0; c < 3; c++) tma_load_3d(sb + B_Q + c * 16384, &tm_q, bQF, c * 64, qt * 128, t);
        const int n = k1 - k0;
        for (int e = 0; e < 2 * n; e++) {
          const int sl = it % 3;
          if (it >= 3) mbar_wait(bE + sl * 8, ((it / 3) - 1) & 1);
          mbar_expect_tx(bF + sl * 8, B_SLOT);
          for (int c = 0; c < 3; c++)
            tma_load_3d(sb + B_KV + sl * B_SLOT + c * 18432, &tm_kv, bF + sl * 8, 192 + (e & 1) * 192 + c * 64, (k0 + (e >> 1)) * 144, t);
          it++;
        }
      }
      if (owner) {
        const int tile = grp * 7 + ci;
        const int t = tile / 11, qt = tile - t * 11;
        mbar_wait(bQE, 0);
        mbar_expect_tx(bQF, 49152);
        for (int c = 0; c < 3; c++) tma_load_3d(sb + B_Q + c * 16384, &tm_x1, bQF, c * 64, qt * 128, t);
      }
    } else if ((warp == 9 || warp == 10) && !owner) {
      for (int sg = 0; sg < 2; sg++) {
        named_bar(5 + (warp - 9), 160);
        if (lane == 0) {
          __threadfence();
          atomicAdd(&g_flag[(grp * 5 + (ci - 7)) * 2 + sg], 1u);
        }
        __syncwarp();
      }
    }
    return;
  }

  asm volatile("setmaxnreg.inc.sync.aligned.u32 240;");
  const int wg = warp >> 2, wq = warp & 3;
  const int wtid = tid & 127;
  const float cs = 0.07216878364870322f * 1.4426950408889634f;
  float oacc[96], sacc[72];
  uint32_t pf[9][4];
  float m0, m1, l0, l1;
  int it = 0;
  const uint32_t qb = sb + B_Q + wg * 8192;
  if (wg == 1) bar_arrive(3, 256);
  TS(1, 0);
  int tsi = 1;

  auto issue_qk = [&](int slot) {
    const uint64_t kd = mk_desc_o(sb + B_KV + slot * B_SLOT, 16, 1024);
    const uint64_t qd = mk_desc_o(qb, 16, 1024);
#pragma unroll
    for (int kk = 0; kk < 12; kk++)
      wgmma_n144_ss<0>(sacc, qd + (kk >> 2) * 1024 + (kk & 3) * 2, kd + (kk >> 2) * 1152 + (kk & 3) * 2, kk > 0);
    wg_commit();
  };
  auto issue_pv = [&](int slot, int accum) {
    const uint64_t vd = mk_desc_o(sb + B_KV + slot * B_SLOT, 18432, 1024);
#pragma unroll
    for (int kk = 0; kk < 9; kk++) wgmma_n192_rs<1>(oacc, pf[kk], vd + kk * 128, kk > 0 ? 1 : accum);
    wg_commit();
  };
  auto softmax = [&](bool first) {
    float t0[4], t1[4];
#pragma unroll
    for (int q = 0; q < 4; q++) {
      t0[q] = fmaxf(sacc[4 * q], sacc[4 * q + 1]);
      t1[q] = fmaxf(sacc[4 * q + 2], sacc[4 * q + 3]);
    }
#pragma unroll
    for (int j = 4; j < 18; j++) {
      t0[j & 3] = fmaxf(t0[j & 3], fmaxf(sacc[4 * j], sacc[4 * j + 1]));
      t1[j & 3] = fmaxf(t1[j & 3], fmaxf(sacc[4 * j + 2], sacc[4 * j + 3]));
    }
    float mx0 = fmaxf(fmaxf(t0[0], t0[1]), fmaxf(t0[2], t0[3]));
    float mx1 = fmaxf(fmaxf(t1[0], t1[1]), fmaxf(t1[2], t1[3]));
    mx0 = fmaxf(mx0, __shfl_xor_sync(0xffffffffu, mx0, 1)); mx1 = fmaxf(mx1, __shfl_xor_sync(0xffffffffu, mx1, 1));
    mx0 = fmaxf(mx0, __shfl_xor_sync(0xffffffffu, mx0, 2)); mx1 = fmaxf(mx1, __shfl_xor_sync(0xffffffffu, mx1, 2));
    if (first) {
      m0 = mx0; m1 = mx1; l0 = 0.f; l1 = 0.f;
    } else {
      const bool need = !((mx0 - m0) * cs <= 8.f) || !((mx1 - m1) * cs <= 8.f);
      if (__any_sync(0xffffffffu, need)) {
        mx0 = fmaxf(mx0, m0); mx1 = fmaxf(mx1, m1);
        const float a0 = ex2((m0 - mx0) * cs), a1 = ex2((m1 - mx1) * cs);
        m0 = mx0; m1 = mx1;
        l0 *= a0; l1 *= a1;
#pragma unroll
        for (int i = 0; i < 24; i++) {
          oacc[4 * i] *= a0; oacc[4 * i + 1] *= a0; oacc[4 * i + 2] *= a1; oacc[4 * i + 3] *= a1;
        }
      }
    }
    const float mc0 = m0 * cs, mc1 = m1 * cs;
#pragma unroll
    for (int q = 0; q < 4; q++) { t0[q] = 0.f; t1[q] = 0.f; }
#pragma unroll
    for (int k = 0; k < 9; k++) {
      float p[8];
#pragma unroll
      for (int e = 0; e < 8; e++) p[e] = ex2(fmaf(sacc[8 * k + e], cs, (e & 2) ? -mc1 : -mc0));
      t0[0] += p[0]; t0[1] += p[1]; t0[2] += p[4]; t0[3] += p[5];
      t1[0] += p[2]; t1[1] += p[3]; t1[2] += p[6]; t1[3] += p[7];
      pf[k][0] = pack_bf16(p[0], p[1]); pf[k][1] = pack_bf16(p[2], p[3]);
      pf[k][2] = pack_bf16(p[4], p[5]); pf[k][3] = pack_bf16(p[6], p[7]);
    }
    l0 += (t0[0] + t0[1]) + (t0[2] + t0[3]);
    l1 += (t1[0] + t1[1]) + (t1[2] + t1[3]);
  };

  for (int sg = 0; sg < nseg; sg++) {
    int n;
    { int tile, k0, k1; b_segment(sg, tile, k0, k1); n = k1 - k0; }
    mbar_wait(bQF, sg & 1);
    {
      const int sl = it % 3;
      mbar_wait(bF + sl * 8, (it / 3) & 1);
      named_bar(3 + wg, 256);
      wg_fence();
      issue_qk(sl);
      bar_arrive(3 + (wg ^ 1), 256);
      wg_wait<0>(); reg_fence(sacc);
      if (lane == 0) { mbar_arrive(bE + sl * 8); if (n == 1) mbar_arrive(bQE); }
      it++;
      softmax(true);
    }
    TS(1, tsi); tsi++;
    for (int j = 1; j < n; j++) {
      const int slv = it % 3, slk = (it + 1) % 3;
      mbar_wait(bF + slv * 8, (it / 3) & 1);
      named_bar(3 + wg, 256);
      wg_fence();
      issue_pv(slv, j > 1);
      mbar_wait(bF + slk * 8, ((it + 1) / 3) & 1);
      issue_qk(slk);
      bar_arrive(3 + (wg ^ 1), 256);
      wg_wait<1>(); reg_fence(oacc);
      if (lane == 0) mbar_arrive(bE + slv * 8);
      wg_wait<0>(); reg_fence(sacc);
      if (lane == 0) { mbar_arrive(bE + slk * 8); if (j == n - 1) mbar_arrive(bQE); }
      it += 2;
      softmax(false);
      TS(1, tsi); tsi++;
    }
    {
      const int sl = it % 3;
      mbar_wait(bF + sl * 8, (it / 3) & 1);
      named_bar(3 + wg, 256);
      wg_fence();
      issue_pv(sl, n > 1);
      if (!(wg == 1 && sg == nseg - 1)) bar_arrive(3 + (wg ^ 1), 256);
      wg_wait<0>(); reg_fence(oacc);
      if (lane == 0) mbar_arrive(bE + sl * 8);
      it++;
    }
    TS(1, tsi); tsi++;
    if (!owner) {
      const int slot = (grp * 5 + (ci - 7)) * 2 + sg;
      uint4* dst = g_part + (size_t)(slot * 2 + wg) * 13 * 128 + wtid;
#pragma unroll
      for (int i = 0; i < 12; i++)
        dst[i * 128] = make_uint4(pack_bf16(oacc[8 * i], oacc[8 * i + 1]), pack_bf16(oacc[8 * i + 2], oacc[8 * i + 3]),
                                  pack_bf16(oacc[8 * i + 4], oacc[8 * i + 5]), pack_bf16(oacc[8 * i + 6], oacc[8 * i + 7]));
      dst[12 * 128] = make_uint4(__float_as_uint(m0), __float_as_uint(m1), __float_as_uint(l0), __float_as_uint(l1));
      bar_arrive(5 + wg, 160);
      TS(1, tsi); tsi++;
    }
  }
  if (!owner) return;

  {
    const int first = (0x9765310 >> (4 * ci)) & 15, cnt = (0x1211221 >> (4 * ci)) & 15;
    const int slot0 = grp * 10 + first;
    if (wtid < cnt) {
      uint32_t n = 0, v;
      do {
        asm volatile("ld.acquire.gpu.global.u32 %0, [%1];" : "=r"(v) : "l"(&g_flag[slot0 + wtid]) : "memory");
      } while (v < 2u && ++n < (1u << 22));
    }
    named_bar(1 + wg, 128);
    uint4 pv[2][13];
#pragma unroll
    for (int q = 0; q < 2; q++) {
      if (q < cnt) {
        const uint4* src = g_part + (size_t)((slot0 + q) * 2 + wg) * 13 * 128 + wtid;
#pragma unroll
        for (int i = 0; i < 13; i++) pv[q][i] = __ldcg(src + i * 128);
      }
    }
#pragma unroll
    for (int q = 0; q < 2; q++) {
      if (q < cnt) {
        const float pm0 = __uint_as_float(pv[q][12].x), pm1 = __uint_as_float(pv[q][12].y);
        const float mx0 = fmaxf(m0, pm0), mx1 = fmaxf(m1, pm1);
        const float a0 = ex2((m0 - mx0) * cs), a1 = ex2((m1 - mx1) * cs);
        const float b0 = ex2((pm0 - mx0) * cs), b1 = ex2((pm1 - mx1) * cs);
        m0 = mx0; m1 = mx1;
        l0 = l0 * a0 + __uint_as_float(pv[q][12].z) * b0; l1 = l1 * a1 + __uint_as_float(pv[q][12].w) * b1;
#pragma unroll
        for (int i = 0; i < 12; i++) {
          const uint4 v = pv[q][i];
          oacc[8 * i + 0] = oacc[8 * i + 0] * a0 + bf_lo(v.x) * b0; oacc[8 * i + 1] = oacc[8 * i + 1] * a0 + bf_hi(v.x) * b0;
          oacc[8 * i + 2] = oacc[8 * i + 2] * a1 + bf_lo(v.y) * b1; oacc[8 * i + 3] = oacc[8 * i + 3] * a1 + bf_hi(v.y) * b1;
          oacc[8 * i + 4] = oacc[8 * i + 4] * a0 + bf_lo(v.z) * b0; oacc[8 * i + 5] = oacc[8 * i + 5] * a0 + bf_hi(v.z) * b0;
          oacc[8 * i + 6] = oacc[8 * i + 6] * a1 + bf_lo(v.w) * b1; oacc[8 * i + 7] = oacc[8 * i + 7] * a1 + bf_hi(v.w) * b1;
        }
      }
    }
  }
  TS(1, 21);
  l0 += __shfl_xor_sync(0xffffffffu, l0, 1); l0 += __shfl_xor_sync(0xffffffffu, l0, 2);
  l1 += __shfl_xor_sync(0xffffffffu, l1, 1); l1 += __shfl_xor_sync(0xffffffffu, l1, 2);
  const float i0 = 1.f / l0, i1 = 1.f / l1;
  mbar_wait(bQF, 1);
  const FragAddr fa(wq, lane);
#pragma unroll
  for (int c = 0; c < 3; c++) resid_chunk(nullptr, &oacc[32 * c], i0, i1, qb + c * 16384, fa);
  fence_proxy_async();
  named_bar(1 + wg, 128);
  TS(1, 22);
  if (wtid == 0) {
    const int tile = grp * 7 + ci;
    const int t = tile / 11, qt = tile - t * 11;
    if (qt * 128 + wg * 64 < NL) {
      for (int c = 0; c < 3; c++) tma_store_3d(&tm_out, qb + c * 16384, c * 64, qt * 128 + wg * 64, t);
      bulk_commit();
      bulk_wait_read0();
    }
  }
  TS(1, 23);
}

typedef CUresult (*EncodeFn)(CUtensorMap*, CUtensorMapDataType, cuuint32_t, void*, const cuuint64_t*, const cuuint64_t*,
                             const cuuint32_t*, const cuuint32_t*, CUtensorMapInterleave, CUtensorMapSwizzle,
                             CUtensorMapL2promotion, CUtensorMapFloatOOBfill);

void make_map(EncodeFn enc, CUtensorMap* m, const void* ptr, int rank, const uint64_t* dims, const uint32_t* box) {
  cuuint64_t gd[3], gs[2];
  cuuint32_t bx[3], es[3] = {1, 1, 1};
  uint64_t stride = 2;
  for (int i = 0; i < rank; i++) {
    gd[i] = dims[i]; bx[i] = box[i];
    stride *= dims[i];
    if (i < rank - 1) gs[i] = stride;
  }
  enc(m, CU_TENSOR_MAP_DATA_TYPE_BFLOAT16, rank, const_cast<void*>(ptr), gd, gs, bx, es, CU_TENSOR_MAP_INTERLEAVE_NONE,
      CU_TENSOR_MAP_SWIZZLE_128B, CU_TENSOR_MAP_L2_PROMOTION_L2_256B, CU_TENSOR_MAP_FLOAT_OOB_FILL_NONE);
}

}

extern "C" void kernel_launch(void* const* d_in, const int* in_sizes, int n_in, void* d_out, int out_size) {
  (void)in_sizes; (void)n_in; (void)out_size;
  EncodeFn enc = nullptr;
  cudaDriverEntryPointQueryResult qres;
  cudaGetDriverEntryPoint("cuTensorMapEncodeTiled", (void**)&enc, cudaEnableDefault, &qres);
  void *p_x1, *p_qkv, *p_wf;
  cudaGetSymbolAddress(&p_wf, g_wf);
  cudaGetSymbolAddress(&p_x1, g_x1);
  cudaGetSymbolAddress(&p_qkv, g_qkv);
  cudaFuncSetAttribute(kernelA, cudaFuncAttributeMaxDynamicSharedMemorySize, A_SMEM);
  cudaFuncSetAttribute(kernelB, cudaFuncAttributeMaxDynamicSharedMemorySize, B_SMEM);

  CUtensorMap tm_x, tm_wqkvt, tm_wot, tm_wqkvs, tm_x1s, tm_qkvs, tm_q, tm_kv, tm_wos, tm_x1l, tm_out, tm_wf;
  const uint64_t d_act[3] = {192, 1296, 7}, d_qkv[3] = {576, 1296, 7}, d_w3[2] = {576, 192}, d_w1[2] = {192, 192}, d_wf[2] = {384, 384};
  const uint32_t b_a[3] = {64, 9, 7}, b_w[2] = {64, 192}, b_q[3] = {64, 128, 1}, b_kv[3] = {64, 144, 1}, b_o[3] = {64, 64, 1}, b_w64[2] = {64, 64};
  make_map(enc, &tm_x, d_in[0], 3, d_act, b_a);
  make_map(enc, &tm_wqkvt, d_in[1], 2, d_w3, b_w64);
  make_map(enc, &tm_wot, d_in[2], 2, d_w1, b_w);
  make_map(enc, &tm_wqkvs, d_in[3], 2, d_w3, b_w64);
  make_map(enc, &tm_wos, d_in[4], 2, d_w1, b_w);
  make_map(enc, &tm_wf, p_wf, 2, d_wf, b_w);
  make_map(enc, &tm_x1s, p_x1, 3, d_act, b_a);
  make_map(enc, &tm_qkvs, p_qkv, 3, d_qkv, b_a);
  make_map(enc, &tm_q, p_qkv, 3, d_qkv, b_q);
  make_map(enc, &tm_kv, p_qkv, 3, d_qkv, b_kv);
  make_map(enc, &tm_x1l, p_x1, 3, d_act, b_q);
  make_map(enc, &tm_out, d_out, 3, d_act, b_o);

  kernelA<<<72 + A_FOLD, 384, A_SMEM, cudaStreamPerThread>>>(tm_x, tm_wqkvt, tm_wot, tm_wqkvs, tm_wos, tm_wf, tm_x1s, tm_qkvs);
  cudaLaunchConfig_t cfg = {};
  cfg.gridDim = dim3(B_GRID); cfg.blockDim = dim3(384); cfg.dynamicSmemBytes = B_SMEM; cfg.stream = cudaStreamPerThread;
  cudaLaunchAttribute at[1];
  at[0].id = cudaLaunchAttributeProgrammaticStreamSerialization;
  at[0].val.programmaticStreamSerializationAllowed = 1;
  cfg.attrs = at; cfg.numAttrs = 1;
  cudaLaunchKernelEx(&cfg, kernelB, tm_q, tm_kv, tm_x1l, tm_out);
}
```

```cpp
#include <cuda_runtime.h>
#include <cuda_bf16.h>
#include <cuda.h>
#include <stdint.h>

namespace {

constexpr int TT = 7, NL = 1296, CC = 192;

__device__ __align__(1024) __nv_bfloat16 g_x1[TT * NL * CC];
__device__ __align__(1024) __nv_bfloat16 g_qkv[TT * NL * 3 * CC];
__device__ __align__(1024) __nv_bfloat16 g_wf[2 * CC * 2 * CC];
__device__ __align__(1024) uint4 g_part[121 * 2 * 13 * 128];
__device__ unsigned int g_flag[128];
__device__ unsigned int g_wflag[4];

#define TS(k, i)

__device__ __forceinline__ uint32_t smem_u32(const void* p) { return (uint32_t)__cvta_generic_to_shared(p); }
__device__ __forceinline__ void mbar_init(uint32_t bar, uint32_t cnt) {
  asm volatile("mbarrier.init.shared::cta.b64 [%0], %1;" ::"r"(bar), "r"(cnt));
}
__device__ __forceinline__ void mbar_expect_tx(uint32_t bar, uint32_t bytes) {
  asm volatile("mbarrier.arrive.expect_tx.shared::cta.b64 _, [%0], %1;" ::"r"(bar), "r"(bytes) : "memory");
}
__device__ __forceinline__ void mbar_arrive(uint32_t bar) {
  asm volatile("mbarrier.arrive.shared::cta.b64 _, [%0];" ::"r"(bar) : "memory");
}
__device__ __forceinline__ bool mbar_try(uint32_t bar, uint32_t parity) {
  uint32_t ok;
  asm volatile("{\n.reg .pred p;\nmbarrier.try_wait.parity.shared::cta.b64 p, [%1], %2;\nselp.u32 %0, 1, 0, p;\n}"
               : "=r"(ok) : "r"(bar), "r"(parity) : "memory");
  return ok != 0;
}
__device__ __forceinline__ void mbar_wait(uint32_t bar, uint32_t parity) {
  if (mbar_try(bar, parity)) return;
  uint32_t n = 0;
  while (!mbar_try(bar, parity)) {
    if (++n > (1u << 22)) break;
  }
}
__device__ __forceinline__ void tma_load_2d(uint32_t dst, const CUtensorMap* m, uint32_t bar, int c0, int c1) {
  asm volatile("cp.async.bulk.tensor.2d.shared::cluster.global.mbarrier::complete_tx::bytes [%0], [%1, {%3, %4}], [%2];"
               ::"r"(dst), "l"(m), "r"(bar), "r"(c0), "r"(c1) : "memory");
}
__device__ __forceinline__ void tma_load_3d(uint32_t dst, const CUtensorMap* m, uint32_t bar, int c0, int c1, int c2) {
  asm volatile("cp.async.bulk.tensor.3d.shared::cluster.global.mbarrier::complete_tx::bytes [%0], [%1, {%3, %4, %5}], [%2];"
               ::"r"(dst), "l"(m), "r"(bar), "r"(c0), "r"(c1), "r"(c2) : "memory");
}
__device__ __forceinline__ void tma_store_3d(const CUtensorMap* m, uint32_t src, int c0, int c1, int c2) {
  asm volatile("cp.async.bulk.tensor.3d.global.shared::cta.bulk_group [%0, {%2, %3, %4}], [%1];"
               ::"l"(m), "r"(src), "r"(c0), "r"(c1), "r"(c2) : "memory");
}
__device__ __forceinline__ void bulk_commit() { asm volatile("cp.async.bulk.commit_group;" ::: "memory"); }
__device__ __forceinline__ void bulk_wait_read0() { asm volatile("cp.async.bulk.wait_group.read 0;" ::: "memory"); }
__device__ __forceinline__ void bulk_wait_read1() { asm volatile("cp.async.bulk.wait_group.read 1;" ::: "memory"); }
__device__ __forceinline__ void bulk_wait0() { asm volatile("cp.async.bulk.wait_group 0;" ::: "memory"); }
__device__ __forceinline__ void fence_proxy_async() { asm volatile("fence.proxy.async.shared::cta;" ::: "memory"); }
__device__ __forceinline__ void prefetch_tmap(const CUtensorMap* m) {
  asm volatile("prefetch.tensormap [%0];" ::"l"(m) : "memory");
}
__device__ __forceinline__ void wg_fence() { asm volatile("wgmma.fence.sync.aligned;" ::: "memory"); }
__device__ __forceinline__ void wg_commit() { asm volatile("wgmma.commit_group.sync.aligned;" ::: "memory"); }
template <int N> __device__ __forceinline__ void wg_wait() { asm volatile("wgmma.wait_group.sync.aligned %0;" ::"n"(N) : "memory"); }
__device__ __forceinline__ void named_bar(int id, int nthreads) {
  asm volatile("bar.sync %0, %1;" ::"r"(id), "r"(nthreads) : "memory");
}
__device__ __forceinline__ void ldsm_x4(uint32_t (&r)[4], uint32_t addr) {
  asm volatile("ldmatrix.sync.aligned.m8n8.x4.shared.b16 {%0,%1,%2,%3}, [%4];"
               : "=r"(r[0]), "=r"(r[1]), "=r"(r[2]), "=r"(r[3]) : "r"(addr) : "memory");
}
__device__ __forceinline__ void stsm_x4(uint32_t addr, const uint32_t (&r)[4]) {
  asm volatile("stmatrix.sync.aligned.m8n8.x4.shared.b16 [%0], {%1,%2,%3,%4};"
               ::"r"(addr), "r"(r[0]), "r"(r[1]), "r"(r[2]), "r"(r[3]) : "memory");
}
__device__ __forceinline__ uint32_t pack_bf16(float lo, float hi) {
  uint32_t r;
  asm("cvt.rn.bf16x2.f32 %0, %1, %2;" : "=r"(r) : "f"(hi), "f"(lo));
  return r;
}
__device__ __forceinline__ float bf_lo(uint32_t v) { return __uint_as_float(v << 16); }
__device__ __forceinline__ float bf_hi(uint32_t v) { return __uint_as_float(v & 0xffff0000u); }
__device__ __forceinline__ float ex2(float x) {
  float y;
  asm("ex2.approx.ftz.f32 %0, %1;" : "=f"(y) : "f"(x));
  return y;
}
__device__ __forceinline__ uint64_t mk_desc(uint32_t addr, uint32_t lbo, uint32_t sbo) {
  return (uint64_t)((addr & 0x3FFFF) >> 4) | ((uint64_t)((lbo & 0x3FFFF) >> 4) << 16) |
         ((uint64_t)((sbo & 0x3FFFF) >> 4) << 32) | (1ull << 62);
}
__device__ __forceinline__ uint64_t mk_desc_o(uint32_t addr, uint32_t lbo, uint32_t sbo) {
  asm volatile("" : "+r"(addr));
  return mk_desc(addr, lbo, sbo);
}
template <int N> __device__ __forceinline__ void reg_fence(uint32_t (&d)[N]) {
#pragma unroll
  for (int i = 0; i < N; i++) asm volatile("" : "+r"(d[i])::"memory");
}
template <int N> __device__ __forceinline__ void reg_fence(float (&d)[N]) {
#pragma unroll
  for (int i = 0; i < N; i++) asm volatile("" : "+f"(d[i])::"memory");
}

template<int TB> __device__ __forceinline__ void wgmma_n144_ss(float (&d)[72], uint64_t da, uint64_t db, int sc) {
  asm volatile("{\n.reg .pred p;\nsetp.ne.b32 p, %74, 0;\n"
    "wgmma.mma_async.sync.aligned.m64n144k16.f32.bf16.bf16 {%0, %1, %2, %3, %4, %5, %6, %7, %8, %9, %10, %11, %12, %13, %14, %15, %16, %17, %18, %19, %20, %21, %22, %23, %24, %25, %26, %27, %28, %29, %30, %31, %32, %33, %34, %35, %36, %37, %38, %39, %40, %41, %42, %43, %44, %45, %46, %47, %48, %49, %50, %51, %52, %53, %54, %55, %56, %57, %58, %59, %60, %61, %62, %63, %64, %65, %66, %67, %68, %69, %70, %71}, %72, %73, p, 1, 1, 0, %75;\n}\n"
    : "+f"(d[0]), "+f"(d[1]), "+f"(d[2]), "+f"(d[3]), "+f"(d[4]), "+f"(d[5]), "+f"(d[6]), "+f"(d[7]), "+f"(d[8]), "+f"(d[9]), "+f"(d[10]), "+f"(d[11]), "+f"(d[12]), "+f"(d[13]), "+f"(d[14]), "+f"(d[15]), "+f"(d[16]), "+f"(d[17]), "+f"(d[18]), "+f"(d[19]), "+f"(d[20]), "+f"(d[21]), "+f"(d[22]), "+f"(d[23]), "+f"(d[24]), "+f"(d[25]), "+f"(d[26]), "+f"(d[27]), "+f"(d[28]), "+f"(d[29]), "+f"(d[30]), "+f"(d[31]), "+f"(d[32]), "+f"(d[33]), "+f"(d[34]), "+f"(d[35]), "+f"(d[36]), "+f"(d[37]), "+f"(d[38]), "+f"(d[39]), "+f"(d[40]), "+f"(d[41]), "+f"(d[42]), "+f"(d[43]), "+f"(d[44]), "+f"(d[45]), "+f"(d[46]), "+f"(d[47]), "+f"(d[48]), "+f"(d[49]), "+f"(d[50]), "+f"(d[51]), "+f"(d[52]), "+f"(d[53]), "+f"(d[54]), "+f"(d[55]), "+f"(d[56]), "+f"(d[57]), "+f"(d[58]), "+f"(d[59]), "+f"(d[60]), "+f"(d[61]), "+f"(d[62]), "+f"(d[63]), "+f"(d[64]), "+f"(d[65]), "+f"(d[66]), "+f"(d[67]), "+f"(d[68]), "+f"(d[69]), "+f"(d[70]), "+f"(d[71])
    : "l"(da), "l"(db), "r"(sc), "n"(TB));
}
template<int TB> __device__ __forceinline__ void wgmma_n192_rs(float (&d)[96], const uint32_t (&a)[4], uint64_t db, int sc) {
  asm volatile("{\n.reg .pred p;\nsetp.ne.b32 p, %101, 0;\n"
    "wgmma.mma_async.sync.aligned.m64n192k16.f32.bf16.bf16 {%0, %1, %2, %3, %4, %5, %6, %7, %8, %9, %10, %11, %12, %13, %14, %15, %16, %17, %18, %19, %20, %21, %22, %23, %24, %25, %26, %27, %28, %29, %30, %31, %32, %33, %34, %35, %36, %37, %38, %39, %40, %41, %42, %43, %44, %45, %46, %47, %48, %49, %50, %51, %52, %53, %54, %55, %56, %57, %58, %59, %60, %61, %62, %63, %64, %65, %66, %67, %68, %69, %70, %71, %72, %73, %74, %75, %76, %77, %78, %79, %80, %81, %82, %83, %84, %85, %86, %87, %88, %89, %90, %91, %92, %93, %94, %95}, {%96, %97, %98, %99}, %100, p, 1, 1, %102;\n}\n"
    : "+f"(d[0]), "+f"(d[1]), "+f"(d[2]), "+f"(d[3]), "+f"(d[4]), "+f"(d[5]), "+f"(d[6]), "+f"(d[7]), "+f"(d[8]), "+f"(d[9]), "+f"(d[10]), "+f"(d[11]), "+f"(d[12]), "+f"(d[13]), "+f"(d[14]), "+f"(d[15]), "+f"(d[16]), "+f"(d[17]), "+f"(d[18]), "+f"(d[19]), "+f"(d[20]), "+f"(d[21]), "+f"(d[22]), "+f"(d[23]), "+f"(d[24]), "+f"(d[25]), "+f"(d[26]), "+f"(d[27]), "+f"(d[28]), "+f"(d[29]), "+f"(d[30]), "+f"(d[31]), "+f"(d[32]), "+f"(d[33]), "+f"(d[34]), "+f"(d[35]), "+f"(d[36]), "+f"(d[37]), "+f"(d[38]), "+f"(d[39]), "+f"(d[40]), "+f"(d[41]), "+f"(d[42]), "+f"(d[43]), "+f"(d[44]), "+f"(d[45]), "+f"(d[46]), "+f"(d[47]), "+f"(d[48]), "+f"(d[49]), "+f"(d[50]), "+f"(d[51]), "+f"(d[52]), "+f"(d[53]), "+f"(d[54]), "+f"(d[55]), "+f"(d[56]), "+f"(d[57]), "+f"(d[58]), "+f"(d[59]), "+f"(d[60]), "+f"(d[61]), "+f"(d[62]), "+f"(d[63]), "+f"(d[64]), "+f"(d[65]), "+f"(d[66]), "+f"(d[67]), "+f"(d[68]), "+f"(d[69]), "+f"(d[70]), "+f"(d[71]), "+f"(d[72]), "+f"(d[73]), "+f"(d[74]), "+f"(d[75]), "+f"(d[76]), "+f"(d[77]), "+f"(d[78]), "+f"(d[79]), "+f"(d[80]), "+f"(d[81]), "+f"(d[82]), "+f"(d[83]), "+f"(d[84]), "+f"(d[85]), "+f"(d[86]), "+f"(d[87]), "+f"(d[88]), "+f"(d[89]), "+f"(d[90]), "+f"(d[91]), "+f"(d[92]), "+f"(d[93]), "+f"(d[94]), "+f"(d[95])
    : "r"(a[0]), "r"(a[1]), "r"(a[2]), "r"(a[3]), "l"(db), "r"(sc), "n"(TB));
}
template<int TB> __device__ __forceinline__ void wgmma_n64_rs(float (&d)[32], const uint32_t (&a)[4], uint64_t db, int sc) {
  asm volatile("{\n.reg .pred p;\nsetp.ne.b32 p, %37, 0;\n"
    "wgmma.mma_async.sync.aligned.m64n64k16.f32.bf16.bf16 {%0, %1, %2, %3, %4, %5, %6, %7, %8, %9, %10, %11, %12, %13, %14, %15, %16, %17, %18, %19, %20, %21, %22, %23, %24, %25, %26, %27, %28, %29, %30, %31}, {%32, %33, %34, %35}, %36, p, 1, 1, %38;\n}\n"
    : "+f"(d[0]), "+f"(d[1]), "+f"(d[2]), "+f"(d[3]), "+f"(d[4]), "+f"(d[5]), "+f"(d[6]), "+f"(d[7]), "+f"(d[8]), "+f"(d[9]), "+f"(d[10]), "+f"(d[11]), "+f"(d[12]), "+f"(d[13]), "+f"(d[14]), "+f"(d[15]), "+f"(d[16]), "+f"(d[17]), "+f"(d[18]), "+f"(d[19]), "+f"(d[20]), "+f"(d[21]), "+f"(d[22]), "+f"(d[23]), "+f"(d[24]), "+f"(d[25]), "+f"(d[26]), "+f"(d[27]), "+f"(d[28]), "+f"(d[29]), "+f"(d[30]), "+f"(d[31])
    : "r"(a[0]), "r"(a[1]), "r"(a[2]), "r"(a[3]), "l"(db), "r"(sc), "n"(TB));
}
template<int TB> __device__ __forceinline__ void wgmma_n64_ss(float (&d)[32], uint64_t da, uint64_t db, int sc) {
  asm volatile("{\n.reg .pred p;\nsetp.ne.b32 p, %34, 0;\n"
    "wgmma.mma_async.sync.aligned.m64n64k16.f32.bf16.bf16 {%0, %1, %2, %3, %4, %5, %6, %7, %8, %9, %10, %11, %12, %13, %14, %15, %16, %17, %18, %19, %20, %21, %22, %23, %24, %25, %26, %27, %28, %29, %30, %31}, %32, %33, p, 1, 1, 0, %35;\n}\n"
    : "+f"(d[0]), "+f"(d[1]), "+f"(d[2]), "+f"(d[3]), "+f"(d[4]), "+f"(d[5]), "+f"(d[6]), "+f"(d[7]), "+f"(d[8]), "+f"(d[9]), "+f"(d[10]), "+f"(d[11]), "+f"(d[12]), "+f"(d[13]), "+f"(d[14]), "+f"(d[15]), "+f"(d[16]), "+f"(d[17]), "+f"(d[18]), "+f"(d[19]), "+f"(d[20]), "+f"(d[21]), "+f"(d[22]), "+f"(d[23]), "+f"(d[24]), "+f"(d[25]), "+f"(d[26]), "+f"(d[27]), "+f"(d[28]), "+f"(d[29]), "+f"(d[30]), "+f"(d[31])
    : "l"(da), "l"(db), "r"(sc), "n"(TB));
}

struct FragAddr {
  uint32_t rowoff;
  uint32_t rx;
  uint32_t hi;
  __device__ __forceinline__ FragAddr(int warp_in_wg, int lane) {
    int row = 16 * warp_in_wg + (lane & 7) + ((lane >> 3) & 1) * 8;
    rowoff = row * 128;
    rx = row & 7;
    hi = lane >> 4;
  }
  __device__ __forceinline__ uint32_t at(uint32_t chunk_base, int kk4) const {
    return chunk_base + rowoff + ((((uint32_t)kk4 * 2 + hi) ^ rx) << 4);
  }
};

__device__ __forceinline__ void layernorm_frags(uint32_t (&f)[12][4]) {
  float s0[2] = {0.f, 0.f}, s1[2] = {0.f, 0.f}, q0[2] = {0.f, 0.f}, q1[2] = {0.f, 0.f};
#pragma unroll
  for (int k = 0; k < 12; k++) {
#pragma unroll
    for (int hf = 0; hf < 2; hf++) {
      const float a = bf_lo(f[k][2 * hf]), b = bf_hi(f[k][2 * hf]);
      const float c = bf_lo(f[k][2 * hf + 1]), d = bf_hi(f[k][2 * hf + 1]);
      s0[hf] += a + b; q0[hf] = fmaf(a, a, fmaf(b, b, q0[hf]));
      s1[hf] += c + d; q1[hf] = fmaf(c, c, fmaf(d, d, q1[hf]));
    }
  }
  float sa = s0[0] + s0[1], sb_ = s1[0] + s1[1], qa = q0[0] + q0[1], qb_ = q1[0] + q1[1];
  sa += __shfl_xor_sync(0xffffffffu, sa, 1); sb_ += __shfl_xor_sync(0xffffffffu, sb_, 1);
  qa += __shfl_xor_sync(0xffffffffu, qa, 1); qb_ += __shfl_xor_sync(0xffffffffu, qb_, 1);
  sa += __shfl_xor_sync(0xffffffffu, sa, 2); sb_ += __shfl_xor_sync(0xffffffffu, sb_, 2);
  qa += __shfl_xor_sync(0xffffffffu, qa, 2); qb_ += __shfl_xor_sync(0xffffffffu, qb_, 2);
  const float m0 = sa * (1.f / 192.f), m1 = sb_ * (1.f / 192.f);
  const float v0 = fmaxf(fmaf(-m0, m0, qa * (1.f / 192.f)), 0.f), v1 = fmaxf(fmaf(-m1, m1, qb_ * (1.f / 192.f)), 0.f);
  const float r0 = rsqrtf(v0 + 1e-5f), r1 = rsqrtf(v1 + 1e-5f);
  const float c0 = -m0 * r0, c1 = -m1 * r1;
#pragma unroll
  for (int k = 0; k < 12; k++) {
    f[k][0] = pack_bf16(fmaf(bf_lo(f[k][0]), r0, c0), fmaf(bf_hi(f[k][0]), r0, c0));
    f[k][2] = pack_bf16(fmaf(bf_lo(f[k][2]), r0, c0), fmaf(bf_hi(f[k][2]), r0, c0));
    f[k][1] = pack_bf16(fmaf(bf_lo(f[k][1]), r1, c1), fmaf(bf_hi(f[k][1]), r1, c1));
    f[k][3] = pack_bf16(fmaf(bf_lo(f[k][3]), r1, c1), fmaf(bf_hi(f[k][3]), r1, c1));
  }
}

#define XDELAY 800
constexpr int A_NST = 5;
constexpr int A_XS = 0;
constexpr int A_VB = 49152;
constexpr int A_W = 98304;
constexpr int A_BAR = A_W + A_NST * 24576;
constexpr int A_SMEM = A_BAR + 256 + 1024;
constexpr int A_FOLD = 36;

__device__ __forceinline__ void a_issue(float (&acc)[32], const uint32_t (&af)[12][4], uint32_t sb, int s) {
  const int st = s % A_NST;
  mbar_wait(sb + A_BAR + st * 8, (s / A_NST) & 1);
  const uint64_t wd = mk_desc_o(sb + A_W + st * 24576, 8192, 1024);
  wg_fence();
#pragma unroll
  for (int kk = 0; kk < 12; kk++) wgmma_n64_rs<1>(acc, af[kk], wd + kk * 128, kk > 0);
  wg_commit();
}
__device__ __forceinline__ void a_release(uint32_t sb, int s, int lane) {
  if (lane == 0) mbar_arrive(sb + A_BAR + 64 + (s % A_NST) * 8);
}
__device__ __forceinline__ void cvt_frags(uint32_t (*dst)[4], const float (&acc)[32]) {
#pragma unroll
  for (int k = 0; k < 4; k++) {
    dst[k][0] = pack_bf16(acc[8 * k + 0], acc[8 * k + 1]);
    dst[k][1] = pack_bf16(acc[8 * k + 2], acc[8 * k + 3]);
    dst[k][2] = pack_bf16(acc[8 * k + 4], acc[8 * k + 5]);
    dst[k][3] = pack_bf16(acc[8 * k + 6], acc[8 * k + 7]);
  }
}
__device__ __forceinline__ void store_chunk(const float (&acc)[32], uint32_t chunk_base, const FragAddr& fa) {
  uint32_t t[4][4];
  cvt_frags(t, acc);
#pragma unroll
  for (int k = 0; k < 4; k++) stsm_x4(fa.at(chunk_base, k), t[k]);
}
__device__ __forceinline__ void resid_chunk(uint32_t (*dst)[4], const float* acc, float s0, float s1, uint32_t chunk_base,
                                            const FragAddr& fa) {
#pragma unroll
  for (int k = 0; k < 4; k++) {
    uint32_t x[4];
    ldsm_x4(x, fa.at(chunk_base, k));
    uint32_t o[4];
    o[0] = pack_bf16(fmaf(acc[8 * k + 0], s0, bf_lo(x[0])), fmaf(acc[8 * k + 1], s0, bf_hi(x[0])));
    o[1] = pack_bf16(fmaf(acc[8 * k + 2], s1, bf_lo(x[1])), fmaf(acc[8 * k + 3], s1, bf_hi(x[1])));
    o[2] = pack_bf16(fmaf(acc[8 * k + 4], s0, bf_lo(x[2])), fmaf(acc[8 * k + 5], s0, bf_hi(x[2])));
    o[3] = pack_bf16(fmaf(acc[8 * k + 6], s1, bf_lo(x[3])), fmaf(acc[8 * k + 7], s1, bf_hi(x[3])));
    stsm_x4(fa.at(chunk_base, k), o);
    if (dst) { dst[k][0] = o[0]; dst[k][1] = o[1]; dst[k][2] = o[2]; dst[k][3] = o[3]; }
  }
}

__global__ void __launch_bounds__(384, 1)
kernelA(const __grid_constant__ CUtensorMap tm_x, const __grid_constant__ CUtensorMap tm_wq64t,
        const __grid_constant__ CUtensorMap tm_wot, const __grid_constant__ CUtensorMap tm_wq64s,
        const __grid_constant__ CUtensorMap tm_wos, const __grid_constant__ CUtensorMap tm_wf,
        const __grid_constant__ CUtensorMap tm_x1, const __grid_constant__ CUtensorMap tm_qkv) {
  extern __shared__ uint8_t smem_raw[];
  const uint32_t sb = (smem_u32(smem_raw) + 1023) & ~1023u;
  const int tid = threadIdx.x, warp = tid >> 5, lane = tid & 31;
  const bool is_fold = blockIdx.x < A_FOLD;
  const int blk = blockIdx.x - A_FOLD;
  if (tid == 256) {
    for (int i = 0; i < A_NST; i++) { mbar_init(sb + A_BAR + i * 8, 1); mbar_init(sb + A_BAR + 64 + i * 8, 8); }
    mbar_init(sb + A_BAR + 128, 1); mbar_init(sb + A_BAR + 136, 1);
    asm volatile("fence.mbarrier_init.release.cluster;" ::: "memory");
    if (!is_fold) {
      __nanosleep(XDELAY);
      for (int w = 0; w < 2; w++) {
        const uint32_t bar = sb + A_BAR + 128 + w * 8;
        mbar_expect_tx(bar, 3 * 63 * 128);
        for (int c = 0; c < 3; c++)
          tma_load_3d(sb + A_XS + w * 24576 + c * 8192, &tm_x, bar, c * 64, (blk * 2 + w) * 9, 0);
      }
    } else {
      const int mat = blockIdx.x / 9, rs = (blockIdx.x % 9) / 3, cs = blockIdx.x % 3;
      const CUtensorMap* mq = (mat < 2) ? &tm_wq64t : &tm_wq64s;
      const CUtensorMap* mo = (mat < 2) ? &tm_wot : &tm_wos;
      const uint32_t bar = sb + A_BAR + 128;
      mbar_expect_tx(bar, 2 * 24576);
      for (int c = 0; c < 3; c++) tma_load_2d(sb + c * 8192, mq, bar, ((mat & 1) ? 384 : 0) + c * 64, rs * 64);
      if (mat & 1) tma_load_2d(sb + 24576, mo, bar, cs * 64, 0);
      else for (int c = 0; c < 3; c++) tma_load_2d(sb + 24576 + c * 8192, mq, bar, 192 + c * 64, cs * 64);
    }
  }
  asm volatile("griddepcontrol.launch_dependents;" ::: "memory");
  if (blockIdx.x == 0 && tid < 128) g_flag[tid] = 0;
  if (!is_fold && tid < 48) {
    uint32_t a = sb + A_XS + (tid >> 3) * 8192 + 63 * 128 + (tid & 7) * 16;
    asm volatile("st.shared.v4.b32 [%0], {%1,%1,%1,%1};" ::"r"(a), "r"(0) : "memory");
  }
  __syncthreads();

  if (warp >= 8) {
    asm volatile("setmaxnreg.dec.sync.aligned.u32 24;");
    if (warp == 8 && lane == 0 && !is_fold) {
      for (int s = 0; s < 12; s++) {
        const int st = s % A_NST;
        const int g = s / 3;
        const int mat = (g == 0) ? 1 : (g == 1) ? 0 : g;
        if (s % 3 == 0) {
          uint32_t n = 0, v;
          do {
            asm volatile("ld.acquire.gpu.global.u32 %0, [%1];" : "=r"(v) : "l"(&g_wflag[mat]) : "memory");
          } while (v < 9u && ++n < (1u << 22));
          asm volatile("fence.proxy.async;" ::: "memory");
        }
        if (s >= A_NST) mbar_wait(sb + A_BAR + 64 + st * 8, ((s / A_NST) - 1) & 1);
        mbar_expect_tx(sb + A_BAR + st * 8, 24576);
        tma_load_2d(sb + A_W + st * 24576, &tm_wf, sb + A_BAR + st * 8, (mat & 1) * 192 + (s % 3) * 64, (mat >> 1) * 192);
      }
    }
    return;
  }

  asm volatile("setmaxnreg.inc.sync.aligned.u32 240;");
  const int wg = warp >> 2, wq = warp & 3;

  if (is_fold) {
    if (wg == 0) {
      const int mat = blockIdx.x / 9, rs = (blockIdx.x % 9) / 3, cs = blockIdx.x % 3;
      float d[32];
      mbar_wait(sb + A_BAR + 128, 0);
      const uint64_t ad = mk_desc_o(sb, 16, 1024);
      if (mat & 1) {
        const uint64_t bd = mk_desc_o(sb + 24576, 8192, 1024);
        wg_fence();
#pragma unroll
        for (int kk = 0; kk < 12; kk++) wgmma_n64_ss<1>(d, ad + (kk >> 2) * 512 + (kk & 3) * 2, bd + kk * 128, kk > 0);
        wg_commit();
      } else {
        const uint64_t bd = mk_desc_o(sb + 24576, 16, 1024);
        wg_fence();
#pragma unroll
        for (int kk = 0; kk < 12; kk++)
          wgmma_n64_ss<0>(d, ad + (kk >> 2) * 512 + (kk & 3) * 2, bd + (kk >> 2) * 512 + (kk & 3) * 2, kk > 0);
        wg_commit();
      }
      wg_wait<0>(); reg_fence(d);
      const int r0 = rs * 64 + wq * 16 + (lane >> 2);
      uint32_t* dst = reinterpret_cast<uint32_t*>(g_wf + ((size_t)(mat >> 1) * 192 + r0) * 384 + (mat & 1) * 192 + cs * 64 + (lane & 3) * 2);
#pragma unroll
      for (int j = 0; j < 8; j++) {
        dst[j * 4] = pack_bf16(d[4 * j], d[4 * j + 1]);
        dst[8 * 192 + j * 4] = pack_bf16(d[4 * j + 2], d[4 * j + 3]);
      }
      asm volatile("fence.proxy.async;" ::: "memory");
      named_bar(1, 128);
      if (tid == 0) { __threadfence(); atomicAdd(&g_wflag[mat], 1u); }
    }
    return;
  }

  const int n0 = (blk * 2 + wg) * 9;
  const FragAddr fa(wq, lane);
  const uint32_t xs = sb + A_XS + wg * 24576, vb = sb + A_VB + wg * 24576;
  const int barid = 1 + wg;
  const bool elected = (tid & 127) == 0;

  uint32_t h[12][4];
  TS(0, 0);
  mbar_wait(sb + A_BAR + 128 + wg * 8, 0);
  TS(0, 1);
#pragma unroll
  for (int k = 0; k < 12; k++) ldsm_x4(h[k], fa.at(xs + (k >> 2) * 8192, k & 3));
  layernorm_frags(h);
#pragma unroll
  for (int k = 0; k < 12; k++) stsm_x4(fa.at(xs + (k >> 2) * 8192, k & 3), h[k]);

  float acc0[32], acc1[32];
  uint32_t qf[12][4];
  TS(0, 2);
  a_issue(acc0, h, sb, 0);
  TS(0, 3);
  a_issue(acc1, h, sb, 1); wg_wait<1>(); reg_fence(acc0); a_release(sb, 0, lane); store_chunk(acc0, vb, fa);
  a_issue(acc0, h, sb, 2); wg_wait<1>(); reg_fence(acc1); a_release(sb, 1, lane); store_chunk(acc1, vb + 8192, fa);
  a_issue(acc1, h, sb, 3); wg_wait<1>(); reg_fence(acc0); a_release(sb, 2, lane); store_chunk(acc0, vb + 16384, fa);
  fence_proxy_async();
  named_bar(barid, 128);
  a_issue(acc0, h, sb, 4); wg_wait<1>(); reg_fence(acc1); a_release(sb, 3, lane); cvt_frags(&qf[0], acc1);
  a_issue(acc1, h, sb, 5); wg_wait<1>(); reg_fence(acc0); a_release(sb, 4, lane); cvt_frags(&qf[4], acc0);
  wg_wait<0>(); reg_fence(acc1); a_release(sb, 5, lane); cvt_frags(&qf[8], acc1);
  TS(0, 4);
  {
    const uint64_t kd = mk_desc_o(xs, 16, 1024);
    wg_fence();
#pragma unroll
    for (int kk = 0; kk < 12; kk++) wgmma_n64_rs<0>(acc0, qf[kk], kd + (kk >> 2) * 512 + (kk & 3) * 2, kk > 0);
    wg_commit();
    wg_wait<0>(); reg_fence(acc0);
  }
  named_bar(barid, 128);
  if (elected) {
    const uint32_t bar = sb + A_BAR + 128 + wg * 8;
    mbar_expect_tx(bar, 3 * 63 * 128);
    for (int c = 0; c < 3; c++) tma_load_3d(xs + c * 8192, &tm_x, bar, c * 64, n0, 0);
  }
  uint32_t pf[4][4];
  {
    const int r0 = 16 * wq + (lane >> 2), r1 = r0 + 8;
    const unsigned long long MB = 0x0040201008040201ull;
    const unsigned long long mk0 = (MB << (r0 % 9)) >> (2 * (lane & 3));
    const unsigned long long mk1 = (MB << (r1 % 9)) >> (2 * (lane & 3));
    const float cs = 0.07216878364870322f * 1.4426950408889634f;
    float mx0 = -INFINITY, mx1 = -INFINITY;
#pragma unroll
    for (int j = 0; j < 8; j++) {
#pragma unroll
      for (int e = 0; e < 2; e++) {
        bool v0 = (mk0 >> (8 * j + e)) & 1, v1 = (mk1 >> (8 * j + e)) & 1;
        acc0[4 * j + e] = v0 ? acc0[4 * j + e] * cs : -INFINITY;
        acc0[4 * j + 2 + e] = v1 ? acc0[4 * j + 2 + e] * cs : -INFINITY;
        mx0 = fmaxf(mx0, acc0[4 * j + e]);
        mx1 = fmaxf(mx1, acc0[4 * j + 2 + e]);
      }
    }
    mx0 = fmaxf(mx0, __shfl_xor_sync(0xffffffffu, mx0, 1)); mx0 = fmaxf(mx0, __shfl_xor_sync(0xffffffffu, mx0, 2));
    mx1 = fmaxf(mx1, __shfl_xor_sync(0xffffffffu, mx1, 1)); mx1 = fmaxf(mx1, __shfl_xor_sync(0xffffffffu, mx1, 2));
    float l0 = 0.f, l1 = 0.f;
#pragma unroll
    for (int j = 0; j < 8; j++) {
#pragma unroll
      for (int e = 0; e < 2; e++) {
        acc0[4 * j + e] = ex2(acc0[4 * j + e] - mx0); l0 += acc0[4 * j + e];
        acc0[4 * j + 2 + e] = ex2(acc0[4 * j + 2 + e] - mx1); l1 += acc0[4 * j + 2 + e];
      }
    }
    l0 += __shfl_xor_sync(0xffffffffu, l0, 1); l0 += __shfl_xor_sync(0xffffffffu, l0, 2);
    l1 += __shfl_xor_sync(0xffffffffu, l1, 1); l1 += __shfl_xor_sync(0xffffffffu, l1, 2);
    const float i0 = 1.f / l0, i1 = 1.f / l1;
#pragma unroll
    for (int j = 0; j < 8; j++) {
      acc0[4 * j] *= i0; acc0[4 * j + 1] *= i0; acc0[4 * j + 2] *= i1; acc0[4 * j + 3] *= i1;
    }
    cvt_frags(pf, acc0);
  }
  TS(0, 5);
  {
    float oacc[96];
    const uint64_t vd = mk_desc_o(vb, 8192, 1024);
    wg_fence();
#pragma unroll
    for (int kk = 0; kk < 4; kk++) wgmma_n192_rs<1>(oacc, pf[kk], vd + kk * 128, kk > 0);
    wg_commit();
    wg_wait<0>(); reg_fence(oacc);
    TS(0, 6);
    mbar_wait(sb + A_BAR + 128 + wg * 8, 1);
#pragma unroll
    for (int c = 0; c < 3; c++) resid_chunk(&h[4 * c], &oacc[32 * c], 1.f, 1.f, xs + c * 8192, fa);
  }
  TS(0, 7);
  fence_proxy_async();
  named_bar(barid, 128);
  if (elected) {
    for (int c = 0; c < 3; c++) tma_store_3d(&tm_x1, xs + c * 8192, c * 64, n0, 0);
    bulk_commit();
  }
  layernorm_frags(h);
#pragma unroll
  for (int k = 0; k < 12; k++) stsm_x4(fa.at(vb + (k >> 2) * 8192, k & 3), h[k]);
  TS(0, 8);
  a_issue(acc0, h, sb, 6);
  a_issue(acc1, h, sb, 7);
  fence_proxy_async();
  if (elected) bulk_wait_read0();
  named_bar(barid, 128);
  if (elected) {
    for (int c = 0; c < 3; c++) tma_store_3d(&tm_qkv, vb + c * 8192, 192 + c * 64, n0, 0);
    bulk_commit();
  }
  wg_wait<1>(); reg_fence(acc0); a_release(sb, 6, lane); store_chunk(acc0, xs, fa);
  a_issue(acc0, h, sb, 8); wg_wait<1>(); reg_fence(acc1); store_chunk(acc1, xs + 8192, fa);
  a_issue(acc1, h, sb, 9); wg_wait<1>(); reg_fence(acc0); store_chunk(acc0, xs + 16384, fa);
  a_issue(acc0, h, sb, 10);
  fence_proxy_async();
  if (elected) bulk_wait_read0();
  named_bar(barid, 128);
  if (elected) {
    for (int c = 0; c < 3; c++) tma_store_3d(&tm_qkv, xs + c * 8192, c * 64, n0, 0);
    bulk_commit();
  }
  {
    const int rr = wq * 16 + (lane >> 3);
    __nv_bfloat16* gdst = g_qkv + 384 + (lane & 7) * 8;
    auto flush = [&](uint32_t cb, int c) {
      __syncwarp();
#pragma unroll
      for (int i = 0; i < 4; i++) {
        const int r = rr + 4 * i;
        uint4 v;
        asm volatile("ld.shared.v4.b32 {%0,%1,%2,%3}, [%4];" : "=r"(v.x), "=r"(v.y), "=r"(v.z), "=r"(v.w)
                     : "r"(cb + r * 128 + (((lane & 7) ^ (r & 7)) << 4)) : "memory");
        const int t = r / 9, loc = r - t * 9;
        if (r < 63) *reinterpret_cast<uint4*>(gdst + ((size_t)t * NL + n0 + loc) * 576 + c * 64) = v;
      }
    };
    wg_wait<1>(); reg_fence(acc1); store_chunk(acc1, vb, fa);
    a_issue(acc1, h, sb, 11);
    flush(vb, 0);
    wg_wait<1>(); reg_fence(acc0); store_chunk(acc0, vb + 8192, fa);
    flush(vb + 8192, 1);
    wg_wait<0>(); reg_fence(acc1); store_chunk(acc1, vb + 16384, fa);
    flush(vb + 16384, 2);
  }
  TS(0, 9);
  if (elected) bulk_wait_read0();
  TS(0, 10);
}

constexpr int B_GRID = 132;
constexpr int B_SLOT = 55296;
constexpr int B_Q = 0;
constexpr int B_KV = 49152;
constexpr int B_BAR = B_KV + 3 * B_SLOT;
constexpr int B_SMEM = B_BAR + 256 + 1024;

__device__ __forceinline__ void bar_arrive(int id, int nthreads) {
  asm volatile("bar.arrive %0, %1;" ::"r"(id), "r"(nthreads) : "memory");
}
#define PP_MODE 0
#define PP_WAIT(x, y) named_bar(x, y)
#define PP_ARRIVE(x, y) bar_arrive(x, y)
__device__ __forceinline__ void b_segment(int sg, int& tile, int& k0, int& k1) {
  const int grp = blockIdx.x / 12, ci = blockIdx.x - grp * 12;
  if (ci < 7) { tile = grp * 7 + ci; k0 = 3; k1 = 9; }
  else {
    const int hh = ci - 7;
    tile = grp * 7 + ((0x54210 >> (4 * hh)) & 15) + sg;
    k0 = sg ? 0 : ((0x10210 >> (4 * hh)) & 15);
    k1 = sg ? ((0x31321 >> (4 * hh)) & 15) : 3;
  }
}

__global__ void __launch_bounds__(384, 1)
kernelB(const __grid_constant__ CUtensorMap tm_q, const __grid_constant__ CUtensorMap tm_kv,
        const __grid_constant__ CUtensorMap tm_x1, const __grid_constant__ CUtensorMap tm_out) {
  extern __shared__ uint8_t smem_raw[];
  const uint32_t sb = (smem_u32(smem_raw) + 1023) & ~1023u;
  const int tid = threadIdx.x, warp = tid >> 5, lane = tid & 31;
  const uint32_t bF = sb + B_BAR, bE = sb + B_BAR + 32, bQF = sb + B_BAR + 64, bQE = sb + B_BAR + 72;
  if (tid == 0) {
    for (int i = 0; i < 3; i++) { mbar_init(bF + i * 8, 1); mbar_init(bE + i * 8, 8); }
    mbar_init(bQF, 1); mbar_init(bQE, 8);
    asm volatile("fence.mbarrier_init.release.cluster;" ::: "memory");
    prefetch_tmap(&tm_q); prefetch_tmap(&tm_kv); prefetch_tmap(&tm_x1); prefetch_tmap(&tm_out);
  }
  __syncthreads();
  asm volatile("griddepcontrol.wait;" ::: "memory");
  const int grp = blockIdx.x / 12, ci = blockIdx.x - grp * 12;
  const bool owner = ci < 7;
  const int nseg = owner ? 1 : 2;

  if (warp >= 8) {
    asm volatile("setmaxnreg.dec.sync.aligned.u32 24;");
    if (warp == 8 && lane == 0) {
      if (blockIdx.x == 0) { g_wflag[0] = 0; g_wflag[1] = 0; g_wflag[2] = 0; g_wflag[3] = 0; }
      int it = 0;
      for (int sg = 0; sg < nseg; sg++) {
        int tile, k0, k1;
        b_segment(sg, tile, k0, k1);
        const int t = tile / 11, qt = tile - t * 11;
        if (sg > 0) mbar_wait(bQE, 0);
        mbar_expect_tx(bQF, 49152);
        for (int c = 0; c < 3; c++) tma_load_3d(sb + B_Q + c * 16384, &tm_q, bQF, c * 64, qt * 128, t);
        const int n = k1 - k0;
        for (int e = 0; e < 2 * n; e++) {
          const int sl = it % 3;
          if (it >= 3) mbar_wait(bE + sl * 8, ((it / 3) - 1) & 1);
#define EXP_NCH 3
          mbar_expect_tx(bF + sl * 8, EXP_NCH * 18432);
          for (int c = 0; c < EXP_NCH; c++)
            tma_load_3d(sb + B_KV + sl * B_SLOT + c * 18432, &tm_kv, bF + sl * 8, 192 + (e & 1) * 192 + c * 64, (k0 + (e >> 1)) * 144, t);
          it++;
        }
      }
      if (owner) {
        const int tile = grp * 7 + ci;
        const int t = tile / 11, qt = tile - t * 11;
        mbar_wait(bQE, 0);
        mbar_expect_tx(bQF, 49152);
        for (int c = 0; c < 3; c++) tma_load_3d(sb + B_Q + c * 16384, &tm_x1, bQF, c * 64, qt * 128, t);
      }
    } else if ((warp == 9 || warp == 10) && !owner) {
      for (int sg = 0; sg < 2; sg++) {
        named_bar(5 + (warp - 9), 160);
        if (lane == 0) {
          __threadfence();
          atomicAdd(&g_flag[(grp * 5 + (ci - 7)) * 2 + sg], 1u);
        }
        __syncwarp();
      }
    }
    return;
  }

  asm volatile("setmaxnreg.inc.sync.aligned.u32 240;");
  const int wg = warp >> 2, wq = warp & 3;
  const int wtid = tid & 127;
  const float cs = 0.07216878364870322f * 1.4426950408889634f;
  float oacc[96], sacc[72];
  uint32_t pf[9][4];
  float m0, m1, l0, l1;
  int it = 0;
  const uint32_t qb = sb + B_Q + wg * 8192;
  if (wg == 1) { PP_ARRIVE(3, 256); }
  TS(1, 0);
  int tsi = 1;

  auto issue_qk = [&](int slot) {
    const uint64_t kd = mk_desc_o(sb + B_KV + slot * B_SLOT, 16, 1024);
    const uint64_t qd = mk_desc_o(qb, 16, 1024);
#pragma unroll
    for (int kk = 0; kk < 12; kk++)
      wgmma_n144_ss<0>(sacc, qd + (kk >> 2) * 1024 + (kk & 3) * 2, kd + (kk >> 2) * 1152 + (kk & 3) * 2, kk > 0);
    wg_commit();
  };
  auto issue_pv = [&](int slot, int accum) {
    const uint64_t vd = mk_desc_o(sb + B_KV + slot * B_SLOT, 18432, 1024);
#pragma unroll
    for (int kk = 0; kk < 9; kk++) wgmma_n192_rs<1>(oacc, pf[kk], vd + kk * 128, kk > 0 ? 1 : accum);
    wg_commit();
  };
  auto softmax = [&](bool first) {
    float t0[4], t1[4];
#pragma unroll
    for (int q = 0; q < 4; q++) {
      t0[q] = fmaxf(sacc[4 * q], sacc[4 * q + 1]);
      t1[q] = fmaxf(sacc[4 * q + 2], sacc[4 * q + 3]);
    }
#pragma unroll
    for (int j = 4; j < 18; j++) {
      t0[j & 3] = fmaxf(t0[j & 3], fmaxf(sacc[4 * j], sacc[4 * j + 1]));
      t1[j & 3] = fmaxf(t1[j & 3], fmaxf(sacc[4 * j + 2], sacc[4 * j + 3]));
    }
    float mx0 = fmaxf(fmaxf(t0[0], t0[1]), fmaxf(t0[2], t0[3]));
    float mx1 = fmaxf(fmaxf(t1[0], t1[1]), fmaxf(t1[2], t1[3]));
    mx0 = fmaxf(mx0, __shfl_xor_sync(0xffffffffu, mx0, 1)); mx1 = fmaxf(mx1, __shfl_xor_sync(0xffffffffu, mx1, 1));
    mx0 = fmaxf(mx0, __shfl_xor_sync(0xffffffffu, mx0, 2)); mx1 = fmaxf(mx1, __shfl_xor_sync(0xffffffffu, mx1, 2));
    if (first) {
      m0 = mx0; m1 = mx1; l0 = 0.f; l1 = 0.f;
    } else {
      const bool need = !((mx0 - m0) * cs <= 8.f) || !((mx1 - m1) * cs <= 8.f);
      if (__any_sync(0xffffffffu, need)) {
        mx0 = fmaxf(mx0, m0); mx1 = fmaxf(mx1, m1);
        const float a0 = ex2((m0 - mx0) * cs), a1 = ex2((m1 - mx1) * cs);
        m0 = mx0; m1 = mx1;
        l0 *= a0; l1 *= a1;
#pragma unroll
        for (int i = 0; i < 24; i++) {
          oacc[4 * i] *= a0; oacc[4 * i + 1] *= a0; oacc[4 * i + 2] *= a1; oacc[4 * i + 3] *= a1;
        }
      }
    }
    const float mc0 = m0 * cs, mc1 = m1 * cs;
#pragma unroll
    for (int q = 0; q < 4; q++) { t0[q] = 0.f; t1[q] = 0.f; }
#pragma unroll
    for (int k = 0; k < 9; k++) {
      float p[8];
#pragma unroll
      for (int e = 0; e < 8; e++) p[e] = ex2(fmaf(sacc[8 * k + e], cs, (e & 2) ? -mc1 : -mc0));
      t0[0] += p[0]; t0[1] += p[1]; t0[2] += p[4]; t0[3] += p[5];
      t1[0] += p[2]; t1[1] += p[3]; t1[2] += p[6]; t1[3] += p[7];
      pf[k][0] = pack_bf16(p[0], p[1]); pf[k][1] = pack_bf16(p[2], p[3]);
      pf[k][2] = pack_bf16(p[4], p[5]); pf[k][3] = pack_bf16(p[6], p[7]);
    }
    l0 += (t0[0] + t0[1]) + (t0[2] + t0[3]);
    l1 += (t1[0] + t1[1]) + (t1[2] + t1[3]);
  };

  for (int sg = 0; sg < nseg; sg++) {
    int n;
    { int tile, k0, k1; b_segment(sg, tile, k0, k1); n = k1 - k0; }
    mbar_wait(bQF, sg & 1);
    {
      const int sl = it % 3;
      mbar_wait(bF + sl * 8, (it / 3) & 1);
      PP_WAIT(3 + wg, 256);
      wg_fence();
      issue_qk(sl);
      PP_ARRIVE(3 + (wg ^ 1), 256);
      wg_wait<0>(); reg_fence(sacc);
      if (lane == 0) { mbar_arrive(bE + sl * 8); if (n == 1) mbar_arrive(bQE); }
      it++;
      softmax(true);
    }
    TS(1, tsi); tsi++;
    for (int j = 1; j < n; j++) {
      const int slv = it % 3, slk = (it + 1) % 3;
      mbar_wait(bF + slv * 8, (it / 3) & 1);
      PP_WAIT(3 + wg, 256);
      wg_fence();
      issue_pv(slv, j > 1);
      mbar_wait(bF + slk * 8, ((it + 1) / 3) & 1);
      issue_qk(slk);
      PP_ARRIVE(3 + (wg ^ 1), 256);
      wg_wait<1>(); reg_fence(oacc);
      if (lane == 0) mbar_arrive(bE + slv * 8);
      wg_wait<0>(); reg_fence(sacc);
      if (lane == 0) { mbar_arrive(bE + slk * 8); if (j == n - 1) mbar_arrive(bQE); }
      it += 2;
      softmax(false);
      TS(1, tsi); tsi++;
    }
    if (owner) break;
    {
      const int sl = it % 3;
      mbar_wait(bF + sl * 8, (it / 3) & 1);
      PP_WAIT(3 + wg, 256);
      wg_fence();
      issue_pv(sl, n > 1);
      if (!(wg == 1 && sg == nseg - 1)) { PP_ARRIVE(3 + (wg ^ 1), 256); }
      wg_wait<0>(); reg_fence(oacc);
      if (lane == 0) mbar_arrive(bE + sl * 8);
      it++;
    }
    TS(1, tsi); tsi++;
    {
      const int slot = (grp * 5 + (ci - 7)) * 2 + sg;
      uint4* dst = g_part + (size_t)(slot * 2 + wg) * 13 * 128 + wtid;
#pragma unroll
      for (int i = 0; i < 12; i++)
        dst[i * 128] = make_uint4(pack_bf16(oacc[8 * i], oacc[8 * i + 1]), pack_bf16(oacc[8 * i + 2], oacc[8 * i + 3]),
                                  pack_bf16(oacc[8 * i + 4], oacc[8 * i + 5]), pack_bf16(oacc[8 * i + 6], oacc[8 * i + 7]));
      dst[12 * 128] = make_uint4(__float_as_uint(m0), __float_as_uint(m1), __float_as_uint(l0), __float_as_uint(l1));
      bar_arrive(5 + wg, 160);
      TS(1, tsi); tsi++;
    }
  }
  if (!owner) return;

  {
    const int sl = it % 3;
    mbar_wait(bF + sl * 8, (it / 3) & 1);
    PP_WAIT(3 + wg, 256);
    wg_fence();
    issue_pv(sl, 1);
    if (wg == 0) { PP_ARRIVE(3 + 1, 256); }
    const int first = (0x9765310 >> (4 * ci)) & 15, cnt = (0x1211221 >> (4 * ci)) & 15;
    const int slot0 = grp * 10 + first;
    if (wtid < cnt) {
      uint32_t n = 0, v;
      do {
        asm volatile("ld.acquire.gpu.global.u32 %0, [%1];" : "=r"(v) : "l"(&g_flag[slot0 + wtid]) : "memory");
      } while (v < 2u && ++n < (1u << 22));
    }
    named_bar(1 + wg, 128);
    uint4 pv0[13];
    {
      const uint4* src = g_part + (size_t)(slot0 * 2 + wg) * 13 * 128 + wtid;
#pragma unroll
      for (int i = 0; i < 13; i++) pv0[i] = __ldcg(src + i * 128);
    }
    wg_wait<0>(); reg_fence(oacc);
    TS(1, 20);
    uint4 pv1[13];
    if (cnt > 1) {
      const uint4* src = g_part + (size_t)((slot0 + 1) * 2 + wg) * 13 * 128 + wtid;
#pragma unroll
      for (int i = 0; i < 13; i++) pv1[i] = __ldcg(src + i * 128);
    }
    auto merge = [&](const uint4 (&pv)[13]) {
      const float pm0 = __uint_as_float(pv[12].x), pm1 = __uint_as_float(pv[12].y);
      const float mx0 = fmaxf(m0, pm0), mx1 = fmaxf(m1, pm1);
      const float a0 = ex2((m0 - mx0) * cs), a1 = ex2((m1 - mx1) * cs);
      const float b0 = ex2((pm0 - mx0) * cs), b1 = ex2((pm1 - mx1) * cs);
      m0 = mx0; m1 = mx1;
      l0 = l0 * a0 + __uint_as_float(pv[12].z) * b0; l1 = l1 * a1 + __uint_as_float(pv[12].w) * b1;
#pragma unroll
      for (int i = 0; i < 12; i++) {
        const uint4 v = pv[i];
        oacc[8 * i + 0] = oacc[8 * i + 0] * a0 + bf_lo(v.x) * b0; oacc[8 * i + 1] = oacc[8 * i + 1] * a0 + bf_hi(v.x) * b0;
        oacc[8 * i + 2] = oacc[8 * i + 2] * a1 + bf_lo(v.y) * b1; oacc[8 * i + 3] = oacc[8 * i + 3] * a1 + bf_hi(v.y) * b1;
        oacc[8 * i + 4] = oacc[8 * i + 4] * a0 + bf_lo(v.z) * b0; oacc[8 * i + 5] = oacc[8 * i + 5] * a0 + bf_hi(v.z) * b0;
        oacc[8 * i + 6] = oacc[8 * i + 6] * a1 + bf_lo(v.w) * b1; oacc[8 * i + 7] = oacc[8 * i + 7] * a1 + bf_hi(v.w) * b1;
      }
    };
    merge(pv0);
    if (cnt > 1) merge(pv1);
  }
  TS(1, 21);
  l0 += __shfl_xor_sync(0xffffffffu, l0, 1); l0 += __shfl_xor_sync(0xffffffffu, l0, 2);
  l1 += __shfl_xor_sync(0xffffffffu, l1, 1); l1 += __shfl_xor_sync(0xffffffffu, l1, 2);
  const float i0 = 1.f / l0, i1 = 1.f / l1;
  mbar_wait(bQF, 1);
  const FragAddr fa(wq, lane);
#pragma unroll
  for (int c = 0; c < 3; c++) resid_chunk(nullptr, &oacc[32 * c], i0, i1, qb + c * 16384, fa);
  fence_proxy_async();
  named_bar(1 + wg, 128);
  TS(1, 22);
  if (wtid == 0) {
    const int tile = grp * 7 + ci;
    const int t = tile / 11, qt = tile - t * 11;
    if (qt * 128 + wg * 64 < NL) {
      for (int c = 0; c < 3; c++) tma_store_3d(&tm_out, qb + c * 16384, c * 64, qt * 128 + wg * 64, t);
      bulk_commit();
      bulk_wait_read0();
    }
  }
  TS(1, 23);
}

typedef CUresult (*EncodeFn)(CUtensorMap*, CUtensorMapDataType, cuuint32_t, void*, const cuuint64_t*, const cuuint64_t*,
                             const cuuint32_t*, const cuuint32_t*, CUtensorMapInterleave, CUtensorMapSwizzle,
                             CUtensorMapL2promotion, CUtensorMapFloatOOBfill);

void make_map(EncodeFn enc, CUtensorMap* m, const void* ptr, int rank, const uint64_t* dims, const uint32_t* box) {
  cuuint64_t gd[3], gs[2];
  cuuint32_t bx[3], es[3] = {1, 1, 1};
  uint64_t stride = 2;
  for (int i = 0; i < rank; i++) {
    gd[i] = dims[i]; bx[i] = box[i];
    stride *= dims[i];
    if (i < rank - 1) gs[i] = stride;
  }
  enc(m, CU_TENSOR_MAP_DATA_TYPE_BFLOAT16, rank, const_cast<void*>(ptr), gd, gs, bx, es, CU_TENSOR_MAP_INTERLEAVE_NONE,
      CU_TENSOR_MAP_SWIZZLE_128B, CU_TENSOR_MAP_L2_PROMOTION_L2_256B, CU_TENSOR_MAP_FLOAT_OOB_FILL_NONE);
}

}

extern "C" void kernel_launch(void* const* d_in, const int* in_sizes, int n_in, void* d_out, int out_size) {
  (void)in_sizes; (void)n_in; (void)out_size;
  EncodeFn enc = nullptr;
  cudaDriverEntryPointQueryResult qres;
  cudaGetDriverEntryPoint("cuTensorMapEncodeTiled", (void**)&enc, cudaEnableDefault, &qres);
  void *p_x1, *p_qkv, *p_wf;
  cudaGetSymbolAddress(&p_wf, g_wf);
  cudaGetSymbolAddress(&p_x1, g_x1);
  cudaGetSymbolAddress(&p_qkv, g_qkv);
  cudaFuncSetAttribute(kernelA, cudaFuncAttributeMaxDynamicSharedMemorySize, A_SMEM);
  cudaFuncSetAttribute(kernelB, cudaFuncAttributeMaxDynamicSharedMemorySize, B_SMEM);

  CUtensorMap tm_x, tm_wqkvt, tm_wot, tm_wqkvs, tm_x1s, tm_qkvs, tm_q, tm_kv, tm_wos, tm_x1l, tm_out, tm_wf;
  const uint64_t d_act[3] = {192, 1296, 7}, d_qkv[3] = {576, 1296, 7}, d_w3[2] = {576, 192}, d_w1[2] = {192, 192}, d_wf[2] = {384, 384};
  const uint32_t b_a[3] = {64, 9, 7}, b_w[2] = {64, 192}, b_q[3] = {64, 128, 1}, b_kv[3] = {64, 144, 1}, b_o[3] = {64, 64, 1}, b_w64[2] = {64, 64};
  make_map(enc, &tm_x, d_in[0], 3, d_act, b_a);
  make_map(enc, &tm_wqkvt, d_in[1], 2, d_w3, b_w64);
  make_map(enc, &tm_wot, d_in[2], 2, d_w1, b_w);
  make_map(enc, &tm_wqkvs, d_in[3], 2, d_w3, b_w64);
  make_map(enc, &tm_wos, d_in[4], 2, d_w1, b_w);
  make_map(enc, &tm_wf, p_wf, 2, d_wf, b_w);
  make_map(enc, &tm_x1s, p_x1, 3, d_act, b_a);
  make_map(enc, &tm_qkvs, p_qkv, 3, d_qkv, b_a);
  make_map(enc, &tm_q, p_qkv, 3, d_qkv, b_q);
  make_map(enc, &tm_kv, p_qkv, 3, d_qkv, b_kv);
  make_map(enc, &tm_x1l, p_x1, 3, d_act, b_q);
  make_map(enc, &tm_out, d_out, 3, d_act, b_o);

  kernelA<<<72 + A_FOLD, 384, A_SMEM, cudaStreamPerThread>>>(tm_x, tm_wqkvt, tm_wot, tm_wqkvs, tm_wos, tm_wf, tm_x1s, tm_qkvs);
  cudaLaunchConfig_t cfg = {};
  cfg.gridDim = dim3(B_GRID); cfg.blockDim = dim3(384); cfg.dynamicSmemBytes = B_SMEM; cfg.stream = cudaStreamPerThread;
  cudaLaunchAttribute at[1];
  at[0].id = cudaLaunchAttributeProgrammaticStreamSerialization;
  at[0].val.programmaticStreamSerializationAllowed = 1;
  cfg.attrs = at; cfg.numAttrs = 1;
  cudaLaunchKernelEx(&cfg, kernelB, tm_q, tm_kv, tm_x1l, tm_out);
}
```

```cpp
#include <cuda_runtime.h>
#include <cuda_bf16.h>
#include <cuda.h>
#include <stdint.h>

namespace {

constexpr int TT = 7, NL = 1296, CC = 192;

__device__ __align__(1024) __nv_bfloat16 g_x1[TT * NL * CC];
__device__ __align__(1024) __nv_bfloat16 g_qkv[TT * NL * 3 * CC];
__device__ __align__(1024) __nv_bfloat16 g_wf[2 * CC * 2 * CC];
__device__ __align__(1024) uint4 g_part[121 * 2 * 13 * 128];
__device__ unsigned int g_flag[128];
__device__ unsigned int g_wflag[4];

#define TS(k, i)

__device__ __forceinline__ uint32_t smem_u32(const void* p) { return (uint32_t)__cvta_generic_to_shared(p); }
__device__ __forceinline__ void mbar_init(uint32_t bar, uint32_t cnt) {
  asm volatile("mbarrier.init.shared::cta.b64 [%0], %1;" ::"r"(bar), "r"(cnt));
}
__device__ __forceinline__ void mbar_expect_tx(uint32_t bar, uint32_t bytes) {
  asm volatile("mbarrier.arrive.expect_tx.shared::cta.b64 _, [%0], %1;" ::"r"(bar), "r"(bytes) : "memory");
}
__device__ __forceinline__ void mbar_arrive(uint32_t bar) {
  asm volatile("mbarrier.arrive.shared::cta.b64 _, [%0];" ::"r"(bar) : "memory");
}
__device__ __forceinline__ bool mbar_try(uint32_t bar, uint32_t parity) {
  uint32_t ok;
  asm volatile("{\n.reg .pred p;\nmbarrier.try_wait.parity.shared::cta.b64 p, [%1], %2;\nselp.u32 %0, 1, 0, p;\n}"
               : "=r"(ok) : "r"(bar), "r"(parity) : "memory");
  return ok != 0;
}
__device__ __forceinline__ void mbar_wait(uint32_t bar, uint32_t parity) {
  if (mbar_try(bar, parity)) return;
  uint32_t n = 0;
  while (!mbar_try(bar, parity)) {
    if (++n > (1u << 22)) break;
  }
}
__device__ __forceinline__ void tma_load_2d(uint32_t dst, const CUtensorMap* m, uint32_t bar, int c0, int c1) {
  asm volatile("cp.async.bulk.tensor.2d.shared::cluster.global.mbarrier::complete_tx::bytes [%0], [%1, {%3, %4}], [%2];"
               ::"r"(dst), "l"(m), "r"(bar), "r"(c0), "r"(c1) : "memory");
}
__device__ __forceinline__ void tma_load_3d(uint32_t dst, const CUtensorMap* m, uint32_t bar, int c0, int c1, int c2) {
  asm volatile("cp.async.bulk.tensor.3d.shared::cluster.global.mbarrier::complete_tx::bytes [%0], [%1, {%3, %4, %5}], [%2];"
               ::"r"(dst), "l"(m), "r"(bar), "r"(c0), "r"(c1), "r"(c2) : "memory");
}
__device__ __forceinline__ void tma_store_3d(const CUtensorMap* m, uint32_t src, int c0, int c1, int c2) {
  asm volatile("cp.async.bulk.tensor.3d.global.shared::cta.bulk_group [%0, {%2, %3, %4}], [%1];"
               ::"l"(m), "r"(src), "r"(c0), "r"(c1), "r"(c2) : "memory");
}
__device__ __forceinline__ void bulk_commit() { asm volatile("cp.async.bulk.commit_group;" ::: "memory"); }
__device__ __forceinline__ void bulk_wait_read0() { asm volatile("cp.async.bulk.wait_group.read 0;" ::: "memory"); }
__device__ __forceinline__ void bulk_wait_read1() { asm volatile("cp.async.bulk.wait_group.read 1;" ::: "memory"); }
__device__ __forceinline__ void bulk_wait0() { asm volatile("cp.async.bulk.wait_group 0;" ::: "memory"); }
__device__ __forceinline__ void fence_proxy_async() { asm volatile("fence.proxy.async.shared::cta;" ::: "memory"); }
__device__ __forceinline__ void prefetch_tmap(const CUtensorMap* m) {
  asm volatile("prefetch.tensormap [%0];" ::"l"(m) : "memory");
}
__device__ __forceinline__ void wg_fence() { asm volatile("wgmma.fence.sync.aligned;" ::: "memory"); }
__device__ __forceinline__ void wg_commit() { asm volatile("wgmma.commit_group.sync.aligned;" ::: "memory"); }
template <int N> __device__ __forceinline__ void wg_wait() { asm volatile("wgmma.wait_group.sync.aligned %0;" ::"n"(N) : "memory"); }
__device__ __forceinline__ void named_bar(int id, int nthreads) {
  asm volatile("bar.sync %0, %1;" ::"r"(id), "r"(nthreads) : "memory");
}
__device__ __forceinline__ void ldsm_x4(uint32_t (&r)[4], uint32_t addr) {
  asm volatile("ldmatrix.sync.aligned.m8n8.x4.shared.b16 {%0,%1,%2,%3}, [%4];"
               : "=r"(r[0]), "=r"(r[1]), "=r"(r[2]), "=r"(r[3]) : "r"(addr) : "memory");
}
__device__ __forceinline__ void stsm_x4(uint32_t addr, const uint32_t (&r)[4]) {
  asm volatile("stmatrix.sync.aligned.m8n8.x4.shared.b16 [%0], {%1,%2,%3,%4};"
               ::"r"(addr), "r"(r[0]), "r"(r[1]), "r"(r[2]), "r"(r[3]) : "memory");
}
__device__ __forceinline__ uint32_t pack_bf16(float lo, float hi) {
  uint32_t r;
  asm("cvt.rn.bf16x2.f32 %0, %1, %2;" : "=r"(r) : "f"(hi), "f"(lo));
  return r;
}
__device__ __forceinline__ float bf_lo(uint32_t v) { return __uint_as_float(v << 16); }
__device__ __forceinline__ float bf_hi(uint32_t v) { return __uint_as_float(v & 0xffff0000u); }
__device__ __forceinline__ float ex2(float x) {
  float y;
  asm("ex2.approx.ftz.f32 %0, %1;" : "=f"(y) : "f"(x));
  return y;
}
__device__ __forceinline__ uint64_t mk_desc(uint32_t addr, uint32_t lbo, uint32_t sbo) {
  return (uint64_t)((addr & 0x3FFFF) >> 4) | ((uint64_t)((lbo & 0x3FFFF) >> 4) << 16) |
         ((uint64_t)((sbo & 0x3FFFF) >> 4) << 32) | (1ull << 62);
}
__device__ __forceinline__ uint64_t mk_desc_o(uint32_t addr, uint32_t lbo, uint32_t sbo) {
  asm volatile("" : "+r"(addr));
  return mk_desc(addr, lbo, sbo);
}
template <int N> __device__ __forceinline__ void reg_fence(uint32_t (&d)[N]) {
#pragma unroll
  for (int i = 0; i < N; i++) asm volatile("" : "+r"(d[i])::"memory");
}
template <int N> __device__ __forceinline__ void reg_fence(float (&d)[N]) {
#pragma unroll
  for (int i = 0; i < N; i++) asm volatile("" : "+f"(d[i])::"memory");
}

template<int TB> __device__ __forceinline__ void wgmma_n144_ss(float (&d)[72], uint64_t da, uint64_t db, int sc) {
  asm volatile("{\n.reg .pred p;\nsetp.ne.b32 p, %74, 0;\n"
    "wgmma.mma_async.sync.aligned.m64n144k16.f32.bf16.bf16 {%0, %1, %2, %3, %4, %5, %6, %7, %8, %9, %10, %11, %12, %13, %14, %15, %16, %17, %18, %19, %20, %21, %22, %23, %24, %25, %26, %27, %28, %29, %30, %31, %32, %33, %34, %35, %36, %37, %38, %39, %40, %41, %42, %43, %44, %45, %46, %47, %48, %49, %50, %51, %52, %53, %54, %55, %56, %57, %58, %59, %60, %61, %62, %63, %64, %65, %66, %67, %68, %69, %70, %71}, %72, %73, p, 1, 1, 0, %75;\n}\n"
    : "+f"(d[0]), "+f"(d[1]), "+f"(d[2]), "+f"(d[3]), "+f"(d[4]), "+f"(d[5]), "+f"(d[6]), "+f"(d[7]), "+f"(d[8]), "+f"(d[9]), "+f"(d[10]), "+f"(d[11]), "+f"(d[12]), "+f"(d[13]), "+f"(d[14]), "+f"(d[15]), "+f"(d[16]), "+f"(d[17]), "+f"(d[18]), "+f"(d[19]), "+f"(d[20]), "+f"(d[21]), "+f"(d[22]), "+f"(d[23]), "+f"(d[24]), "+f"(d[25]), "+f"(d[26]), "+f"(d[27]), "+f"(d[28]), "+f"(d[29]), "+f"(d[30]), "+f"(d[31]), "+f"(d[32]), "+f"(d[33]), "+f"(d[34]), "+f"(d[35]), "+f"(d[36]), "+f"(d[37]), "+f"(d[38]), "+f"(d[39]), "+f"(d[40]), "+f"(d[41]), "+f"(d[42]), "+f"(d[43]), "+f"(d[44]), "+f"(d[45]), "+f"(d[46]), "+f"(d[47]), "+f"(d[48]), "+f"(d[49]), "+f"(d[50]), "+f"(d[51]), "+f"(d[52]), "+f"(d[53]), "+f"(d[54]), "+f"(d[55]), "+f"(d[56]), "+f"(d[57]), "+f"(d[58]), "+f"(d[59]), "+f"(d[60]), "+f"(d[61]), "+f"(d[62]), "+f"(d[63]), "+f"(d[64]), "+f"(d[65]), "+f"(d[66]), "+f"(d[67]), "+f"(d[68]), "+f"(d[69]), "+f"(d[70]), "+f"(d[71])
    : "l"(da), "l"(db), "r"(sc), "n"(TB));
}
template<int TB> __device__ __forceinline__ void wgmma_n192_rs(float (&d)[96], const uint32_t (&a)[4], uint64_t db, int sc) {
  asm volatile("{\n.reg .pred p;\nsetp.ne.b32 p, %101, 0;\n"
    "wgmma.mma_async.sync.aligned.m64n192k16.f32.bf16.bf16 {%0, %1, %2, %3, %4, %5, %6, %7, %8, %9, %10, %11, %12, %13, %14, %15, %16, %17, %18, %19, %20, %21, %22, %23, %24, %25, %26, %27, %28, %29, %30, %31, %32, %33, %34, %35, %36, %37, %38, %39, %40, %41, %42, %43, %44, %45, %46, %47, %48, %49, %50, %51, %52, %53, %54, %55, %56, %57, %58, %59, %60, %61, %62, %63, %64, %65, %66, %67, %68, %69, %70, %71, %72, %73, %74, %75, %76, %77, %78, %79, %80, %81, %82, %83, %84, %85, %86, %87, %88, %89, %90, %91, %92, %93, %94, %95}, {%96, %97, %98, %99}, %100, p, 1, 1, %102;\n}\n"
    : "+f"(d[0]), "+f"(d[1]), "+f"(d[2]), "+f"(d[3]), "+f"(d[4]), "+f"(d[5]), "+f"(d[6]), "+f"(d[7]), "+f"(d[8]), "+f"(d[9]), "+f"(d[10]), "+f"(d[11]), "+f"(d[12]), "+f"(d[13]), "+f"(d[14]), "+f"(d[15]), "+f"(d[16]), "+f"(d[17]), "+f"(d[18]), "+f"(d[19]), "+f"(d[20]), "+f"(d[21]), "+f"(d[22]), "+f"(d[23]), "+f"(d[24]), "+f"(d[25]), "+f"(d[26]), "+f"(d[27]), "+f"(d[28]), "+f"(d[29]), "+f"(d[30]), "+f"(d[31]), "+f"(d[32]), "+f"(d[33]), "+f"(d[34]), "+f"(d[35]), "+f"(d[36]), "+f"(d[37]), "+f"(d[38]), "+f"(d[39]), "+f"(d[40]), "+f"(d[41]), "+f"(d[42]), "+f"(d[43]), "+f"(d[44]), "+f"(d[45]), "+f"(d[46]), "+f"(d[47]), "+f"(d[48]), "+f"(d[49]), "+f"(d[50]), "+f"(d[51]), "+f"(d[52]), "+f"(d[53]), "+f"(d[54]), "+f"(d[55]), "+f"(d[56]), "+f"(d[57]), "+f"(d[58]), "+f"(d[59]), "+f"(d[60]), "+f"(d[61]), "+f"(d[62]), "+f"(d[63]), "+f"(d[64]), "+f"(d[65]), "+f"(d[66]), "+f"(d[67]), "+f"(d[68]), "+f"(d[69]), "+f"(d[70]), "+f"(d[71]), "+f"(d[72]), "+f"(d[73]), "+f"(d[74]), "+f"(d[75]), "+f"(d[76]), "+f"(d[77]), "+f"(d[78]), "+f"(d[79]), "+f"(d[80]), "+f"(d[81]), "+f"(d[82]), "+f"(d[83]), "+f"(d[84]), "+f"(d[85]), "+f"(d[86]), "+f"(d[87]), "+f"(d[88]), "+f"(d[89]), "+f"(d[90]), "+f"(d[91]), "+f"(d[92]), "+f"(d[93]), "+f"(d[94]), "+f"(d[95])
    : "r"(a[0]), "r"(a[1]), "r"(a[2]), "r"(a[3]), "l"(db), "r"(sc), "n"(TB));
}
template<int TB> __device__ __forceinline__ void wgmma_n64_ss(float (&d)[32], uint64_t da, uint64_t db, int sc) {
  asm volatile("{\n.reg .pred p;\nsetp.ne.b32 p, %34, 0;\n"
    "wgmma.mma_async.sync.aligned.m64n64k16.f32.bf16.bf16 {%0, %1, %2, %3, %4, %5, %6, %7, %8, %9, %10, %11, %12, %13, %14, %15, %16, %17, %18, %19, %20, %21, %22, %23, %24, %25, %26, %27, %28, %29, %30, %31}, %32, %33, p, 1, 1, 0, %35;\n}\n"
    : "+f"(d[0]), "+f"(d[1]), "+f"(d[2]), "+f"(d[3]), "+f"(d[4]), "+f"(d[5]), "+f"(d[6]), "+f"(d[7]), "+f"(d[8]), "+f"(d[9]), "+f"(d[10]), "+f"(d[11]), "+f"(d[12]), "+f"(d[13]), "+f"(d[14]), "+f"(d[15]), "+f"(d[16]), "+f"(d[17]), "+f"(d[18]), "+f"(d[19]), "+f"(d[20]), "+f"(d[21]), "+f"(d[22]), "+f"(d[23]), "+f"(d[24]), "+f"(d[25]), "+f"(d[26]), "+f"(d[27]), "+f"(d[28]), "+f"(d[29]), "+f"(d[30]), "+f"(d[31])
    : "l"(da), "l"(db), "r"(sc), "n"(TB));
}
template<int TB> __device__ __forceinline__ void wgmma_n72_st(float (&d)[36], uint64_t da, uint64_t db, int sc) {
  asm volatile("{\n.reg .pred p;\nsetp.ne.b32 p, %38, 0;\n"
    "wgmma.mma_async.sync.aligned.m64n72k16.f32.bf16.bf16 {%0, %1, %2, %3, %4, %5, %6, %7, %8, %9, %10, %11, %12, %13, %14, %15, %16, %17, %18, %19, %20, %21, %22, %23, %24, %25, %26, %27, %28, %29, %30, %31, %32, %33, %34, %35}, %36, %37, p, 1, 1, 1, %39;\n}\n"
    : "+f"(d[0]), "+f"(d[1]), "+f"(d[2]), "+f"(d[3]), "+f"(d[4]), "+f"(d[5]), "+f"(d[6]), "+f"(d[7]), "+f"(d[8]), "+f"(d[9]), "+f"(d[10]), "+f"(d[11]), "+f"(d[12]), "+f"(d[13]), "+f"(d[14]), "+f"(d[15]), "+f"(d[16]), "+f"(d[17]), "+f"(d[18]), "+f"(d[19]), "+f"(d[20]), "+f"(d[21]), "+f"(d[22]), "+f"(d[23]), "+f"(d[24]), "+f"(d[25]), "+f"(d[26]), "+f"(d[27]), "+f"(d[28]), "+f"(d[29]), "+f"(d[30]), "+f"(d[31]), "+f"(d[32]), "+f"(d[33]), "+f"(d[34]), "+f"(d[35])
    : "l"(da), "l"(db), "r"(sc), "n"(TB));
}
template<int TB> __device__ __forceinline__ void wgmma_n80_ss(float (&d)[40], uint64_t da, uint64_t db, int sc) {
  asm volatile("{\n.reg .pred p;\nsetp.ne.b32 p, %42, 0;\n"
    "wgmma.mma_async.sync.aligned.m64n80k16.f32.bf16.bf16 {%0, %1, %2, %3, %4, %5, %6, %7, %8, %9, %10, %11, %12, %13, %14, %15, %16, %17, %18, %19, %20, %21, %22, %23, %24, %25, %26, %27, %28, %29, %30, %31, %32, %33, %34, %35, %36, %37, %38, %39}, %40, %41, p, 1, 1, 0, %43;\n}\n"
    : "+f"(d[0]), "+f"(d[1]), "+f"(d[2]), "+f"(d[3]), "+f"(d[4]), "+f"(d[5]), "+f"(d[6]), "+f"(d[7]), "+f"(d[8]), "+f"(d[9]), "+f"(d[10]), "+f"(d[11]), "+f"(d[12]), "+f"(d[13]), "+f"(d[14]), "+f"(d[15]), "+f"(d[16]), "+f"(d[17]), "+f"(d[18]), "+f"(d[19]), "+f"(d[20]), "+f"(d[21]), "+f"(d[22]), "+f"(d[23]), "+f"(d[24]), "+f"(d[25]), "+f"(d[26]), "+f"(d[27]), "+f"(d[28]), "+f"(d[29]), "+f"(d[30]), "+f"(d[31]), "+f"(d[32]), "+f"(d[33]), "+f"(d[34]), "+f"(d[35]), "+f"(d[36]), "+f"(d[37]), "+f"(d[38]), "+f"(d[39])
    : "l"(da), "l"(db), "r"(sc), "n"(TB));
}

struct FragAddr {
  uint32_t rowoff;
  uint32_t rx;
  uint32_t hi;
  __device__ __forceinline__ FragAddr(int warp_in_wg, int lane) {
    int row = 16 * warp_in_wg + (lane & 7) + ((lane >> 3) & 1) * 8;
    rowoff = row * 128;
    rx = row & 7;
    hi = lane >> 4;
  }
  __device__ __forceinline__ uint32_t at(uint32_t chunk_base, int kk4) const {
    return chunk_base + rowoff + ((((uint32_t)kk4 * 2 + hi) ^ rx) << 4);
  }
};

__device__ __forceinline__ void layernorm_frags(uint32_t (&f)[12][4]) {
  float s0[2] = {0.f, 0.f}, s1[2] = {0.f, 0.f}, q0[2] = {0.f, 0.f}, q1[2] = {0.f, 0.f};
#pragma unroll
  for (int k = 0; k < 12; k++) {
#pragma unroll
    for (int hf = 0; hf < 2; hf++) {
      const float a = bf_lo(f[k][2 * hf]), b = bf_hi(f[k][2 * hf]);
      const float c = bf_lo(f[k][2 * hf + 1]), d = bf_hi(f[k][2 * hf + 1]);
      s0[hf] += a + b; q0[hf] = fmaf(a, a, fmaf(b, b, q0[hf]));
      s1[hf] += c + d; q1[hf] = fmaf(c, c, fmaf(d, d, q1[hf]));
    }
  }
  float sa = s0[0] + s0[1], sb_ = s1[0] + s1[1], qa = q0[0] + q0[1], qb_ = q1[0] + q1[1];
  sa += __shfl_xor_sync(0xffffffffu, sa, 1); sb_ += __shfl_xor_sync(0xffffffffu, sb_, 1);
  qa += __shfl_xor_sync(0xffffffffu, qa, 1); qb_ += __shfl_xor_sync(0xffffffffu, qb_, 1);
  sa += __shfl_xor_sync(0xffffffffu, sa, 2); sb_ += __shfl_xor_sync(0xffffffffu, sb_, 2);
  qa += __shfl_xor_sync(0xffffffffu, qa, 2); qb_ += __shfl_xor_sync(0xffffffffu, qb_, 2);
  const float m0 = sa * (1.f / 192.f), m1 = sb_ * (1.f / 192.f);
  const float v0 = fmaxf(fmaf(-m0, m0, qa * (1.f / 192.f)), 0.f), v1 = fmaxf(fmaf(-m1, m1, qb_ * (1.f / 192.f)), 0.f);
  const float r0 = rsqrtf(v0 + 1e-5f), r1 = rsqrtf(v1 + 1e-5f);
  const float c0 = -m0 * r0, c1 = -m1 * r1;
#pragma unroll
  for (int k = 0; k < 12; k++) {
    f[k][0] = pack_bf16(fmaf(bf_lo(f[k][0]), r0, c0), fmaf(bf_hi(f[k][0]), r0, c0));
    f[k][2] = pack_bf16(fmaf(bf_lo(f[k][2]), r0, c0), fmaf(bf_hi(f[k][2]), r0, c0));
    f[k][1] = pack_bf16(fmaf(bf_lo(f[k][1]), r1, c1), fmaf(bf_hi(f[k][1]), r1, c1));
    f[k][3] = pack_bf16(fmaf(bf_lo(f[k][3]), r1, c1), fmaf(bf_hi(f[k][3]), r1, c1));
  }
}

constexpr int A_NST = 4;
constexpr int A_HB = 0;
constexpr int A_VB = 30720;
constexpr int A_QB = 61440;
constexpr int A_W = 110592;
constexpr int A_BAR = A_W + A_NST * 24576;
constexpr int A_SMEM = A_BAR + 256 + 1024;
constexpr int A_GRID = 130;
constexpr int A_FOLD = 36;

__device__ __forceinline__ void stsm_x4_t(uint32_t addr, uint32_t r0, uint32_t r1, uint32_t r2, uint32_t r3) {
  asm volatile("stmatrix.sync.aligned.m8n8.x4.trans.shared.b16 [%0], {%1,%2,%3,%4};"
               ::"r"(addr), "r"(r0), "r"(r1), "r"(r2), "r"(r3) : "memory");
}
__device__ __forceinline__ void stsm_x2_t(uint32_t addr, uint32_t r0, uint32_t r1) {
  asm volatile("stmatrix.sync.aligned.m8n8.x2.trans.shared.b16 [%0], {%1,%2};" ::"r"(addr), "r"(r0), "r"(r1) : "memory");
}
__device__ __forceinline__ void a_issue(float (&acc)[36], uint32_t sb, int s) {
  const int st = s % A_NST;
  mbar_wait(sb + A_BAR + st * 8, (s / A_NST) & 1);
  const uint64_t wd = mk_desc_o(sb + A_W + st * 24576, 8192, 1024);
  const uint64_t hd = mk_desc_o(sb + A_HB, 16, 1024);
  wg_fence();
#pragma unroll
  for (int kk = 0; kk < 12; kk++) wgmma_n72_st<0>(acc, wd + kk * 128, hd + (kk >> 2) * 640 + (kk & 3) * 2, kk > 0);
  wg_commit();
}
__device__ __forceinline__ void a_release(uint32_t sb, int s, int lane) {
  if (lane == 0) mbar_arrive(sb + A_BAR + 64 + (s % A_NST) * 8);
}
__device__ __forceinline__ void store_chunk_t(const float (&d)[36], uint32_t chunk_base, int wq, int lane) {
  const int mi = lane >> 3, i = lane & 7;
  const uint32_t cc = 2 * wq + (mi & 1);
  const uint32_t base = chunk_base + ((mi >> 1) * 8 + i) * 128 + ((cc ^ i) << 4);
#pragma unroll
  for (int j = 0; j < 8; j += 2)
    stsm_x4_t(base + j * 1024, pack_bf16(d[4 * j], d[4 * j + 1]), pack_bf16(d[4 * j + 2], d[4 * j + 3]),
              pack_bf16(d[4 * j + 4], d[4 * j + 5]), pack_bf16(d[4 * j + 6], d[4 * j + 7]));
  stsm_x2_t(chunk_base + (64 + i) * 128 + ((cc ^ i) << 4), pack_bf16(d[32], d[33]), pack_bf16(d[34], d[35]));
}
__device__ __forceinline__ void resid_chunk(uint32_t (*dst)[4], const float* acc, float s0, float s1, uint32_t chunk_base,
                                            const FragAddr& fa) {
#pragma unroll
  for (int k = 0; k < 4; k++) {
    uint32_t x[4];
    ldsm_x4(x, fa.at(chunk_base, k));
    uint32_t o[4];
    o[0] = pack_bf16(fmaf(acc[8 * k + 0], s0, bf_lo(x[0])), fmaf(acc[8 * k + 1], s0, bf_hi(x[0])));
    o[1] = pack_bf16(fmaf(acc[8 * k + 2], s1, bf_lo(x[1])), fmaf(acc[8 * k + 3], s1, bf_hi(x[1])));
    o[2] = pack_bf16(fmaf(acc[8 * k + 4], s0, bf_lo(x[2])), fmaf(acc[8 * k + 5], s0, bf_hi(x[2])));
    o[3] = pack_bf16(fmaf(acc[8 * k + 6], s1, bf_lo(x[3])), fmaf(acc[8 * k + 7], s1, bf_hi(x[3])));
    stsm_x4(fa.at(chunk_base, k), o);
    if (dst) { dst[k][0] = o[0]; dst[k][1] = o[1]; dst[k][2] = o[2]; dst[k][3] = o[3]; }
  }
}

__global__ void __launch_bounds__(384, 1)
kernelA(const __grid_constant__ CUtensorMap tm_x, const __grid_constant__ CUtensorMap tm_wq64t,
        const __grid_constant__ CUtensorMap tm_wot, const __grid_constant__ CUtensorMap tm_wq64s,
        const __grid_constant__ CUtensorMap tm_wos, const __grid_constant__ CUtensorMap tm_wf,
        const __grid_constant__ CUtensorMap tm_x1, const __grid_constant__ CUtensorMap tm_qkv) {
  extern __shared__ uint8_t smem_raw[];
  const uint32_t sb = (smem_u32(smem_raw) + 1023) & ~1023u;
  const int tid = threadIdx.x, warp = tid >> 5, lane = tid & 31;
  const bool is_fold = blockIdx.x < A_FOLD;
  const int n0 = blockIdx.x * 10;
  const uint32_t bX = sb + A_BAR + 128, bFF = sb + A_BAR + 136, bFD = sb + A_BAR + 144;
  if (tid == 256) {
    for (int i = 0; i < A_NST; i++) { mbar_init(sb + A_BAR + i * 8, 1); mbar_init(sb + A_BAR + 64 + i * 8, 4); }
    mbar_init(bX, 1); mbar_init(bFF, 1); mbar_init(bFD, 4);
    asm volatile("fence.mbarrier_init.release.cluster;" ::: "memory");
    if (is_fold) {
      const int mat = blockIdx.x / 9, rs = (blockIdx.x % 9) / 3, cs = blockIdx.x % 3;
      const CUtensorMap* mq = (mat < 2) ? &tm_wq64t : &tm_wq64s;
      const CUtensorMap* mo = (mat < 2) ? &tm_wot : &tm_wos;
      mbar_expect_tx(bFF, 2 * 24576);
      for (int c = 0; c < 3; c++) tma_load_2d(sb + A_W + c * 8192, mq, bFF, ((mat & 1) ? 384 : 0) + c * 64, rs * 64);
      if (mat & 1) tma_load_2d(sb + A_W + 24576, mo, bFF, cs * 64, 0);
      else for (int c = 0; c < 3; c++) tma_load_2d(sb + A_W + 24576 + c * 8192, mq, bFF, 192 + c * 64, cs * 64);
    }
    mbar_expect_tx(bX, 3 * 70 * 128);
    for (int c = 0; c < 3; c++) tma_load_3d(sb + A_VB + c * 10240, &tm_x, bX, c * 64, n0, 0);
  }
  asm volatile("griddepcontrol.launch_dependents;" ::: "memory");
  if (blockIdx.x == 129 && tid < 128) g_flag[tid] = 0;
  if (tid < 240) {
    const uint32_t a = sb + A_VB + (tid / 80) * 10240 + 70 * 128 + (tid % 80) * 16;
    asm volatile("st.shared.v4.b32 [%0], {%1,%1,%1,%1};" ::"r"(a), "r"(0) : "memory");
  }
  __syncthreads();

  if (warp >= 8) {
    asm volatile("setmaxnreg.dec.sync.aligned.u32 24;");
    if (warp == 8 && lane == 0) {
      if (is_fold) mbar_wait(bFD, 0);
      for (int s = 0; s < 12; s++) {
        const int st = s % A_NST;
        const int g = s / 3;
        const int mat = (g == 0) ? 1 : (g == 1) ? 0 : g;
        if (s % 3 == 0) {
          uint32_t n = 0, v;
          do {
            asm volatile("ld.acquire.gpu.global.u32 %0, [%1];" : "=r"(v) : "l"(&g_wflag[mat]) : "memory");
          } while (v < 9u && ++n < (1u << 22));
          asm volatile("fence.proxy.async;" ::: "memory");
        }
        if (s >= A_NST) mbar_wait(sb + A_BAR + 64 + st * 8, ((s / A_NST) - 1) & 1);
        mbar_expect_tx(sb + A_BAR + st * 8, 24576);
        tma_load_2d(sb + A_W + st * 24576, &tm_wf, sb + A_BAR + st * 8, (mat & 1) * 192 + (s % 3) * 64, (mat >> 1) * 192);
      }
    }
    return;
  }

  asm volatile("setmaxnreg.inc.sync.aligned.u32 240;");
  const int wg = warp >> 2, wq = warp & 3;
  const bool elected = (tid & 127) == 0;
  TS(0, 0);

  if (is_fold && wg == 1) {
    const int mat = blockIdx.x / 9, rs = (blockIdx.x % 9) / 3, cs = blockIdx.x % 3;
    float d[32];
    mbar_wait(bFF, 0);
    const uint64_t ad = mk_desc_o(sb + A_W, 16, 1024);
    if (mat & 1) {
      const uint64_t bd = mk_desc_o(sb + A_W + 24576, 8192, 1024);
      wg_fence();
#pragma unroll
      for (int kk = 0; kk < 12; kk++) wgmma_n64_ss<1>(d, ad + (kk >> 2) * 512 + (kk & 3) * 2, bd + kk * 128, kk > 0);
      wg_commit();
    } else {
      const uint64_t bd = mk_desc_o(sb + A_W + 24576, 16, 1024);
      wg_fence();
#pragma unroll
      for (int kk = 0; kk < 12; kk++)
        wgmma_n64_ss<0>(d, ad + (kk >> 2) * 512 + (kk & 3) * 2, bd + (kk >> 2) * 512 + (kk & 3) * 2, kk > 0);
      wg_commit();
    }
    wg_wait<0>(); reg_fence(d);
    if (lane == 0) mbar_arrive(bFD);
    const int r0 = rs * 64 + wq * 16 + (lane >> 2);
    uint32_t* dst = reinterpret_cast<uint32_t*>(g_wf + ((size_t)(mat >> 1) * 192 + r0) * 384 + (mat & 1) * 192 + cs * 64 + (lane & 3) * 2);
#pragma unroll
    for (int j = 0; j < 8; j++) {
      dst[j * 4] = pack_bf16(d[4 * j], d[4 * j + 1]);
      dst[8 * 192 + j * 4] = pack_bf16(d[4 * j + 2], d[4 * j + 3]);
    }
    asm volatile("fence.proxy.async;" ::: "memory");
    named_bar(2, 128);
    if (elected) { __threadfence(); atomicAdd(&g_wflag[mat], 1u); }
  }

  const bool rows_ok = warp < 5;
  const FragAddr fa(warp, lane);
  uint32_t h[12][4];
  if (rows_ok) {
    mbar_wait(bX, 0);
#pragma unroll
    for (int k = 0; k < 12; k++) ldsm_x4(h[k], fa.at(sb + A_VB + (k >> 2) * 10240, k & 3));
    layernorm_frags(h);
#pragma unroll
    for (int k = 0; k < 12; k++) stsm_x4(fa.at(sb + A_HB + (k >> 2) * 10240, k & 3), h[k]);
  }
  fence_proxy_async();
  named_bar(1, 256);
  TS(0, 1);

  float acc0[36], acc1[36];
  {
    auto dst1 = [&](int s) { return s < 3 ? sb + A_VB + s * 10240 : sb + A_QB + (s - 3) * 16384; };
    a_issue(acc0, sb, wg);
    TS(0, 2);
    a_issue(acc1, sb, wg + 2); wg_wait<1>(); reg_fence(acc0); a_release(sb, wg, lane); store_chunk_t(acc0, dst1(wg), wq, lane);
    a_issue(acc0, sb, wg + 4); wg_wait<1>(); reg_fence(acc1); a_release(sb, wg + 2, lane); store_chunk_t(acc1, dst1(wg + 2), wq, lane);
    wg_wait<0>(); reg_fence(acc0); a_release(sb, wg + 4, lane); store_chunk_t(acc0, dst1(wg + 4), wq, lane);
  }
  fence_proxy_async();
  named_bar(1, 256);
  TS(0, 3);
  uint32_t pf[5][4];
  {
    float sacc[40];
    const uint64_t qd = mk_desc_o(sb + A_QB + wg * 8192, 16, 1024);
    const uint64_t kd = mk_desc_o(sb + A_HB, 16, 1024);
    wg_fence();
#pragma unroll
    for (int kk = 0; kk < 12; kk++)
      wgmma_n80_ss<0>(sacc, qd + (kk >> 2) * 1024 + (kk & 3) * 2, kd + (kk >> 2) * 640 + (kk & 3) * 2, kk > 0);
    wg_commit();
    wg_wait<0>(); reg_fence(sacc);
    named_bar(1, 256);
    if (tid == 0) {
      mbar_expect_tx(bX, 3 * 70 * 128);
      for (int c = 0; c < 3; c++) tma_load_3d(sb + A_QB + c * 16384, &tm_x, bX, c * 64, n0, 0);
    }
    TS(0, 4);
    const int r0 = 16 * warp + (lane >> 2), r1 = r0 + 8;
    const unsigned long long MLO = 0x1004010040100401ull;
    const int sh = 2 * (lane & 3);
    unsigned long long lo0, lo1; uint32_t hi0, hi1;
    {
      const int a = r0 % 10, b = r1 % 10;
      unsigned long long l = MLO << a; uint32_t hh = a >= 4 ? (1u << (a - 4)) : 0u;
      lo0 = (l >> sh) | (sh ? ((unsigned long long)hh << (64 - sh)) : 0ull); hi0 = hh >> sh;
      l = MLO << b; hh = b >= 4 ? (1u << (b - 4)) : 0u;
      lo1 = (l >> sh) | (sh ? ((unsigned long long)hh << (64 - sh)) : 0ull); hi1 = hh >> sh;
    }
    const float cs = 0.07216878364870322f * 1.4426950408889634f;
    float mx0 = -INFINITY, mx1 = -INFINITY;
#pragma unroll
    for (int j = 0; j < 10; j++) {
#pragma unroll
      for (int e = 0; e < 2; e++) {
        const int pos = 8 * j + e;
        const bool v0 = pos < 64 ? ((lo0 >> pos) & 1) : ((hi0 >> (pos - 64)) & 1);
        const bool v1 = pos < 64 ? ((lo1 >> pos) & 1) : ((hi1 >> (pos - 64)) & 1);
        sacc[4 * j + e] = v0 ? sacc[4 * j + e] * cs : -INFINITY;
        sacc[4 * j + 2 + e] = v1 ? sacc[4 * j + 2 + e] * cs : -INFINITY;
        mx0 = fmaxf(mx0, sacc[4 * j + e]);
        mx1 = fmaxf(mx1, sacc[4 * j + 2 + e]);
      }
    }
    mx0 = fmaxf(mx0, __shfl_xor_sync(0xffffffffu, mx0, 1)); mx1 = fmaxf(mx1, __shfl_xor_sync(0xffffffffu, mx1, 1));
    mx0 = fmaxf(mx0, __shfl_xor_sync(0xffffffffu, mx0, 2)); mx1 = fmaxf(mx1, __shfl_xor_sync(0xffffffffu, mx1, 2));
    float l0 = 0.f, l1 = 0.f;
#pragma unroll
    for (int j = 0; j < 10; j++) {
#pragma unroll
      for (int e = 0; e < 2; e++) {
        sacc[4 * j + e] = ex2(sacc[4 * j + e] - mx0); l0 += sacc[4 * j + e];
        sacc[4 * j + 2 + e] = ex2(sacc[4 * j + 2 + e] - mx1); l1 += sacc[4 * j + 2 + e];
      }
    }
    l0 += __shfl_xor_sync(0xffffffffu, l0, 1); l1 += __shfl_xor_sync(0xffffffffu, l1, 1);
    l0 += __shfl_xor_sync(0xffffffffu, l0, 2); l1 += __shfl_xor_sync(0xffffffffu, l1, 2);
    const float i0 = 1.f / l0, i1 = 1.f / l1;
#pragma unroll
    for (int k = 0; k < 5; k++) {
      pf[k][0] = pack_bf16(sacc[8 * k + 0] * i0, sacc[8 * k + 1] * i0); pf[k][1] = pack_bf16(sacc[8 * k + 2] * i1, sacc[8 * k + 3] * i1);
      pf[k][2] = pack_bf16(sacc[8 * k + 4] * i0, sacc[8 * k + 5] * i0); pf[k][3] = pack_bf16(sacc[8 * k + 6] * i1, sacc[8 * k + 7] * i1);
    }
  }
  TS(0, 5);
  {
    float oacc[96];
    const uint64_t vd = mk_desc_o(sb + A_VB, 10240, 1024);
    wg_fence();
#pragma unroll
    for (int kk = 0; kk < 5; kk++) wgmma_n192_rs<1>(oacc, pf[kk], vd + kk * 128, kk > 0);
    wg_commit();
    wg_wait<0>(); reg_fence(oacc);
    TS(0, 6);
    if (rows_ok) {
      mbar_wait(bX, 1);
#pragma unroll
      for (int c = 0; c < 3; c++) resid_chunk(&h[4 * c], &oacc[32 * c], 1.f, 1.f, sb + A_QB + c * 16384, fa);
      layernorm_frags(h);
#pragma unroll
      for (int k = 0; k < 12; k++) stsm_x4(fa.at(sb + A_HB + (k >> 2) * 10240, k & 3), h[k]);
    }
  }
  fence_proxy_async();
  named_bar(1, 256);
  TS(0, 7);
  if (tid == 0) {
    for (int c = 0; c < 3; c++) tma_store_3d(&tm_x1, sb + A_QB + c * 16384, c * 64, n0, 0);
    bulk_commit();
    for (int c = 0; c < 3; c++) tma_store_3d(&tm_qkv, sb + A_HB + c * 10240, 192 + c * 64, n0, 0);
    bulk_commit();
  }
  {
    auto dst2 = [&](int s) { return s < 9 ? sb + A_VB + (s - 6) * 10240 : sb + A_QB + (s - 9) * 16384; };
    auto flush = [&](int s) {
      fence_proxy_async();
      named_bar(2 + wg, 128);
      if (elected) { tma_store_3d(&tm_qkv, dst2(s), (s < 9 ? (s - 6) * 64 : 384 + (s - 9) * 64), n0, 0); bulk_commit(); }
    };
    a_issue(acc0, sb, 6 + wg);
    a_issue(acc1, sb, 8 + wg); wg_wait<1>(); reg_fence(acc0); a_release(sb, 6 + wg, lane);
    store_chunk_t(acc0, dst2(6 + wg), wq, lane);
    if (tid == 0) bulk_wait_read1();
    named_bar(1, 256);
    flush(6 + wg);
    a_issue(acc0, sb, 10 + wg); wg_wait<1>(); reg_fence(acc1);
    store_chunk_t(acc1, dst2(8 + wg), wq, lane);
    flush(8 + wg);
    wg_wait<0>(); reg_fence(acc0);
    store_chunk_t(acc0, dst2(10 + wg), wq, lane);
    flush(10 + wg);
  }
  TS(0, 9);
  if (elected) bulk_wait_read0();
  TS(0, 10);
}

constexpr int B_GRID = 132;
constexpr int B_SLOT = 55296;
constexpr int B_Q = 0;
constexpr int B_KV = 49152;
constexpr int B_BAR = B_KV + 3 * B_SLOT;
constexpr int B_SMEM = B_BAR + 256 + 1024;

__device__ __forceinline__ void bar_arrive(int id, int nthreads) {
  asm volatile("bar.arrive %0, %1;" ::"r"(id), "r"(nthreads) : "memory");
}
#define PP_MODE 0
#define PP_WAIT(x, y) named_bar(x, y)
#define PP_ARRIVE(x, y) bar_arrive(x, y)
__device__ __forceinline__ void b_segment(int sg, int& tile, int& k0, int& k1) {
  const int grp = blockIdx.x / 12, ci = blockIdx.x - grp * 12;
  if (ci < 7) { tile = grp * 7 + ci; k0 = 3; k1 = 9; }
  else {
    const int hh = ci - 7;
    tile = grp * 7 + ((0x54210 >> (4 * hh)) & 15) + sg;
    k0 = sg ? 0 : ((0x10210 >> (4 * hh)) & 15);
    k1 = sg ? ((0x31321 >> (4 * hh)) & 15) : 3;
  }
}

__global__ void __launch_bounds__(384, 1)
kernelB(const __grid_constant__ CUtensorMap tm_q, const __grid_constant__ CUtensorMap tm_kv,
        const __grid_constant__ CUtensorMap tm_x1, const __grid_constant__ CUtensorMap tm_out) {
  extern __shared__ uint8_t smem_raw[];
  const uint32_t sb = (smem_u32(smem_raw) + 1023) & ~1023u;
  const int tid = threadIdx.x, warp = tid >> 5, lane = tid & 31;
  const uint32_t bF = sb + B_BAR, bE = sb + B_BAR + 32, bQF = sb + B_BAR + 64, bQE = sb + B_BAR + 72;
  if (tid == 0) {
    for (int i = 0; i < 3; i++) { mbar_init(bF + i * 8, 1); mbar_init(bE + i * 8, 8); }
    mbar_init(bQF, 1); mbar_init(bQE, 8);
    asm volatile("fence.mbarrier_init.release.cluster;" ::: "memory");
    prefetch_tmap(&tm_q); prefetch_tmap(&tm_kv); prefetch_tmap(&tm_x1); prefetch_tmap(&tm_out);
  }
  __syncthreads();
  asm volatile("griddepcontrol.wait;" ::: "memory");
  const int grp = blockIdx.x / 12, ci = blockIdx.x - grp * 12;
  const bool owner = ci < 7;
  const int nseg = owner ? 1 : 2;

  if (warp >= 8) {
    asm volatile("setmaxnreg.dec.sync.aligned.u32 24;");
    if (warp == 8 && lane == 0) {
      if (blockIdx.x == 0) { g_wflag[0] = 0; g_wflag[1] = 0; g_wflag[2] = 0; g_wflag[3] = 0; }
      int it = 0;
      for (int sg = 0; sg < nseg; sg++) {
        int tile, k0, k1;
        b_segment(sg, tile, k0, k1);
        const int t = tile / 11, qt = tile - t * 11;
        if (sg > 0) mbar_wait(bQE, 0);
        mbar_expect_tx(bQF, 49152);
        for (int c = 0; c < 3; c++) tma_load_3d(sb + B_Q + c * 16384, &tm_q, bQF, c * 64, qt * 128, t);
        const int n = k1 - k0;
        for (int e = 0; e < 2 * n; e++) {
          const int sl = it % 3;
          if (it >= 3) mbar_wait(bE + sl * 8, ((it / 3) - 1) & 1);
#define EXP_NCH 3
          mbar_expect_tx(bF + sl * 8, EXP_NCH * 18432);
          for (int c = 0; c < EXP_NCH; c++)
            tma_load_3d(sb + B_KV + sl * B_SLOT + c * 18432, &tm_kv, bF + sl * 8, 192 + (e & 1) * 192 + c * 64, (k0 + (e >> 1)) * 144, t);
          it++;
        }
      }
      if (owner) {
        const int tile = grp * 7 + ci;
        const int t = tile / 11, qt = tile - t * 11;
        mbar_wait(bQE, 0);
        mbar_expect_tx(bQF, 49152);
        for (int c = 0; c < 3; c++) tma_load_3d(sb + B_Q + c * 16384, &tm_x1, bQF, c * 64, qt * 128, t);
      }
    } else if ((warp == 9 || warp == 10) && !owner) {
      for (int sg = 0; sg < 2; sg++) {
        named_bar(5 + (warp - 9), 160);
        if (lane == 0) {
          __threadfence();
          atomicAdd(&g_flag[(grp * 5 + (ci - 7)) * 2 + sg], 1u);
        }
        __syncwarp();
      }
    }
    return;
  }

  asm volatile("setmaxnreg.inc.sync.aligned.u32 240;");
  const int wg = warp >> 2, wq = warp & 3;
  const int wtid = tid & 127;
  const float cs = 0.07216878364870322f * 1.4426950408889634f;
  float oacc[96], sacc[72];
  uint32_t pf[9][4];
  float m0, m1, l0, l1;
  int it = 0;
  const uint32_t qb = sb + B_Q + wg * 8192;
  if (wg == 1) { PP_ARRIVE(3, 256); }
  TS(1, 0);
  int tsi = 1;

  auto issue_qk = [&](int slot) {
    const uint64_t kd = mk_desc_o(sb + B_KV + slot * B_SLOT, 16, 1024);
    const uint64_t qd = mk_desc_o(qb, 16, 1024);
#pragma unroll
    for (int kk = 0; kk < 12; kk++)
      wgmma_n144_ss<0>(sacc, qd + (kk >> 2) * 1024 + (kk & 3) * 2, kd + (kk >> 2) * 1152 + (kk & 3) * 2, kk > 0);
    wg_commit();
  };
  auto issue_pv = [&](int slot, int accum) {
    const uint64_t vd = mk_desc_o(sb + B_KV + slot * B_SLOT, 18432, 1024);
#pragma unroll
    for (int kk = 0; kk < 9; kk++) wgmma_n192_rs<1>(oacc, pf[kk], vd + kk * 128, kk > 0 ? 1 : accum);
    wg_commit();
  };
  auto softmax = [&](bool first) {
    float t0[4], t1[4];
#pragma unroll
    for (int q = 0; q < 4; q++) {
      t0[q] = fmaxf(sacc[4 * q], sacc[4 * q + 1]);
      t1[q] = fmaxf(sacc[4 * q + 2], sacc[4 * q + 3]);
    }
#pragma unroll
    for (int j = 4; j < 18; j++) {
      t0[j & 3] = fmaxf(t0[j & 3], fmaxf(sacc[4 * j], sacc[4 * j + 1]));
      t1[j & 3] = fmaxf(t1[j & 3], fmaxf(sacc[4 * j + 2], sacc[4 * j + 3]));
    }
    float mx0 = fmaxf(fmaxf(t0[0], t0[1]), fmaxf(t0[2], t0[3]));
    float mx1 = fmaxf(fmaxf(t1[0], t1[1]), fmaxf(t1[2], t1[3]));
    mx0 = fmaxf(mx0, __shfl_xor_sync(0xffffffffu, mx0, 1)); mx1 = fmaxf(mx1, __shfl_xor_sync(0xffffffffu, mx1, 1));
    mx0 = fmaxf(mx0, __shfl_xor_sync(0xffffffffu, mx0, 2)); mx1 = fmaxf(mx1, __shfl_xor_sync(0xffffffffu, mx1, 2));
    if (first) {
      m0 = mx0; m1 = mx1; l0 = 0.f; l1 = 0.f;
    } else {
      const bool need = !((mx0 - m0) * cs <= 8.f) || !((mx1 - m1) * cs <= 8.f);
      if (__any_sync(0xffffffffu, need)) {
        mx0 = fmaxf(mx0, m0); mx1 = fmaxf(mx1, m1);
        const float a0 = ex2((m0 - mx0) * cs), a1 = ex2((m1 - mx1) * cs);
        m0 = mx0; m1 = mx1;
        l0 *= a0; l1 *= a1;
#pragma unroll
        for (int i = 0; i < 24; i++) {
          oacc[4 * i] *= a0; oacc[4 * i + 1] *= a0; oacc[4 * i + 2] *= a1; oacc[4 * i + 3] *= a1;
        }
      }
    }
    const float mc0 = m0 * cs, mc1 = m1 * cs;
#pragma unroll
    for (int q = 0; q < 4; q++) { t0[q] = 0.f; t1[q] = 0.f; }
#pragma unroll
    for (int k = 0; k < 9; k++) {
      float p[8];
#pragma unroll
      for (int e = 0; e < 8; e++) p[e] = ex2(fmaf(sacc[8 * k + e], cs, (e & 2) ? -mc1 : -mc0));
      t0[0] += p[0]; t0[1] += p[1]; t0[2] += p[4]; t0[3] += p[5];
      t1[0] += p[2]; t1[1] += p[3]; t1[2] += p[6]; t1[3] += p[7];
      pf[k][0] = pack_bf16(p[0], p[1]); pf[k][1] = pack_bf16(p[2], p[3]);
      pf[k][2] = pack_bf16(p[4], p[5]); pf[k][3] = pack_bf16(p[6], p[7]);
    }
    l0 += (t0[0] + t0[1]) + (t0[2] + t0[3]);
    l1 += (t1[0] + t1[1]) + (t1[2] + t1[3]);
  };

  for (int sg = 0; sg < nseg; sg++) {
    int n;
    { int tile, k0, k1; b_segment(sg, tile, k0, k1); n = k1 - k0; }
    mbar_wait(bQF, sg & 1);
    {
      const int sl = it % 3;
      mbar_wait(bF + sl * 8, (it / 3) & 1);
      PP_WAIT(3 + wg, 256);
      wg_fence();
      issue_qk(sl);
      PP_ARRIVE(3 + (wg ^ 1), 256);
      wg_wait<0>(); reg_fence(sacc);
      if (lane == 0) { mbar_arrive(bE + sl * 8); if (n == 1) mbar_arrive(bQE); }
      it++;
      softmax(true);
    }
    TS(1, tsi); tsi++;
    for (int j = 1; j < n; j++) {
      const int slv = it % 3, slk = (it + 1) % 3;
      mbar_wait(bF + slv * 8, (it / 3) & 1);
      PP_WAIT(3 + wg, 256);
      wg_fence();
      issue_pv(slv, j > 1);
      mbar_wait(bF + slk * 8, ((it + 1) / 3) & 1);
      issue_qk(slk);
      PP_ARRIVE(3 + (wg ^ 1), 256);
      wg_wait<1>(); reg_fence(oacc);
      if (lane == 0) mbar_arrive(bE + slv * 8);
      wg_wait<0>(); reg_fence(sacc);
      if (lane == 0) { mbar_arrive(bE + slk * 8); if (j == n - 1) mbar_arrive(bQE); }
      it += 2;
      softmax(false);
      TS(1, tsi); tsi++;
    }
    if (owner) break;
    {
      const int sl = it % 3;
      mbar_wait(bF + sl * 8, (it / 3) & 1);
      PP_WAIT(3 + wg, 256);
      wg_fence();
      issue_pv(sl, n > 1);
      if (!(wg == 1 && sg == nseg - 1)) { PP_ARRIVE(3 + (wg ^ 1), 256); }
      wg_wait<0>(); reg_fence(oacc);
      if (lane == 0) mbar_arrive(bE + sl * 8);
      it++;
    }
    TS(1, tsi); tsi++;
    {
      const int slot = (grp * 5 + (ci - 7)) * 2 + sg;
      uint4* dst = g_part + (size_t)(slot * 2 + wg) * 13 * 128 + wtid;
#pragma unroll
      for (int i = 0; i < 12; i++)
        dst[i * 128] = make_uint4(pack_bf16(oacc[8 * i], oacc[8 * i + 1]), pack_bf16(oacc[8 * i + 2], oacc[8 * i + 3]),
                                  pack_bf16(oacc[8 * i + 4], oacc[8 * i + 5]), pack_bf16(oacc[8 * i + 6], oacc[8 * i + 7]));
      dst[12 * 128] = make_uint4(__float_as_uint(m0), __float_as_uint(m1), __float_as_uint(l0), __float_as_uint(l1));
      bar_arrive(5 + wg, 160);
      TS(1, tsi); tsi++;
    }
  }
  if (!owner) return;

  {
    const int sl = it % 3;
    mbar_wait(bF + sl * 8, (it / 3) & 1);
    PP_WAIT(3 + wg, 256);
    wg_fence();
    issue_pv(sl, 1);
    if (wg == 0) { PP_ARRIVE(3 + 1, 256); }
    const int first = (0x9765310 >> (4 * ci)) & 15, cnt = (0x1211221 >> (4 * ci)) & 15;
    const int slot0 = grp * 10 + first;
    if (wtid < cnt) {
      uint32_t n = 0, v;
      do {
        asm volatile("ld.acquire.gpu.global.u32 %0, [%1];" : "=r"(v) : "l"(&g_flag[slot0 + wtid]) : "memory");
      } while (v < 2u && ++n < (1u << 22));
    }
    named_bar(1 + wg, 128);
    uint4 pv0[13];
    {
      const uint4* src = g_part + (size_t)(slot0 * 2 + wg) * 13 * 128 + wtid;
#pragma unroll
      for (int i = 0; i < 13; i++) pv0[i] = __ldcg(src + i * 128);
    }
    wg_wait<0>(); reg_fence(oacc);
    TS(1, 20);
    uint4 pv1[13];
    if (cnt > 1) {
      const uint4* src = g_part + (size_t)((slot0 + 1) * 2 + wg) * 13 * 128 + wtid;
#pragma unroll
      for (int i = 0; i < 13; i++) pv1[i] = __ldcg(src + i * 128);
    }
    auto merge = [&](const uint4 (&pv)[13]) {
      const float pm0 = __uint_as_float(pv[12].x), pm1 = __uint_as_float(pv[12].y);
      const float mx0 = fmaxf(m0, pm0), mx1 = fmaxf(m1, pm1);
      const float a0 = ex2((m0 - mx0) * cs), a1 = ex2((m1 - mx1) * cs);
      const float b0 = ex2((pm0 - mx0) * cs), b1 = ex2((pm1 - mx1) * cs);
      m0 = mx0; m1 = mx1;
      l0 = l0 * a0 + __uint_as_float(pv[12].z) * b0; l1 = l1 * a1 + __uint_as_float(pv[12].w) * b1;
#pragma unroll
      for (int i = 0; i < 12; i++) {
        const uint4 v = pv[i];
        oacc[8 * i + 0] = oacc[8 * i + 0] * a0 + bf_lo(v.x) * b0; oacc[8 * i + 1] = oacc[8 * i + 1] * a0 + bf_hi(v.x) * b0;
        oacc[8 * i + 2] = oacc[8 * i + 2] * a1 + bf_lo(v.y) * b1; oacc[8 * i + 3] = oacc[8 * i + 3] * a1 + bf_hi(v.y) * b1;
        oacc[8 * i + 4] = oacc[8 * i + 4] * a0 + bf_lo(v.z) * b0; oacc[8 * i + 5] = oacc[8 * i + 5] * a0 + bf_hi(v.z) * b0;
        oacc[8 * i + 6] = oacc[8 * i + 6] * a1 + bf_lo(v.w) * b1; oacc[8 * i + 7] = oacc[8 * i + 7] * a1 + bf_hi(v.w) * b1;
      }
    };
    merge(pv0);
    if (cnt > 1) merge(pv1);
  }
  TS(1, 21);
  l0 += __shfl_xor_sync(0xffffffffu, l0, 1); l0 += __shfl_xor_sync(0xffffffffu, l0, 2);
  l1 += __shfl_xor_sync(0xffffffffu, l1, 1); l1 += __shfl_xor_sync(0xffffffffu, l1, 2);
  const float i0 = 1.f / l0, i1 = 1.f / l1;
  mbar_wait(bQF, 1);
  const FragAddr fa(wq, lane);
#pragma unroll
  for (int c = 0; c < 3; c++) resid_chunk(nullptr, &oacc[32 * c], i0, i1, qb + c * 16384, fa);
  fence_proxy_async();
  named_bar(1 + wg, 128);
  TS(1, 22);
  if (wtid == 0) {
    const int tile = grp * 7 + ci;
    const int t = tile / 11, qt = tile - t * 11;
    if (qt * 128 + wg * 64 < NL) {
      for (int c = 0; c < 3; c++) tma_store_3d(&tm_out, qb + c * 16384, c * 64, qt * 128 + wg * 64, t);
      bulk_commit();
      bulk_wait_read0();
    }
  }
  TS(1, 23);
}

typedef CUresult (*EncodeFn)(CUtensorMap*, CUtensorMapDataType, cuuint32_t, void*, const cuuint64_t*, const cuuint64_t*,
                             const cuuint32_t*, const cuuint32_t*, CUtensorMapInterleave, CUtensorMapSwizzle,
                             CUtensorMapL2promotion, CUtensorMapFloatOOBfill);

void make_map(EncodeFn enc, CUtensorMap* m, const void* ptr, int rank, const uint64_t* dims, const uint32_t* box) {
  cuuint64_t gd[3], gs[2];
  cuuint32_t bx[3], es[3] = {1, 1, 1};
  uint64_t stride = 2;
  for (int i = 0; i < rank; i++) {
    gd[i] = dims[i]; bx[i] = box[i];
    stride *= dims[i];
    if (i < rank - 1) gs[i] = stride;
  }
  enc(m, CU_TENSOR_MAP_DATA_TYPE_BFLOAT16, rank, const_cast<void*>(ptr), gd, gs, bx, es, CU_TENSOR_MAP_INTERLEAVE_NONE,
      CU_TENSOR_MAP_SWIZZLE_128B, CU_TENSOR_MAP_L2_PROMOTION_L2_256B, CU_TENSOR_MAP_FLOAT_OOB_FILL_NONE);
}

}

extern "C" void kernel_launch(void* const* d_in, const int* in_sizes, int n_in, void* d_out, int out_size) {
  (void)in_sizes; (void)n_in; (void)out_size;
  EncodeFn enc = nullptr;
  cudaDriverEntryPointQueryResult qres;
  cudaGetDriverEntryPoint("cuTensorMapEncodeTiled", (void**)&enc, cudaEnableDefault, &qres);
  void *p_x1, *p_qkv, *p_wf;
  cudaGetSymbolAddress(&p_wf, g_wf);
  cudaGetSymbolAddress(&p_x1, g_x1);
  cudaGetSymbolAddress(&p_qkv, g_qkv);
  cudaFuncSetAttribute(kernelA, cudaFuncAttributeMaxDynamicSharedMemorySize, A_SMEM);
  cudaFuncSetAttribute(kernelB, cudaFuncAttributeMaxDynamicSharedMemorySize, B_SMEM);

  CUtensorMap tm_x, tm_wqkvt, tm_wot, tm_wqkvs, tm_x1s, tm_qkvs, tm_q, tm_kv, tm_wos, tm_x1l, tm_out, tm_wf;
  const uint64_t d_act[3] = {192, 1296, 7}, d_qkv[3] = {576, 1296, 7}, d_w3[2] = {576, 192}, d_w1[2] = {192, 192}, d_wf[2] = {384, 384};
  const uint32_t b_a[3] = {64, 10, 7}, b_w[2] = {64, 192}, b_q[3] = {64, 128, 1}, b_kv[3] = {64, 144, 1}, b_o[3] = {64, 64, 1}, b_w64[2] = {64, 64};
  make_map(enc, &tm_x, d_in[0], 3, d_act, b_a);
  make_map(enc, &tm_wqkvt, d_in[1], 2, d_w3, b_w64);
  make_map(enc, &tm_wot, d_in[2], 2, d_w1, b_w);
  make_map(enc, &tm_wqkvs, d_in[3], 2, d_w3, b_w64);
  make_map(enc, &tm_wos, d_in[4], 2, d_w1, b_w);
  make_map(enc, &tm_wf, p_wf, 2, d_wf, b_w);
  make_map(enc, &tm_x1s, p_x1, 3, d_act, b_a);
  make_map(enc, &tm_qkvs, p_qkv, 3, d_qkv, b_a);
  make_map(enc, &tm_q, p_qkv, 3, d_qkv, b_q);
  make_map(enc, &tm_kv, p_qkv, 3, d_qkv, b_kv);
  make_map(enc, &tm_x1l, p_x1, 3, d_act, b_q);
  make_map(enc, &tm_out, d_out, 3, d_act, b_o);

  kernelA<<<A_GRID, 384, A_SMEM, cudaStreamPerThread>>>(tm_x, tm_wqkvt, tm_wot, tm_wqkvs, tm_wos, tm_wf, tm_x1s, tm_qkvs);
  cudaLaunchConfig_t cfg = {};
  cfg.gridDim = dim3(B_GRID); cfg.blockDim = dim3(384); cfg.dynamicSmemBytes = B_SMEM; cfg.stream = cudaStreamPerThread;
  cudaLaunchAttribute at[1];
  at[0].id = cudaLaunchAttributeProgrammaticStreamSerialization;
  at[0].val.programmaticStreamSerializationAllowed = 1;
  cfg.attrs = at; cfg.numAttrs = 1;
  cudaLaunchKernelEx(&cfg, kernelB, tm_q, tm_kv, tm_x1l, tm_out);
}
```

```cpp
#include <cuda_runtime.h>
#include <cuda_bf16.h>
#include <cuda.h>
#include <stdint.h>

namespace {

constexpr int TT = 7, NL = 1296, CC = 192;

__device__ __align__(1024) __nv_bfloat16 g_x1[TT * NL * CC];
__device__ __align__(1024) __nv_bfloat16 g_qkv[TT * NL * 3 * CC];
__device__ __align__(1024) __nv_bfloat16 g_wf[2 * CC * 2 * CC];
__device__ __align__(1024) uint4 g_part[121 * 2 * 13 * 128];
__device__ unsigned int g_flag[128];
__device__ unsigned int g_wflag[4];

#define TS(k, i)

__device__ __forceinline__ uint32_t smem_u32(const void* p) { return (uint32_t)__cvta_generic_to_shared(p); }
__device__ __forceinline__ void mbar_init(uint32_t bar, uint32_t cnt) {
  asm volatile("mbarrier.init.shared::cta.b64 [%0], %1;" ::"r"(bar), "r"(cnt));
}
__device__ __forceinline__ void mbar_expect_tx(uint32_t bar, uint32_t bytes) {
  asm volatile("mbarrier.arrive.expect_tx.shared::cta.b64 _, [%0], %1;" ::"r"(bar), "r"(bytes) : "memory");
}
__device__ __forceinline__ void mbar_arrive(uint32_t bar) {
  asm volatile("mbarrier.arrive.shared::cta.b64 _, [%0];" ::"r"(bar) : "memory");
}
__device__ __forceinline__ bool mbar_try(uint32_t bar, uint32_t parity) {
  uint32_t ok;
  asm volatile("{\n.reg .pred p;\nmbarrier.try_wait.parity.shared::cta.b64 p, [%1], %2;\nselp.u32 %0, 1, 0, p;\n}"
               : "=r"(ok) : "r"(bar), "r"(parity) : "memory");
  return ok != 0;
}
__device__ __forceinline__ void mbar_wait(uint32_t bar, uint32_t parity) {
  if (mbar_try(bar, parity)) return;
  uint32_t n = 0;
  while (!mbar_try(bar, parity)) {
    if (++n > (1u << 22)) break;
  }
}
__device__ __forceinline__ void tma_load_2d(uint32_t dst, const CUtensorMap* m, uint32_t bar, int c0, int c1) {
  asm volatile("cp.async.bulk.tensor.2d.shared::cluster.global.mbarrier::complete_tx::bytes [%0], [%1, {%3, %4}], [%2];"
               ::"r"(dst), "l"(m), "r"(bar), "r"(c0), "r"(c1) : "memory");
}
__device__ __forceinline__ void tma_load_3d(uint32_t dst, const CUtensorMap* m, uint32_t bar, int c0, int c1, int c2) {
  asm volatile("cp.async.bulk.tensor.3d.shared::cluster.global.mbarrier::complete_tx::bytes [%0], [%1, {%3, %4, %5}], [%2];"
               ::"r"(dst), "l"(m), "r"(bar), "r"(c0), "r"(c1), "r"(c2) : "memory");
}
__device__ __forceinline__ void tma_store_3d(const CUtensorMap* m, uint32_t src, int c0, int c1, int c2) {
  asm volatile("cp.async.bulk.tensor.3d.global.shared::cta.bulk_group [%0, {%2, %3, %4}], [%1];"
               ::"l"(m), "r"(src), "r"(c0), "r"(c1), "r"(c2) : "memory");
}
__device__ __forceinline__ void bulk_commit() { asm volatile("cp.async.bulk.commit_group;" ::: "memory"); }
__device__ __forceinline__ void bulk_wait_read0() { asm volatile("cp.async.bulk.wait_group.read 0;" ::: "memory"); }
__device__ __forceinline__ void bulk_wait_read1() { asm volatile("cp.async.bulk.wait_group.read 1;" ::: "memory"); }
__device__ __forceinline__ void bulk_wait0() { asm volatile("cp.async.bulk.wait_group 0;" ::: "memory"); }
__device__ __forceinline__ void fence_proxy_async() { asm volatile("fence.proxy.async.shared::cta;" ::: "memory"); }
__device__ __forceinline__ void prefetch_tmap(const CUtensorMap* m) {
  asm volatile("prefetch.tensormap [%0];" ::"l"(m) : "memory");
}
__device__ __forceinline__ void wg_fence() { asm volatile("wgmma.fence.sync.aligned;" ::: "memory"); }
__device__ __forceinline__ void wg_commit() { asm volatile("wgmma.commit_group.sync.aligned;" ::: "memory"); }
template <int N> __device__ __forceinline__ void wg_wait() { asm volatile("wgmma.wait_group.sync.aligned %0;" ::"n"(N) : "memory"); }
__device__ __forceinline__ void named_bar(int id, int nthreads) {
  asm volatile("bar.sync %0, %1;" ::"r"(id), "r"(nthreads) : "memory");
}
__device__ __forceinline__ void ldsm_x4(uint32_t (&r)[4], uint32_t addr) {
  asm volatile("ldmatrix.sync.aligned.m8n8.x4.shared.b16 {%0,%1,%2,%3}, [%4];"
               : "=r"(r[0]), "=r"(r[1]), "=r"(r[2]), "=r"(r[3]) : "r"(addr) : "memory");
}
__device__ __forceinline__ void stsm_x4(uint32_t addr, const uint32_t (&r)[4]) {
  asm volatile("stmatrix.sync.aligned.m8n8.x4.shared.b16 [%0], {%1,%2,%3,%4};"
               ::"r"(addr), "r"(r[0]), "r"(r[1]), "r"(r[2]), "r"(r[3]) : "memory");
}
__device__ __forceinline__ uint32_t pack_bf16(float lo, float hi) {
  uint32_t r;
  asm("cvt.rn.bf16x2.f32 %0, %1, %2;" : "=r"(r) : "f"(hi), "f"(lo));
  return r;
}
__device__ __forceinline__ float bf_lo(uint32_t v) { return __uint_as_float(v << 16); }
__device__ __forceinline__ float bf_hi(uint32_t v) { return __uint_as_float(v & 0xffff0000u); }
__device__ __forceinline__ float ex2(float x) {
  float y;
  asm("ex2.approx.ftz.f32 %0, %1;" : "=f"(y) : "f"(x));
  return y;
}
__device__ __forceinline__ uint64_t mk_desc(uint32_t addr, uint32_t lbo, uint32_t sbo) {
  return (uint64_t)((addr & 0x3FFFF) >> 4) | ((uint64_t)((lbo & 0x3FFFF) >> 4) << 16) |
         ((uint64_t)((sbo & 0x3FFFF) >> 4) << 32) | (1ull << 62);
}
__device__ __forceinline__ uint64_t mk_desc_o(uint32_t addr, uint32_t lbo, uint32_t sbo) {
  asm volatile("" : "+r"(addr));
  return mk_desc(addr, lbo, sbo);
}
template <int N> __device__ __forceinline__ void reg_fence(uint32_t (&d)[N]) {
#pragma unroll
  for (int i = 0; i < N; i++) asm volatile("" : "+r"(d[i])::"memory");
}
template <int N> __device__ __forceinline__ void reg_fence(float (&d)[N]) {
#pragma unroll
  for (int i = 0; i < N; i++) asm volatile("" : "+f"(d[i])::"memory");
}

template<int TB> __device__ __forceinline__ void wgmma_n144_ss(float (&d)[72], uint64_t da, uint64_t db, int sc) {
  asm volatile("{\n.reg .pred p;\nsetp.ne.b32 p, %74, 0;\n"
    "wgmma.mma_async.sync.aligned.m64n144k16.f32.bf16.bf16 {%0, %1, %2, %3, %4, %5, %6, %7, %8, %9, %10, %11, %12, %13, %14, %15, %16, %17, %18, %19, %20, %21, %22, %23, %24, %25, %26, %27, %28, %29, %30, %31, %32, %33, %34, %35, %36, %37, %38, %39, %40, %41, %42, %43, %44, %45, %46, %47, %48, %49, %50, %51, %52, %53, %54, %55, %56, %57, %58, %59, %60, %61, %62, %63, %64, %65, %66, %67, %68, %69, %70, %71}, %72, %73, p, 1, 1, 0, %75;\n}\n"
    : "+f"(d[0]), "+f"(d[1]), "+f"(d[2]), "+f"(d[3]), "+f"(d[4]), "+f"(d[5]), "+f"(d[6]), "+f"(d[7]), "+f"(d[8]), "+f"(d[9]), "+f"(d[10]), "+f"(d[11]), "+f"(d[12]), "+f"(d[13]), "+f"(d[14]), "+f"(d[15]), "+f"(d[16]), "+f"(d[17]), "+f"(d[18]), "+f"(d[19]), "+f"(d[20]), "+f"(d[21]), "+f"(d[22]), "+f"(d[23]), "+f"(d[24]), "+f"(d[25]), "+f"(d[26]), "+f"(d[27]), "+f"(d[28]), "+f"(d[29]), "+f"(d[30]), "+f"(d[31]), "+f"(d[32]), "+f"(d[33]), "+f"(d[34]), "+f"(d[35]), "+f"(d[36]), "+f"(d[37]), "+f"(d[38]), "+f"(d[39]), "+f"(d[40]), "+f"(d[41]), "+f"(d[42]), "+f"(d[43]), "+f"(d[44]), "+f"(d[45]), "+f"(d[46]), "+f"(d[47]), "+f"(d[48]), "+f"(d[49]), "+f"(d[50]), "+f"(d[51]), "+f"(d[52]), "+f"(d[53]), "+f"(d[54]), "+f"(d[55]), "+f"(d[56]), "+f"(d[57]), "+f"(d[58]), "+f"(d[59]), "+f"(d[60]), "+f"(d[61]), "+f"(d[62]), "+f"(d[63]), "+f"(d[64]), "+f"(d[65]), "+f"(d[66]), "+f"(d[67]), "+f"(d[68]), "+f"(d[69]), "+f"(d[70]), "+f"(d[71])
    : "l"(da), "l"(db), "r"(sc), "n"(TB));
}
template<int TB> __device__ __forceinline__ void wgmma_n192_rs(float (&d)[96], const uint32_t (&a)[4], uint64_t db, int sc) {
  asm volatile("{\n.reg .pred p;\nsetp.ne.b32 p, %101, 0;\n"
    "wgmma.mma_async.sync.aligned.m64n192k16.f32.bf16.bf16 {%0, %1, %2, %3, %4, %5, %6, %7, %8, %9, %10, %11, %12, %13, %14, %15, %16, %17, %18, %19, %20, %21, %22, %23, %24, %25, %26, %27, %28, %29, %30, %31, %32, %33, %34, %35, %36, %37, %38, %39, %40, %41, %42, %43, %44, %45, %46, %47, %48, %49, %50, %51, %52, %53, %54, %55, %56, %57, %58, %59, %60, %61, %62, %63, %64, %65, %66, %67, %68, %69, %70, %71, %72, %73, %74, %75, %76, %77, %78, %79, %80, %81, %82, %83, %84, %85, %86, %87, %88, %89, %90, %91, %92, %93, %94, %95}, {%96, %97, %98, %99}, %100, p, 1, 1, %102;\n}\n"
    : "+f"(d[0]), "+f"(d[1]), "+f"(d[2]), "+f"(d[3]), "+f"(d[4]), "+f"(d[5]), "+f"(d[6]), "+f"(d[7]), "+f"(d[8]), "+f"(d[9]), "+f"(d[10]), "+f"(d[11]), "+f"(d[12]), "+f"(d[13]), "+f"(d[14]), "+f"(d[15]), "+f"(d[16]), "+f"(d[17]), "+f"(d[18]), "+f"(d[19]), "+f"(d[20]), "+f"(d[21]), "+f"(d[22]), "+f"(d[23]), "+f"(d[24]), "+f"(d[25]), "+f"(d[26]), "+f"(d[27]), "+f"(d[28]), "+f"(d[29]), "+f"(d[30]), "+f"(d[31]), "+f"(d[32]), "+f"(d[33]), "+f"(d[34]), "+f"(d[35]), "+f"(d[36]), "+f"(d[37]), "+f"(d[38]), "+f"(d[39]), "+f"(d[40]), "+f"(d[41]), "+f"(d[42]), "+f"(d[43]), "+f"(d[44]), "+f"(d[45]), "+f"(d[46]), "+f"(d[47]), "+f"(d[48]), "+f"(d[49]), "+f"(d[50]), "+f"(d[51]), "+f"(d[52]), "+f"(d[53]), "+f"(d[54]), "+f"(d[55]), "+f"(d[56]), "+f"(d[57]), "+f"(d[58]), "+f"(d[59]), "+f"(d[60]), "+f"(d[61]), "+f"(d[62]), "+f"(d[63]), "+f"(d[64]), "+f"(d[65]), "+f"(d[66]), "+f"(d[67]), "+f"(d[68]), "+f"(d[69]), "+f"(d[70]), "+f"(d[71]), "+f"(d[72]), "+f"(d[73]), "+f"(d[74]), "+f"(d[75]), "+f"(d[76]), "+f"(d[77]), "+f"(d[78]), "+f"(d[79]), "+f"(d[80]), "+f"(d[81]), "+f"(d[82]), "+f"(d[83]), "+f"(d[84]), "+f"(d[85]), "+f"(d[86]), "+f"(d[87]), "+f"(d[88]), "+f"(d[89]), "+f"(d[90]), "+f"(d[91]), "+f"(d[92]), "+f"(d[93]), "+f"(d[94]), "+f"(d[95])
    : "r"(a[0]), "r"(a[1]), "r"(a[2]), "r"(a[3]), "l"(db), "r"(sc), "n"(TB));
}
template<int TB> __device__ __forceinline__ void wgmma_n64_ss(float (&d)[32], uint64_t da, uint64_t db, int sc) {
  asm volatile("{\n.reg .pred p;\nsetp.ne.b32 p, %34, 0;\n"
    "wgmma.mma_async.sync.aligned.m64n64k16.f32.bf16.bf16 {%0, %1, %2, %3, %4, %5, %6, %7, %8, %9, %10, %11, %12, %13, %14, %15, %16, %17, %18, %19, %20, %21, %22, %23, %24, %25, %26, %27, %28, %29, %30, %31}, %32, %33, p, 1, 1, 0, %35;\n}\n"
    : "+f"(d[0]), "+f"(d[1]), "+f"(d[2]), "+f"(d[3]), "+f"(d[4]), "+f"(d[5]), "+f"(d[6]), "+f"(d[7]), "+f"(d[8]), "+f"(d[9]), "+f"(d[10]), "+f"(d[11]), "+f"(d[12]), "+f"(d[13]), "+f"(d[14]), "+f"(d[15]), "+f"(d[16]), "+f"(d[17]), "+f"(d[18]), "+f"(d[19]), "+f"(d[20]), "+f"(d[21]), "+f"(d[22]), "+f"(d[23]), "+f"(d[24]), "+f"(d[25]), "+f"(d[26]), "+f"(d[27]), "+f"(d[28]), "+f"(d[29]), "+f"(d[30]), "+f"(d[31])
    : "l"(da), "l"(db), "r"(sc), "n"(TB));
}
template<int TB> __device__ __forceinline__ void wgmma_n72_st(float (&d)[36], uint64_t da, uint64_t db, int sc) {
  asm volatile("{\n.reg .pred p;\nsetp.ne.b32 p, %38, 0;\n"
    "wgmma.mma_async.sync.aligned.m64n72k16.f32.bf16.bf16 {%0, %1, %2, %3, %4, %5, %6, %7, %8, %9, %10, %11, %12, %13, %14, %15, %16, %17, %18, %19, %20, %21, %22, %23, %24, %25, %26, %27, %28, %29, %30, %31, %32, %33, %34, %35}, %36, %37, p, 1, 1, 1, %39;\n}\n"
    : "+f"(d[0]), "+f"(d[1]), "+f"(d[2]), "+f"(d[3]), "+f"(d[4]), "+f"(d[5]), "+f"(d[6]), "+f"(d[7]), "+f"(d[8]), "+f"(d[9]), "+f"(d[10]), "+f"(d[11]), "+f"(d[12]), "+f"(d[13]), "+f"(d[14]), "+f"(d[15]), "+f"(d[16]), "+f"(d[17]), "+f"(d[18]), "+f"(d[19]), "+f"(d[20]), "+f"(d[21]), "+f"(d[22]), "+f"(d[23]), "+f"(d[24]), "+f"(d[25]), "+f"(d[26]), "+f"(d[27]), "+f"(d[28]), "+f"(d[29]), "+f"(d[30]), "+f"(d[31]), "+f"(d[32]), "+f"(d[33]), "+f"(d[34]), "+f"(d[35])
    : "l"(da), "l"(db), "r"(sc), "n"(TB));
}
template<int TB> __device__ __forceinline__ void wgmma_n80_ss(float (&d)[40], uint64_t da, uint64_t db, int sc) {
  asm volatile("{\n.reg .pred p;\nsetp.ne.b32 p, %42, 0;\n"
    "wgmma.mma_async.sync.aligned.m64n80k16.f32.bf16.bf16 {%0, %1, %2, %3, %4, %5, %6, %7, %8, %9, %10, %11, %12, %13, %14, %15, %16, %17, %18, %19, %20, %21, %22, %23, %24, %25, %26, %27, %28, %29, %30, %31, %32, %33, %34, %35, %36, %37, %38, %39}, %40, %41, p, 1, 1, 0, %43;\n}\n"
    : "+f"(d[0]), "+f"(d[1]), "+f"(d[2]), "+f"(d[3]), "+f"(d[4]), "+f"(d[5]), "+f"(d[6]), "+f"(d[7]), "+f"(d[8]), "+f"(d[9]), "+f"(d[10]), "+f"(d[11]), "+f"(d[12]), "+f"(d[13]), "+f"(d[14]), "+f"(d[15]), "+f"(d[16]), "+f"(d[17]), "+f"(d[18]), "+f"(d[19]), "+f"(d[20]), "+f"(d[21]), "+f"(d[22]), "+f"(d[23]), "+f"(d[24]), "+f"(d[25]), "+f"(d[26]), "+f"(d[27]), "+f"(d[28]), "+f"(d[29]), "+f"(d[30]), "+f"(d[31]), "+f"(d[32]), "+f"(d[33]), "+f"(d[34]), "+f"(d[35]), "+f"(d[36]), "+f"(d[37]), "+f"(d[38]), "+f"(d[39])
    : "l"(da), "l"(db), "r"(sc), "n"(TB));
}

struct FragAddr {
  uint32_t rowoff;
  uint32_t rx;
  uint32_t hi;
  __device__ __forceinline__ FragAddr(int warp_in_wg, int lane) {
    int row = 16 * warp_in_wg + (lane & 7) + ((lane >> 3) & 1) * 8;
    rowoff = row * 128;
    rx = row & 7;
    hi = lane >> 4;
  }
  __device__ __forceinline__ uint32_t at(uint32_t chunk_base, int kk4) const {
    return chunk_base + rowoff + ((((uint32_t)kk4 * 2 + hi) ^ rx) << 4);
  }
};

__device__ __forceinline__ void layernorm_frags(uint32_t (&f)[12][4]) {
  float s0[2] = {0.f, 0.f}, s1[2] = {0.f, 0.f}, q0[2] = {0.f, 0.f}, q1[2] = {0.f, 0.f};
#pragma unroll
  for (int k = 0; k < 12; k++) {
#pragma unroll
    for (int hf = 0; hf < 2; hf++) {
      const float a = bf_lo(f[k][2 * hf]), b = bf_hi(f[k][2 * hf]);
      const float c = bf_lo(f[k][2 * hf + 1]), d = bf_hi(f[k][2 * hf + 1]);
      s0[hf] += a + b; q0[hf] = fmaf(a, a, fmaf(b, b, q0[hf]));
      s1[hf] += c + d; q1[hf] = fmaf(c, c, fmaf(d, d, q1[hf]));
    }
  }
  float sa = s0[0] + s0[1], sb_ = s1[0] + s1[1], qa = q0[0] + q0[1], qb_ = q1[0] + q1[1];
  sa += __shfl_xor_sync(0xffffffffu, sa, 1); sb_ += __shfl_xor_sync(0xffffffffu, sb_, 1);
  qa += __shfl_xor_sync(0xffffffffu, qa, 1); qb_ += __shfl_xor_sync(0xffffffffu, qb_, 1);
  sa += __shfl_xor_sync(0xffffffffu, sa, 2); sb_ += __shfl_xor_sync(0xffffffffu, sb_, 2);
  qa += __shfl_xor_sync(0xffffffffu, qa, 2); qb_ += __shfl_xor_sync(0xffffffffu, qb_, 2);
  const float m0 = sa * (1.f / 192.f), m1 = sb_ * (1.f / 192.f);
  const float v0 = fmaxf(fmaf(-m0, m0, qa * (1.f / 192.f)), 0.f), v1 = fmaxf(fmaf(-m1, m1, qb_ * (1.f / 192.f)), 0.f);
  const float r0 = rsqrtf(v0 + 1e-5f), r1 = rsqrtf(v1 + 1e-5f);
  const float c0 = -m0 * r0, c1 = -m1 * r1;
#pragma unroll
  for (int k = 0; k < 12; k++) {
    f[k][0] = pack_bf16(fmaf(bf_lo(f[k][0]), r0, c0), fmaf(bf_hi(f[k][0]), r0, c0));
    f[k][2] = pack_bf16(fmaf(bf_lo(f[k][2]), r0, c0), fmaf(bf_hi(f[k][2]), r0, c0));
    f[k][1] = pack_bf16(fmaf(bf_lo(f[k][1]), r1, c1), fmaf(bf_hi(f[k][1]), r1, c1));
    f[k][3] = pack_bf16(fmaf(bf_lo(f[k][3]), r1, c1), fmaf(bf_hi(f[k][3]), r1, c1));
  }
}

constexpr int A_NST = 4;
constexpr int A_HB = 0;
constexpr int A_VB = 30720;
constexpr int A_QB = 61440;
constexpr int A_W = 110592;
constexpr int A_BAR = A_W + A_NST * 24576;
constexpr int A_SMEM = A_BAR + 256 + 1024;
constexpr int A_GRID = 130;
constexpr int A_FOLD = 36;

__device__ __forceinline__ void stsm_x4_t(uint32_t addr, uint32_t r0, uint32_t r1, uint32_t r2, uint32_t r3) {
  asm volatile("stmatrix.sync.aligned.m8n8.x4.trans.shared.b16 [%0], {%1,%2,%3,%4};"
               ::"r"(addr), "r"(r0), "r"(r1), "r"(r2), "r"(r3) : "memory");
}
__device__ __forceinline__ void stsm_x2_t(uint32_t addr, uint32_t r0, uint32_t r1) {
  asm volatile("stmatrix.sync.aligned.m8n8.x2.trans.shared.b16 [%0], {%1,%2};" ::"r"(addr), "r"(r0), "r"(r1) : "memory");
}
__device__ __forceinline__ void a_issue(float (&acc)[36], uint32_t sb, int s) {
  const int st = s % A_NST;
  mbar_wait(sb + A_BAR + st * 8, (s / A_NST) & 1);
  const uint64_t wd = mk_desc_o(sb + A_W + st * 24576, 8192, 1024);
  const uint64_t hd = mk_desc_o(sb + A_HB, 16, 1024);
  wg_fence();
#pragma unroll
  for (int kk = 0; kk < 12; kk++) wgmma_n72_st<0>(acc, wd + kk * 128, hd + (kk >> 2) * 640 + (kk & 3) * 2, kk > 0);
  wg_commit();
}
__device__ __forceinline__ void a_release(uint32_t sb, int s, int lane) {
  if (lane == 0) mbar_arrive(sb + A_BAR + 64 + (s % A_NST) * 8);
}
__device__ __forceinline__ void store_chunk_t(const float (&d)[36], uint32_t chunk_base, int wq, int lane) {
  const int mi = lane >> 3, i = lane & 7;
  const uint32_t cc = 2 * wq + (mi & 1);
  const uint32_t base = chunk_base + ((mi >> 1) * 8 + i) * 128 + ((cc ^ i) << 4);
#pragma unroll
  for (int j = 0; j < 8; j += 2)
    stsm_x4_t(base + j * 1024, pack_bf16(d[4 * j], d[4 * j + 1]), pack_bf16(d[4 * j + 2], d[4 * j + 3]),
              pack_bf16(d[4 * j + 4], d[4 * j + 5]), pack_bf16(d[4 * j + 6], d[4 * j + 7]));
  stsm_x2_t(chunk_base + (64 + i) * 128 + ((cc ^ i) << 4), pack_bf16(d[32], d[33]), pack_bf16(d[34], d[35]));
}
__device__ __forceinline__ void resid_chunk(uint32_t (*dst)[4], const float* acc, float s0, float s1, uint32_t chunk_base,
                                            const FragAddr& fa) {
#pragma unroll
  for (int k = 0; k < 4; k++) {
    uint32_t x[4];
    ldsm_x4(x, fa.at(chunk_base, k));
    uint32_t o[4];
    o[0] = pack_bf16(fmaf(acc[8 * k + 0], s0, bf_lo(x[0])), fmaf(acc[8 * k + 1], s0, bf_hi(x[0])));
    o[1] = pack_bf16(fmaf(acc[8 * k + 2], s1, bf_lo(x[1])), fmaf(acc[8 * k + 3], s1, bf_hi(x[1])));
    o[2] = pack_bf16(fmaf(acc[8 * k + 4], s0, bf_lo(x[2])), fmaf(acc[8 * k + 5], s0, bf_hi(x[2])));
    o[3] = pack_bf16(fmaf(acc[8 * k + 6], s1, bf_lo(x[3])), fmaf(acc[8 * k + 7], s1, bf_hi(x[3])));
    stsm_x4(fa.at(chunk_base, k), o);
    if (dst) { dst[k][0] = o[0]; dst[k][1] = o[1]; dst[k][2] = o[2]; dst[k][3] = o[3]; }
  }
}

__global__ void __launch_bounds__(384, 1)
kernelA(const __grid_constant__ CUtensorMap tm_x, const __grid_constant__ CUtensorMap tm_wq64t,
        const __grid_constant__ CUtensorMap tm_wot, const __grid_constant__ CUtensorMap tm_wq64s,
        const __grid_constant__ CUtensorMap tm_wos, const __grid_constant__ CUtensorMap tm_wf,
        const __grid_constant__ CUtensorMap tm_x1, const __grid_constant__ CUtensorMap tm_qkv) {
  extern __shared__ uint8_t smem_raw[];
  const uint32_t sb = (smem_u32(smem_raw) + 1023) & ~1023u;
  const int tid = threadIdx.x, warp = tid >> 5, lane = tid & 31;
  const bool is_fold = blockIdx.x < A_FOLD;
  const int n0 = blockIdx.x * 10;
  const uint32_t bX = sb + A_BAR + 128, bFF = sb + A_BAR + 136, bFD = sb + A_BAR + 144;
  if (tid == 256) {
    for (int i = 0; i < A_NST; i++) { mbar_init(sb + A_BAR + i * 8, 1); mbar_init(sb + A_BAR + 64 + i * 8, 4); }
    mbar_init(bX, 1); mbar_init(bFF, 1); mbar_init(bFD, 4);
    asm volatile("fence.mbarrier_init.release.cluster;" ::: "memory");
    if (is_fold) {
      const int mat = blockIdx.x / 9, rs = (blockIdx.x % 9) / 3, cs = blockIdx.x % 3;
      const CUtensorMap* mq = (mat < 2) ? &tm_wq64t : &tm_wq64s;
      const CUtensorMap* mo = (mat < 2) ? &tm_wot : &tm_wos;
      mbar_expect_tx(bFF, 2 * 24576);
      for (int c = 0; c < 3; c++) tma_load_2d(sb + A_W + c * 8192, mq, bFF, ((mat & 1) ? 384 : 0) + c * 64, rs * 64);
      if (mat & 1) tma_load_2d(sb + A_W + 24576, mo, bFF, cs * 64, 0);
      else for (int c = 0; c < 3; c++) tma_load_2d(sb + A_W + 24576 + c * 8192, mq, bFF, 192 + c * 64, cs * 64);
    }
    mbar_expect_tx(bX, 3 * 70 * 128);
    for (int c = 0; c < 3; c++) tma_load_3d(sb + A_VB + c * 10240, &tm_x, bX, c * 64, n0, 0);
  }
  asm volatile("griddepcontrol.launch_dependents;" ::: "memory");
  if (blockIdx.x == 129 && tid < 128) g_flag[tid] = 0;
  if (tid < 240) {
    const uint32_t a = sb + A_VB + (tid / 80) * 10240 + 70 * 128 + (tid % 80) * 16;
    asm volatile("st.shared.v4.b32 [%0], {%1,%1,%1,%1};" ::"r"(a), "r"(0) : "memory");
  }
  __syncthreads();

  if (warp >= 8) {
    asm volatile("setmaxnreg.dec.sync.aligned.u32 24;");
    if (warp == 8 && lane == 0) {
      if (is_fold) mbar_wait(bFD, 0);
      for (int s = 0; s < 12; s++) {
        const int st = s % A_NST;
        const int g = s / 3;
        const int mat = (g == 0) ? 1 : (g == 1) ? 0 : g;
        if (s % 3 == 0) {
          uint32_t n = 0, v;
          do {
            asm volatile("ld.acquire.gpu.global.u32 %0, [%1];" : "=r"(v) : "l"(&g_wflag[mat]) : "memory");
          } while (v < 9u && ++n < (1u << 22));
          asm volatile("fence.proxy.async;" ::: "memory");
        }
        if (s >= A_NST) mbar_wait(sb + A_BAR + 64 + st * 8, ((s / A_NST) - 1) & 1);
        mbar_expect_tx(sb + A_BAR + st * 8, 24576);
        tma_load_2d(sb + A_W + st * 24576, &tm_wf, sb + A_BAR + st * 8, (mat & 1) * 192 + (s % 3) * 64, (mat >> 1) * 192);
      }
    }
    return;
  }

  asm volatile("setmaxnreg.inc.sync.aligned.u32 240;");
  const int wg = warp >> 2, wq = warp & 3;
  const bool elected = (tid & 127) == 0;
  TS(0, 0);

  if (is_fold && wg == 1) {
    const int mat = blockIdx.x / 9, rs = (blockIdx.x % 9) / 3, cs = blockIdx.x % 3;
    float d[32];
    mbar_wait(bFF, 0);
    const uint64_t ad = mk_desc_o(sb + A_W, 16, 1024);
    if (mat & 1) {
      const uint64_t bd = mk_desc_o(sb + A_W + 24576, 8192, 1024);
      wg_fence();
#pragma unroll
      for (int kk = 0; kk < 12; kk++) wgmma_n64_ss<1>(d, ad + (kk >> 2) * 512 + (kk & 3) * 2, bd + kk * 128, kk > 0);
      wg_commit();
    } else {
      const uint64_t bd = mk_desc_o(sb + A_W + 24576, 16, 1024);
      wg_fence();
#pragma unroll
      for (int kk = 0; kk < 12; kk++)
        wgmma_n64_ss<0>(d, ad + (kk >> 2) * 512 + (kk & 3) * 2, bd + (kk >> 2) * 512 + (kk & 3) * 2, kk > 0);
      wg_commit();
    }
    wg_wait<0>(); reg_fence(d);
    if (lane == 0) mbar_arrive(bFD);
    const int r0 = rs * 64 + wq * 16 + (lane >> 2);
    uint32_t* dst = reinterpret_cast<uint32_t*>(g_wf + ((size_t)(mat >> 1) * 192 + r0) * 384 + (mat & 1) * 192 + cs * 64 + (lane & 3) * 2);
#pragma unroll
    for (int j = 0; j < 8; j++) {
      dst[j * 4] = pack_bf16(d[4 * j], d[4 * j + 1]);
      dst[8 * 192 + j * 4] = pack_bf16(d[4 * j + 2], d[4 * j + 3]);
    }
    asm volatile("fence.proxy.async;" ::: "memory");
    named_bar(2, 128);
    if (elected) { __threadfence(); atomicAdd(&g_wflag[mat], 1u); }
  }

  const bool rows_ok = warp < 5;
  const FragAddr fa(warp, lane);
  uint32_t h[12][4];
  if (rows_ok) {
    mbar_wait(bX, 0);
#pragma unroll
    for (int k = 0; k < 12; k++) ldsm_x4(h[k], fa.at(sb + A_VB + (k >> 2) * 10240, k & 3));
    layernorm_frags(h);
#pragma unroll
    for (int k = 0; k < 12; k++) stsm_x4(fa.at(sb + A_HB + (k >> 2) * 10240, k & 3), h[k]);
  }
  fence_proxy_async();
  named_bar(1, 256);
  TS(0, 1);

  float acc0[36], acc1[36];
  {
    auto dst1 = [&](int s) { return s < 3 ? sb + A_VB + s * 10240 : sb + A_QB + (s - 3) * 16384; };
    a_issue(acc0, sb, wg);
    TS(0, 2);
    a_issue(acc1, sb, wg + 2); wg_wait<1>(); reg_fence(acc0); a_release(sb, wg, lane); store_chunk_t(acc0, dst1(wg), wq, lane);
    a_issue(acc0, sb, wg + 4); wg_wait<1>(); reg_fence(acc1); a_release(sb, wg + 2, lane); store_chunk_t(acc1, dst1(wg + 2), wq, lane);
    wg_wait<0>(); reg_fence(acc0); a_release(sb, wg + 4, lane); store_chunk_t(acc0, dst1(wg + 4), wq, lane);
  }
  fence_proxy_async();
  named_bar(1, 256);
  TS(0, 3);
  uint32_t pf[5][4];
  {
    float sacc[40];
    const uint64_t qd = mk_desc_o(sb + A_QB + wg * 8192, 16, 1024);
    const uint64_t kd = mk_desc_o(sb + A_HB, 16, 1024);
    wg_fence();
#pragma unroll
    for (int kk = 0; kk < 12; kk++)
      wgmma_n80_ss<0>(sacc, qd + (kk >> 2) * 1024 + (kk & 3) * 2, kd + (kk >> 2) * 640 + (kk & 3) * 2, kk > 0);
    wg_commit();
    wg_wait<0>(); reg_fence(sacc);
    named_bar(1, 256);
    if (tid == 0) {
      mbar_expect_tx(bX, 3 * 70 * 128);
      for (int c = 0; c < 3; c++) tma_load_3d(sb + A_QB + c * 16384, &tm_x, bX, c * 64, n0, 0);
    }
    TS(0, 4);
    const int r0 = 16 * warp + (lane >> 2), r1 = r0 + 8;
    const unsigned long long MLO = 0x1004010040100401ull;
    const int sh = 2 * (lane & 3);
    unsigned long long lo0, lo1; uint32_t hi0, hi1;
    {
      const int a = r0 % 10, b = r1 % 10;
      unsigned long long l = MLO << a; uint32_t hh = a >= 4 ? (1u << (a - 4)) : 0u;
      lo0 = (l >> sh) | (sh ? ((unsigned long long)hh << (64 - sh)) : 0ull); hi0 = hh >> sh;
      l = MLO << b; hh = b >= 4 ? (1u << (b - 4)) : 0u;
      lo1 = (l >> sh) | (sh ? ((unsigned long long)hh << (64 - sh)) : 0ull); hi1 = hh >> sh;
    }
    const float cs = 0.07216878364870322f * 1.4426950408889634f;
    float mx0 = -INFINITY, mx1 = -INFINITY;
#pragma unroll
    for (int j = 0; j < 10; j++) {
#pragma unroll
      for (int e = 0; e < 2; e++) {
        const int pos = 8 * j + e;
        const bool v0 = pos < 64 ? ((lo0 >> pos) & 1) : ((hi0 >> (pos - 64)) & 1);
        const bool v1 = pos < 64 ? ((lo1 >> pos) & 1) : ((hi1 >> (pos - 64)) & 1);
        sacc[4 * j + e] = v0 ? sacc[4 * j + e] * cs : -INFINITY;
        sacc[4 * j + 2 + e] = v1 ? sacc[4 * j + 2 + e] * cs : -INFINITY;
        mx0 = fmaxf(mx0, sacc[4 * j + e]);
        mx1 = fmaxf(mx1, sacc[4 * j + 2 + e]);
      }
    }
    mx0 = fmaxf(mx0, __shfl_xor_sync(0xffffffffu, mx0, 1)); mx1 = fmaxf(mx1, __shfl_xor_sync(0xffffffffu, mx1, 1));
    mx0 = fmaxf(mx0, __shfl_xor_sync(0xffffffffu, mx0, 2)); mx1 = fmaxf(mx1, __shfl_xor_sync(0xffffffffu, mx1, 2));
    float l0 = 0.f, l1 = 0.f;
#pragma unroll
    for (int j = 0; j < 10; j++) {
#pragma unroll
      for (int e = 0; e < 2; e++) {
        sacc[4 * j + e] = ex2(sacc[4 * j + e] - mx0); l0 += sacc[4 * j + e];
        sacc[4 * j + 2 + e] = ex2(sacc[4 * j + 2 + e] - mx1); l1 += sacc[4 * j + 2 + e];
      }
    }
    l0 += __shfl_xor_sync(0xffffffffu, l0, 1); l1 += __shfl_xor_sync(0xffffffffu, l1, 1);
    l0 += __shfl_xor_sync(0xffffffffu, l0, 2); l1 += __shfl_xor_sync(0xffffffffu, l1, 2);
    const float i0 = 1.f / l0, i1 = 1.f / l1;
#pragma unroll
    for (int k = 0; k < 5; k++) {
      pf[k][0] = pack_bf16(sacc[8 * k + 0] * i0, sacc[8 * k + 1] * i0); pf[k][1] = pack_bf16(sacc[8 * k + 2] * i1, sacc[8 * k + 3] * i1);
      pf[k][2] = pack_bf16(sacc[8 * k + 4] * i0, sacc[8 * k + 5] * i0); pf[k][3] = pack_bf16(sacc[8 * k + 6] * i1, sacc[8 * k + 7] * i1);
    }
  }
  TS(0, 5);
  {
    float oacc[96];
    const uint64_t vd = mk_desc_o(sb + A_VB, 10240, 1024);
    wg_fence();
#pragma unroll
    for (int kk = 0; kk < 5; kk++) wgmma_n192_rs<1>(oacc, pf[kk], vd + kk * 128, kk > 0);
    wg_commit();
    wg_wait<0>(); reg_fence(oacc);
    TS(0, 6);
    if (rows_ok) {
      mbar_wait(bX, 1);
#pragma unroll
      for (int c = 0; c < 3; c++) resid_chunk(&h[4 * c], &oacc[32 * c], 1.f, 1.f, sb + A_QB + c * 16384, fa);
      fence_proxy_async();
      named_bar(4, 160);
      if (tid == 0) {
        for (int c = 0; c < 3; c++) tma_store_3d(&tm_x1, sb + A_QB + c * 16384, c * 64, n0, 0);
        bulk_commit();
      }
      layernorm_frags(h);
#pragma unroll
      for (int k = 0; k < 12; k++) stsm_x4(fa.at(sb + A_HB + (k >> 2) * 10240, k & 3), h[k]);
    }
  }
  fence_proxy_async();
  named_bar(1, 256);
  TS(0, 7);
  if (tid == 128) {
    for (int c = 0; c < 3; c++) tma_store_3d(&tm_qkv, sb + A_HB + c * 10240, 192 + c * 64, n0, 0);
    bulk_commit();
  }
  {
    auto dst2 = [&](int s) { return s < 8 ? sb + A_VB + (s - 6) * 10240 : sb + A_W + (s % A_NST) * 24576; };
    auto flush = [&](int s) {
      fence_proxy_async();
      named_bar(2 + wg, 128);
      if (elected) { tma_store_3d(&tm_qkv, dst2(s), (s < 9 ? (s - 6) * 64 : 384 + (s - 9) * 64), n0, 0); bulk_commit(); }
    };
    a_issue(acc0, sb, 6 + wg);
    a_issue(acc1, sb, 8 + wg); wg_wait<1>(); reg_fence(acc0); a_release(sb, 6 + wg, lane);
    store_chunk_t(acc0, dst2(6 + wg), wq, lane);
    flush(6 + wg);
    a_issue(acc0, sb, 10 + wg); wg_wait<1>(); reg_fence(acc1);
    named_bar(2 + wg, 128);
    store_chunk_t(acc1, dst2(8 + wg), wq, lane);
    flush(8 + wg);
    wg_wait<0>(); reg_fence(acc0);
    named_bar(2 + wg, 128);
    store_chunk_t(acc0, dst2(10 + wg), wq, lane);
    flush(10 + wg);
  }
  TS(0, 9);
  if (elected) bulk_wait_read0();
  TS(0, 10);
}

constexpr int B_GRID = 132;
constexpr int B_SLOT = 55296;
constexpr int B_Q = 0;
constexpr int B_KV = 49152;
constexpr int B_BAR = B_KV + 3 * B_SLOT;
constexpr int B_SMEM = B_BAR + 256 + 1024;

__device__ __forceinline__ void bar_arrive(int id, int nthreads) {
  asm volatile("bar.arrive %0, %1;" ::"r"(id), "r"(nthreads) : "memory");
}
#define PP_MODE 0
#define PP_WAIT(x, y) named_bar(x, y)
#define PP_ARRIVE(x, y) bar_arrive(x, y)
__device__ __forceinline__ void b_segment(int sg, int& tile, int& k0, int& k1) {
  const int grp = blockIdx.x / 12, ci = blockIdx.x - grp * 12;
  if (ci < 7) { tile = grp * 7 + ci; k0 = 3; k1 = 9; }
  else {
    const int hh = ci - 7;
    tile = grp * 7 + ((0x54210 >> (4 * hh)) & 15) + sg;
    k0 = sg ? 0 : ((0x10210 >> (4 * hh)) & 15);
    k1 = sg ? ((0x31321 >> (4 * hh)) & 15) : 3;
  }
}

__global__ void __launch_bounds__(384, 1)
kernelB(const __grid_constant__ CUtensorMap tm_q, const __grid_constant__ CUtensorMap tm_kv,
        const __grid_constant__ CUtensorMap tm_x1, const __grid_constant__ CUtensorMap tm_out) {
  extern __shared__ uint8_t smem_raw[];
  const uint32_t sb = (smem_u32(smem_raw) + 1023) & ~1023u;
  const int tid = threadIdx.x, warp = tid >> 5, lane = tid & 31;
  const uint32_t bF = sb + B_BAR, bE = sb + B_BAR + 32, bQF = sb + B_BAR + 64, bQE = sb + B_BAR + 72;
  if (tid == 0) {
    for (int i = 0; i < 3; i++) { mbar_init(bF + i * 8, 1); mbar_init(bE + i * 8, 8); }
    mbar_init(bQF, 1); mbar_init(bQE, 8);
    asm volatile("fence.mbarrier_init.release.cluster;" ::: "memory");
    prefetch_tmap(&tm_q); prefetch_tmap(&tm_kv); prefetch_tmap(&tm_x1); prefetch_tmap(&tm_out);
  }
  __syncthreads();
  asm volatile("griddepcontrol.wait;" ::: "memory");
  const int grp = blockIdx.x / 12, ci = blockIdx.x - grp * 12;
  const bool owner = ci < 7;
  const int nseg = owner ? 1 : 2;

  if (warp >= 8) {
    asm volatile("setmaxnreg.dec.sync.aligned.u32 24;");
    if (warp == 8 && lane == 0) {
      if (blockIdx.x == 0) { g_wflag[0] = 0; g_wflag[1] = 0; g_wflag[2] = 0; g_wflag[3] = 0; }
      int it = 0;
      for (int sg = 0; sg < nseg; sg++) {
        int tile, k0, k1;
        b_segment(sg, tile, k0, k1);
        const int t = tile / 11, qt = tile - t * 11;
        if (sg > 0) mbar_wait(bQE, 0);
        mbar_expect_tx(bQF, 49152);
        for (int c = 0; c < 3; c++) tma_load_3d(sb + B_Q + c * 16384, &tm_q, bQF, c * 64, qt * 128, t);
        const int n = k1 - k0;
        for (int e = 0; e < 2 * n; e++) {
          const int sl = it % 3;
          if (it >= 3) mbar_wait(bE + sl * 8, ((it / 3) - 1) & 1);
#define EXP_NCH 3
          mbar_expect_tx(bF + sl * 8, EXP_NCH * 18432);
          for (int c = 0; c < EXP_NCH; c++)
            tma_load_3d(sb + B_KV + sl * B_SLOT + c * 18432, &tm_kv, bF + sl * 8, 192 + (e & 1) * 192 + c * 64, (k0 + (e >> 1)) * 144, t);
          it++;
        }
      }
      if (owner) {
        const int tile = grp * 7 + ci;
        const int t = tile / 11, qt = tile - t * 11;
        mbar_wait(bQE, 0);
        mbar_expect_tx(bQF, 49152);
        for (int c = 0; c < 3; c++) tma_load_3d(sb + B_Q + c * 16384, &tm_x1, bQF, c * 64, qt * 128, t);
      }
    } else if ((warp == 9 || warp == 10) && !owner) {
      for (int sg = 0; sg < 2; sg++) {
        named_bar(5 + (warp - 9), 160);
        if (lane == 0) {
          __threadfence();
          atomicAdd(&g_flag[(grp * 5 + (ci - 7)) * 2 + sg], 1u);
        }
        __syncwarp();
      }
    }
    return;
  }

  asm volatile("setmaxnreg.inc.sync.aligned.u32 240;");
  const int wg = warp >> 2, wq = warp & 3;
  const int wtid = tid & 127;
  const float cs = 0.07216878364870322f * 1.4426950408889634f;
  float oacc[96], sacc[72];
  uint32_t pf[9][4];
  float m0, m1, l0, l1;
  int it = 0;
  const uint32_t qb = sb + B_Q + wg * 8192;
  if (wg == 1) { PP_ARRIVE(3, 256); }
  TS(1, 0);
  int tsi = 1;

  auto issue_qk = [&](int slot) {
    const uint64_t kd = mk_desc_o(sb + B_KV + slot * B_SLOT, 16, 1024);
    const uint64_t qd = mk_desc_o(qb, 16, 1024);
#pragma unroll
    for (int kk = 0; kk < 12; kk++)
      wgmma_n144_ss<0>(sacc, qd + (kk >> 2) * 1024 + (kk & 3) * 2, kd + (kk >> 2) * 1152 + (kk & 3) * 2, kk > 0);
    wg_commit();
  };
  auto issue_pv = [&](int slot, int accum) {
    const uint64_t vd = mk_desc_o(sb + B_KV + slot * B_SLOT, 18432, 1024);
#pragma unroll
    for (int kk = 0; kk < 9; kk++) wgmma_n192_rs<1>(oacc, pf[kk], vd + kk * 128, kk > 0 ? 1 : accum);
    wg_commit();
  };
  auto softmax = [&](bool first) {
    float t0[4], t1[4];
#pragma unroll
    for (int q = 0; q < 4; q++) {
      t0[q] = fmaxf(sacc[4 * q], sacc[4 * q + 1]);
      t1[q] = fmaxf(sacc[4 * q + 2], sacc[4 * q + 3]);
    }
#pragma unroll
    for (int j = 4; j < 18; j++) {
      t0[j & 3] = fmaxf(t0[j & 3], fmaxf(sacc[4 * j], sacc[4 * j + 1]));
      t1[j & 3] = fmaxf(t1[j & 3], fmaxf(sacc[4 * j + 2], sacc[4 * j + 3]));
    }
    float mx0 = fmaxf(fmaxf(t0[0], t0[1]), fmaxf(t0[2], t0[3]));
    float mx1 = fmaxf(fmaxf(t1[0], t1[1]), fmaxf(t1[2], t1[3]));
    mx0 = fmaxf(mx0, __shfl_xor_sync(0xffffffffu, mx0, 1)); mx1 = fmaxf(mx1, __shfl_xor_sync(0xffffffffu, mx1, 1));
    mx0 = fmaxf(mx0, __shfl_xor_sync(0xffffffffu, mx0, 2)); mx1 = fmaxf(mx1, __shfl_xor_sync(0xffffffffu, mx1, 2));
    if (first) {
      m0 = mx0; m1 = mx1; l0 = 0.f; l1 = 0.f;
    } else {
      const bool need = !((mx0 - m0) * cs <= 8.f) || !((mx1 - m1) * cs <= 8.f);
      if (__any_sync(0xffffffffu, need)) {
        mx0 = fmaxf(mx0, m0); mx1 = fmaxf(mx1, m1);
        const float a0 = ex2((m0 - mx0) * cs), a1 = ex2((m1 - mx1) * cs);
        m0 = mx0; m1 = mx1;
        l0 *= a0; l1 *= a1;
#pragma unroll
        for (int i = 0; i < 24; i++) {
          oacc[4 * i] *= a0; oacc[4 * i + 1] *= a0; oacc[4 * i + 2] *= a1; oacc[4 * i + 3] *= a1;
        }
      }
    }
    const float mc0 = m0 * cs, mc1 = m1 * cs;
#pragma unroll
    for (int q = 0; q < 4; q++) { t0[q] = 0.f; t1[q] = 0.f; }
#pragma unroll
    for (int k = 0; k < 9; k++) {
      float p[8];
#pragma unroll
      for (int e = 0; e < 8; e++) p[e] = ex2(fmaf(sacc[8 * k + e], cs, (e & 2) ? -mc1 : -mc0));
      t0[0] += p[0]; t0[1] += p[1]; t0[2] += p[4]; t0[3] += p[5];
      t1[0] += p[2]; t1[1] += p[3]; t1[2] += p[6]; t1[3] += p[7];
      pf[k][0] = pack_bf16(p[0], p[1]); pf[k][1] = pack_bf16(p[2], p[3]);
      pf[k][2] = pack_bf16(p[4], p[5]); pf[k][3] = pack_bf16(p[6], p[7]);
    }
    l0 += (t0[0] + t0[1]) + (t0[2] + t0[3]);
    l1 += (t1[0] + t1[1]) + (t1[2] + t1[3]);
  };

  for (int sg = 0; sg < nseg; sg++) {
    int n;
    { int tile, k0, k1; b_segment(sg, tile, k0, k1); n = k1 - k0; }
    mbar_wait(bQF, sg & 1);
    {
      const int sl = it % 3;
      mbar_wait(bF + sl * 8, (it / 3) & 1);
      PP_WAIT(3 + wg, 256);
      wg_fence();
      issue_qk(sl);
      PP_ARRIVE(3 + (wg ^ 1), 256);
      wg_wait<0>(); reg_fence(sacc);
      if (lane == 0) { mbar_arrive(bE + sl * 8); if (n == 1) mbar_arrive(bQE); }
      it++;
      softmax(true);
    }
    TS(1, tsi); tsi++;
    for (int j = 1; j < n; j++) {
      const int slv = it % 3, slk = (it + 1) % 3;
      mbar_wait(bF + slv * 8, (it / 3) & 1);
      PP_WAIT(3 + wg, 256);
      wg_fence();
      issue_pv(slv, j > 1);
      mbar_wait(bF + slk * 8, ((it + 1) / 3) & 1);
      issue_qk(slk);
      PP_ARRIVE(3 + (wg ^ 1), 256);
      wg_wait<1>(); reg_fence(oacc);
      if (lane == 0) mbar_arrive(bE + slv * 8);
      wg_wait<0>(); reg_fence(sacc);
      if (lane == 0) { mbar_arrive(bE + slk * 8); if (j == n - 1) mbar_arrive(bQE); }
      it += 2;
      softmax(false);
      TS(1, tsi); tsi++;
    }
    if (owner) break;
    {
      const int sl = it % 3;
      mbar_wait(bF + sl * 8, (it / 3) & 1);
      PP_WAIT(3 + wg, 256);
      wg_fence();
      issue_pv(sl, n > 1);
      if (!(wg == 1 && sg == nseg - 1)) { PP_ARRIVE(3 + (wg ^ 1), 256); }
      wg_wait<0>(); reg_fence(oacc);
      if (lane == 0) mbar_arrive(bE + sl * 8);
      it++;
    }
    TS(1, tsi); tsi++;
    {
      const int slot = (grp * 5 + (ci - 7)) * 2 + sg;
      uint4* dst = g_part + (size_t)(slot * 2 + wg) * 13 * 128 + wtid;
#pragma unroll
      for (int i = 0; i < 12; i++)
        dst[i * 128] = make_uint4(pack_bf16(oacc[8 * i], oacc[8 * i + 1]), pack_bf16(oacc[8 * i + 2], oacc[8 * i + 3]),
                                  pack_bf16(oacc[8 * i + 4], oacc[8 * i + 5]), pack_bf16(oacc[8 * i + 6], oacc[8 * i + 7]));
      dst[12 * 128] = make_uint4(__float_as_uint(m0), __float_as_uint(m1), __float_as_uint(l0), __float_as_uint(l1));
      bar_arrive(5 + wg, 160);
      TS(1, tsi); tsi++;
    }
  }
  if (!owner) return;

  {
    const int sl = it % 3;
    mbar_wait(bF + sl * 8, (it / 3) & 1);
    PP_WAIT(3 + wg, 256);
    wg_fence();
    issue_pv(sl, 1);
    if (wg == 0) { PP_ARRIVE(3 + 1, 256); }
    const int first = (0x9765310 >> (4 * ci)) & 15, cnt = (0x1211221 >> (4 * ci)) & 15;
    const int slot0 = grp * 10 + first;
    if (wtid < cnt) {
      uint32_t n = 0, v;
      do {
        asm volatile("ld.acquire.gpu.global.u32 %0, [%1];" : "=r"(v) : "l"(&g_flag[slot0 + wtid]) : "memory");
      } while (v < 2u && ++n < (1u << 22));
    }
    named_bar(1 + wg, 128);
    uint4 pv0[13];
    {
      const uint4* src = g_part + (size_t)(slot0 * 2 + wg) * 13 * 128 + wtid;
#pragma unroll
      for (int i = 0; i < 13; i++) pv0[i] = __ldcg(src + i * 128);
    }
    wg_wait<0>(); reg_fence(oacc);
    TS(1, 20);
    uint4 pv1[13];
    if (cnt > 1) {
      const uint4* src = g_part + (size_t)((slot0 + 1) * 2 + wg) * 13 * 128 + wtid;
#pragma unroll
      for (int i = 0; i < 13; i++) pv1[i] = __ldcg(src + i * 128);
    }
    auto merge = [&](const uint4 (&pv)[13]) {
      const float pm0 = __uint_as_float(pv[12].x), pm1 = __uint_as_float(pv[12].y);
      const float mx0 = fmaxf(m0, pm0), mx1 = fmaxf(m1, pm1);
      const float a0 = ex2((m0 - mx0) * cs), a1 = ex2((m1 - mx1) * cs);
      const float b0 = ex2((pm0 - mx0) * cs), b1 = ex2((pm1 - mx1) * cs);
      m0 = mx0; m1 = mx1;
      l0 = l0 * a0 + __uint_as_float(pv[12].z) * b0; l1 = l1 * a1 + __uint_as_float(pv[12].w) * b1;
#pragma unroll
      for (int i = 0; i < 12; i++) {
        const uint4 v = pv[i];
        oacc[8 * i + 0] = oacc[8 * i + 0] * a0 + bf_lo(v.x) * b0; oacc[8 * i + 1] = oacc[8 * i + 1] * a0 + bf_hi(v.x) * b0;
        oacc[8 * i + 2] = oacc[8 * i + 2] * a1 + bf_lo(v.y) * b1; oacc[8 * i + 3] = oacc[8 * i + 3] * a1 + bf_hi(v.y) * b1;
        oacc[8 * i + 4] = oacc[8 * i + 4] * a0 + bf_lo(v.z) * b0; oacc[8 * i + 5] = oacc[8 * i + 5] * a0 + bf_hi(v.z) * b0;
        oacc[8 * i + 6] = oacc[8 * i + 6] * a1 + bf_lo(v.w) * b1; oacc[8 * i + 7] = oacc[8 * i + 7] * a1 + bf_hi(v.w) * b1;
      }
    };
    merge(pv0);
    if (cnt > 1) merge(pv1);
  }
  TS(1, 21);
  l0 += __shfl_xor_sync(0xffffffffu, l0, 1); l0 += __shfl_xor_sync(0xffffffffu, l0, 2);
  l1 += __shfl_xor_sync(0xffffffffu, l1, 1); l1 += __shfl_xor_sync(0xffffffffu, l1, 2);
  const float i0 = 1.f / l0, i1 = 1.f / l1;
  mbar_wait(bQF, 1);
  const FragAddr fa(wq, lane);
#pragma unroll
  for (int c = 0; c < 3; c++) resid_chunk(nullptr, &oacc[32 * c], i0, i1, qb + c * 16384, fa);
  fence_proxy_async();
  named_bar(1 + wg, 128);
  TS(1, 22);
  if (wtid == 0) {
    const int tile = grp * 7 + ci;
    const int t = tile / 11, qt = tile - t * 11;
    if (qt * 128 + wg * 64 < NL) {
      for (int c = 0; c < 3; c++) tma_store_3d(&tm_out, qb + c * 16384, c * 64, qt * 128 + wg * 64, t);
      bulk_commit();
      bulk_wait_read0();
    }
  }
  TS(1, 23);
}

typedef CUresult (*EncodeFn)(CUtensorMap*, CUtensorMapDataType, cuuint32_t, void*, const cuuint64_t*, const cuuint64_t*,
                             const cuuint32_t*, const cuuint32_t*, CUtensorMapInterleave, CUtensorMapSwizzle,
                             CUtensorMapL2promotion, CUtensorMapFloatOOBfill);

void make_map(EncodeFn enc, CUtensorMap* m, const void* ptr, int rank, const uint64_t* dims, const uint32_t* box) {
  cuuint64_t gd[3], gs[2];
  cuuint32_t bx[3], es[3] = {1, 1, 1};
  uint64_t stride = 2;
  for (int i = 0; i < rank; i++) {
    gd[i] = dims[i]; bx[i] = box[i];
    stride *= dims[i];
    if (i < rank - 1) gs[i] = stride;
  }
  enc(m, CU_TENSOR_MAP_DATA_TYPE_BFLOAT16, rank, const_cast<void*>(ptr), gd, gs, bx, es, CU_TENSOR_MAP_INTERLEAVE_NONE,
      CU_TENSOR_MAP_SWIZZLE_128B, CU_TENSOR_MAP_L2_PROMOTION_L2_256B, CU_TENSOR_MAP_FLOAT_OOB_FILL_NONE);
}

}

extern "C" void kernel_launch(void* const* d_in, const int* in_sizes, int n_in, void* d_out, int out_size) {
  (void)in_sizes; (void)n_in; (void)out_size;
  EncodeFn enc = nullptr;
  cudaDriverEntryPointQueryResult qres;
  cudaGetDriverEntryPoint("cuTensorMapEncodeTiled", (void**)&enc, cudaEnableDefault, &qres);
  void *p_x1, *p_qkv, *p_wf;
  cudaGetSymbolAddress(&p_wf, g_wf);
  cudaGetSymbolAddress(&p_x1, g_x1);
  cudaGetSymbolAddress(&p_qkv, g_qkv);
  cudaFuncSetAttribute(kernelA, cudaFuncAttributeMaxDynamicSharedMemorySize, A_SMEM);
  cudaFuncSetAttribute(kernelB, cudaFuncAttributeMaxDynamicSharedMemorySize, B_SMEM);

  CUtensorMap tm_x, tm_wqkvt, tm_wot, tm_wqkvs, tm_x1s, tm_qkvs, tm_q, tm_kv, tm_wos, tm_x1l, tm_out, tm_wf;
  const uint64_t d_act[3] = {192, 1296, 7}, d_qkv[3] = {576, 1296, 7}, d_w3[2] = {576, 192}, d_w1[2] = {192, 192}, d_wf[2] = {384, 384};
  const uint32_t b_a[3] = {64, 10, 7}, b_w[2] = {64, 192}, b_q[3] = {64, 128, 1}, b_kv[3] = {64, 144, 1}, b_o[3] = {64, 64, 1}, b_w64[2] = {64, 64};
  make_map(enc, &tm_x, d_in[0], 3, d_act, b_a);
  make_map(enc, &tm_wqkvt, d_in[1], 2, d_w3, b_w64);
  make_map(enc, &tm_wot, d_in[2], 2, d_w1, b_w);
  make_map(enc, &tm_wqkvs, d_in[3], 2, d_w3, b_w64);
  make_map(enc, &tm_wos, d_in[4], 2, d_w1, b_w);
  make_map(enc, &tm_wf, p_wf, 2, d_wf, b_w);
  make_map(enc, &tm_x1s, p_x1, 3, d_act, b_a);
  make_map(enc, &tm_qkvs, p_qkv, 3, d_qkv, b_a);
  make_map(enc, &tm_q, p_qkv, 3, d_qkv, b_q);
  make_map(enc, &tm_kv, p_qkv, 3, d_qkv, b_kv);
  make_map(enc, &tm_x1l, p_x1, 3, d_act, b_q);
  make_map(enc, &tm_out, d_out, 3, d_act, b_o);

  kernelA<<<A_GRID, 384, A_SMEM, cudaStreamPerThread>>>(tm_x, tm_wqkvt, tm_wot, tm_wqkvs, tm_wos, tm_wf, tm_x1s, tm_qkvs);
  cudaLaunchConfig_t cfg = {};
  cfg.gridDim = dim3(B_GRID); cfg.blockDim = dim3(384); cfg.dynamicSmemBytes = B_SMEM; cfg.stream = cudaStreamPerThread;
  cudaLaunchAttribute at[1];
  at[0].id = cudaLaunchAttributeProgrammaticStreamSerialization;
  at[0].val.programmaticStreamSerializationAllowed = 1;
  cfg.attrs = at; cfg.numAttrs = 1;
  cudaLaunchKernelEx(&cfg, kernelB, tm_q, tm_kv, tm_x1l, tm_out);
}
```

```cpp
#include <cuda_runtime.h>
#include <cuda_bf16.h>
#include <cuda.h>
#include <stdint.h>

namespace {

constexpr int TT = 7, NL = 1296, CC = 192;

__device__ __align__(1024) __nv_bfloat16 g_x1[TT * NL * CC];
__device__ __align__(1024) __nv_bfloat16 g_qkv[TT * NL * 3 * CC];
__device__ __align__(1024) __nv_bfloat16 g_wf[2 * CC * 2 * CC];
__device__ __align__(1024) uint4 g_part[121 * 2 * 13 * 128];
__device__ unsigned int g_flag[128];
__device__ unsigned int g_wflag[4];

#define TS(k, i)

__device__ __forceinline__ uint32_t smem_u32(const void* p) { return (uint32_t)__cvta_generic_to_shared(p); }
__device__ __forceinline__ void mbar_init(uint32_t bar, uint32_t cnt) {
  asm volatile("mbarrier.init.shared::cta.b64 [%0], %1;" ::"r"(bar), "r"(cnt));
}
__device__ __forceinline__ void mbar_expect_tx(uint32_t bar, uint32_t bytes) {
  asm volatile("mbarrier.arrive.expect_tx.shared::cta.b64 _, [%0], %1;" ::"r"(bar), "r"(bytes) : "memory");
}
__device__ __forceinline__ void mbar_arrive(uint32_t bar) {
  asm volatile("mbarrier.arrive.shared::cta.b64 _, [%0];" ::"r"(bar) : "memory");
}
__device__ __forceinline__ bool mbar_try(uint32_t bar, uint32_t parity) {
  uint32_t ok;
  asm volatile("{\n.reg .pred p;\nmbarrier.try_wait.parity.shared::cta.b64 p, [%1], %2;\nselp.u32 %0, 1, 0, p;\n}"
               : "=r"(ok) : "r"(bar), "r"(parity) : "memory");
  return ok != 0;
}
__device__ __forceinline__ void mbar_wait(uint32_t bar, uint32_t parity) {
  if (mbar_try(bar, parity)) return;
  uint32_t n = 0;
  while (!mbar_try(bar, parity)) {
    if (++n > (1u << 22)) break;
  }
}
__device__ __forceinline__ void tma_load_2d(uint32_t dst, const CUtensorMap* m, uint32_t bar, int c0, int c1) {
  asm volatile("cp.async.bulk.tensor.2d.shared::cluster.global.mbarrier::complete_tx::bytes [%0], [%1, {%3, %4}], [%2];"
               ::"r"(dst), "l"(m), "r"(bar), "r"(c0), "r"(c1) : "memory");
}
__device__ __forceinline__ void tma_load_3d(uint32_t dst, const CUtensorMap* m, uint32_t bar, int c0, int c1, int c2) {
  asm volatile("cp.async.bulk.tensor.3d.shared::cluster.global.mbarrier::complete_tx::bytes [%0], [%1, {%3, %4, %5}], [%2];"
               ::"r"(dst), "l"(m), "r"(bar), "r"(c0), "r"(c1), "r"(c2) : "memory");
}
__device__ __forceinline__ void tma_store_3d(const CUtensorMap* m, uint32_t src, int c0, int c1, int c2) {
  asm volatile("cp.async.bulk.tensor.3d.global.shared::cta.bulk_group [%0, {%2, %3, %4}], [%1];"
               ::"l"(m), "r"(src), "r"(c0), "r"(c1), "r"(c2) : "memory");
}
__device__ __forceinline__ void bulk_commit() { asm volatile("cp.async.bulk.commit_group;" ::: "memory"); }
__device__ __forceinline__ void bulk_wait_read0() { asm volatile("cp.async.bulk.wait_group.read 0;" ::: "memory"); }
__device__ __forceinline__ void bulk_wait_read1() { asm volatile("cp.async.bulk.wait_group.read 1;" ::: "memory"); }
__device__ __forceinline__ void bulk_wait0() { asm volatile("cp.async.bulk.wait_group 0;" ::: "memory"); }
__device__ __forceinline__ void fence_proxy_async() { asm volatile("fence.proxy.async.shared::cta;" ::: "memory"); }
__device__ __forceinline__ void prefetch_tmap(const CUtensorMap* m) {
  asm volatile("prefetch.tensormap [%0];" ::"l"(m) : "memory");
}
__device__ __forceinline__ void wg_fence() { asm volatile("wgmma.fence.sync.aligned;" ::: "memory"); }
__device__ __forceinline__ void wg_commit() { asm volatile("wgmma.commit_group.sync.aligned;" ::: "memory"); }
template <int N> __device__ __forceinline__ void wg_wait() { asm volatile("wgmma.wait_group.sync.aligned %0;" ::"n"(N) : "memory"); }
__device__ __forceinline__ void named_bar(int id, int nthreads) {
  asm volatile("bar.sync %0, %1;" ::"r"(id), "r"(nthreads) : "memory");
}
__device__ __forceinline__ void ldsm_x4(uint32_t (&r)[4], uint32_t addr) {
  asm volatile("ldmatrix.sync.aligned.m8n8.x4.shared.b16 {%0,%1,%2,%3}, [%4];"
               : "=r"(r[0]), "=r"(r[1]), "=r"(r[2]), "=r"(r[3]) : "r"(addr) : "memory");
}
__device__ __forceinline__ void stsm_x4(uint32_t addr, const uint32_t (&r)[4]) {
  asm volatile("stmatrix.sync.aligned.m8n8.x4.shared.b16 [%0], {%1,%2,%3,%4};"
               ::"r"(addr), "r"(r[0]), "r"(r[1]), "r"(r[2]), "r"(r[3]) : "memory");
}
__device__ __forceinline__ uint32_t pack_bf16(float lo, float hi) {
  uint32_t r;
  asm("cvt.rn.bf16x2.f32 %0, %1, %2;" : "=r"(r) : "f"(hi), "f"(lo));
  return r;
}
__device__ __forceinline__ float bf_lo(uint32_t v) { return __uint_as_float(v << 16); }
__device__ __forceinline__ float bf_hi(uint32_t v) { return __uint_as_float(v & 0xffff0000u); }
__device__ __forceinline__ float ex2(float x) {
  float y;
  asm("ex2.approx.ftz.f32 %0, %1;" : "=f"(y) : "f"(x));
  return y;
}
__device__ __forceinline__ uint64_t mk_desc(uint32_t addr, uint32_t lbo, uint32_t sbo) {
  return (uint64_t)((addr & 0x3FFFF) >> 4) | ((uint64_t)((lbo & 0x3FFFF) >> 4) << 16) |
         ((uint64_t)((sbo & 0x3FFFF) >> 4) << 32) | (1ull << 62);
}
__device__ __forceinline__ uint64_t mk_desc_o(uint32_t addr, uint32_t lbo, uint32_t sbo) {
  asm volatile("" : "+r"(addr));
  return mk_desc(addr, lbo, sbo);
}
template <int N> __device__ __forceinline__ void reg_fence(uint32_t (&d)[N]) {
#pragma unroll
  for (int i = 0; i < N; i++) asm volatile("" : "+r"(d[i])::"memory");
}
template <int N> __device__ __forceinline__ void reg_fence(float (&d)[N]) {
#pragma unroll
  for (int i = 0; i < N; i++) asm volatile("" : "+f"(d[i])::"memory");
}

template<int TB> __device__ __forceinline__ void wgmma_n144_ss(float (&d)[72], uint64_t da, uint64_t db, int sc) {
  asm volatile("{\n.reg .pred p;\nsetp.ne.b32 p, %74, 0;\n"
    "wgmma.mma_async.sync.aligned.m64n144k16.f32.bf16.bf16 {%0, %1, %2, %3, %4, %5, %6, %7, %8, %9, %10, %11, %12, %13, %14, %15, %16, %17, %18, %19, %20, %21, %22, %23, %24, %25, %26, %27, %28, %29, %30, %31, %32, %33, %34, %35, %36, %37, %38, %39, %40, %41, %42, %43, %44, %45, %46, %47, %48, %49, %50, %51, %52, %53, %54, %55, %56, %57, %58, %59, %60, %61, %62, %63, %64, %65, %66, %67, %68, %69, %70, %71}, %72, %73, p, 1, 1, 0, %75;\n}\n"
    : "+f"(d[0]), "+f"(d[1]), "+f"(d[2]), "+f"(d[3]), "+f"(d[4]), "+f"(d[5]), "+f"(d[6]), "+f"(d[7]), "+f"(d[8]), "+f"(d[9]), "+f"(d[10]), "+f"(d[11]), "+f"(d[12]), "+f"(d[13]), "+f"(d[14]), "+f"(d[15]), "+f"(d[16]), "+f"(d[17]), "+f"(d[18]), "+f"(d[19]), "+f"(d[20]), "+f"(d[21]), "+f"(d[22]), "+f"(d[23]), "+f"(d[24]), "+f"(d[25]), "+f"(d[26]), "+f"(d[27]), "+f"(d[28]), "+f"(d[29]), "+f"(d[30]), "+f"(d[31]), "+f"(d[32]), "+f"(d[33]), "+f"(d[34]), "+f"(d[35]), "+f"(d[36]), "+f"(d[37]), "+f"(d[38]), "+f"(d[39]), "+f"(d[40]), "+f"(d[41]), "+f"(d[42]), "+f"(d[43]), "+f"(d[44]), "+f"(d[45]), "+f"(d[46]), "+f"(d[47]), "+f"(d[48]), "+f"(d[49]), "+f"(d[50]), "+f"(d[51]), "+f"(d[52]), "+f"(d[53]), "+f"(d[54]), "+f"(d[55]), "+f"(d[56]), "+f"(d[57]), "+f"(d[58]), "+f"(d[59]), "+f"(d[60]), "+f"(d[61]), "+f"(d[62]), "+f"(d[63]), "+f"(d[64]), "+f"(d[65]), "+f"(d[66]), "+f"(d[67]), "+f"(d[68]), "+f"(d[69]), "+f"(d[70]), "+f"(d[71])
    : "l"(da), "l"(db), "r"(sc), "n"(TB));
}
template<int TB> __device__ __forceinline__ void wgmma_n192_rs(float (&d)[96], const uint32_t (&a)[4], uint64_t db, int sc) {
  asm volatile("{\n.reg .pred p;\nsetp.ne.b32 p, %101, 0;\n"
    "wgmma.mma_async.sync.aligned.m64n192k16.f32.bf16.bf16 {%0, %1, %2, %3, %4, %5, %6, %7, %8, %9, %10, %11, %12, %13, %14, %15, %16, %17, %18, %19, %20, %21, %22, %23, %24, %25, %26, %27, %28, %29, %30, %31, %32, %33, %34, %35, %36, %37, %38, %39, %40, %41, %42, %43, %44, %45, %46, %47, %48, %49, %50, %51, %52, %53, %54, %55, %56, %57, %58, %59, %60, %61, %62, %63, %64, %65, %66, %67, %68, %69, %70, %71, %72, %73, %74, %75, %76, %77, %78, %79, %80, %81, %82, %83, %84, %85, %86, %87, %88, %89, %90, %91, %92, %93, %94, %95}, {%96, %97, %98, %99}, %100, p, 1, 1, %102;\n}\n"
    : "+f"(d[0]), "+f"(d[1]), "+f"(d[2]), "+f"(d[3]), "+f"(d[4]), "+f"(d[5]), "+f"(d[6]), "+f"(d[7]), "+f"(d[8]), "+f"(d[9]), "+f"(d[10]), "+f"(d[11]), "+f"(d[12]), "+f"(d[13]), "+f"(d[14]), "+f"(d[15]), "+f"(d[16]), "+f"(d[17]), "+f"(d[18]), "+f"(d[19]), "+f"(d[20]), "+f"(d[21]), "+f"(d[22]), "+f"(d[23]), "+f"(d[24]), "+f"(d[25]), "+f"(d[26]), "+f"(d[27]), "+f"(d[28]), "+f"(d[29]), "+f"(d[30]), "+f"(d[31]), "+f"(d[32]), "+f"(d[33]), "+f"(d[34]), "+f"(d[35]), "+f"(d[36]), "+f"(d[37]), "+f"(d[38]), "+f"(d[39]), "+f"(d[40]), "+f"(d[41]), "+f"(d[42]), "+f"(d[43]), "+f"(d[44]), "+f"(d[45]), "+f"(d[46]), "+f"(d[47]), "+f"(d[48]), "+f"(d[49]), "+f"(d[50]), "+f"(d[51]), "+f"(d[52]), "+f"(d[53]), "+f"(d[54]), "+f"(d[55]), "+f"(d[56]), "+f"(d[57]), "+f"(d[58]), "+f"(d[59]), "+f"(d[60]), "+f"(d[61]), "+f"(d[62]), "+f"(d[63]), "+f"(d[64]), "+f"(d[65]), "+f"(d[66]), "+f"(d[67]), "+f"(d[68]), "+f"(d[69]), "+f"(d[70]), "+f"(d[71]), "+f"(d[72]), "+f"(d[73]), "+f"(d[74]), "+f"(d[75]), "+f"(d[76]), "+f"(d[77]), "+f"(d[78]), "+f"(d[79]), "+f"(d[80]), "+f"(d[81]), "+f"(d[82]), "+f"(d[83]), "+f"(d[84]), "+f"(d[85]), "+f"(d[86]), "+f"(d[87]), "+f"(d[88]), "+f"(d[89]), "+f"(d[90]), "+f"(d[91]), "+f"(d[92]), "+f"(d[93]), "+f"(d[94]), "+f"(d[95])
    : "r"(a[0]), "r"(a[1]), "r"(a[2]), "r"(a[3]), "l"(db), "r"(sc), "n"(TB));
}
template<int TB> __device__ __forceinline__ void wgmma_n64_ss(float (&d)[32], uint64_t da, uint64_t db, int sc) {
  asm volatile("{\n.reg .pred p;\nsetp.ne.b32 p, %34, 0;\n"
    "wgmma.mma_async.sync.aligned.m64n64k16.f32.bf16.bf16 {%0, %1, %2, %3, %4, %5, %6, %7, %8, %9, %10, %11, %12, %13, %14, %15, %16, %17, %18, %19, %20, %21, %22, %23, %24, %25, %26, %27, %28, %29, %30, %31}, %32, %33, p, 1, 1, 0, %35;\n}\n"
    : "+f"(d[0]), "+f"(d[1]), "+f"(d[2]), "+f"(d[3]), "+f"(d[4]), "+f"(d[5]), "+f"(d[6]), "+f"(d[7]), "+f"(d[8]), "+f"(d[9]), "+f"(d[10]), "+f"(d[11]), "+f"(d[12]), "+f"(d[13]), "+f"(d[14]), "+f"(d[15]), "+f"(d[16]), "+f"(d[17]), "+f"(d[18]), "+f"(d[19]), "+f"(d[20]), "+f"(d[21]), "+f"(d[22]), "+f"(d[23]), "+f"(d[24]), "+f"(d[25]), "+f"(d[26]), "+f"(d[27]), "+f"(d[28]), "+f"(d[29]), "+f"(d[30]), "+f"(d[31])
    : "l"(da), "l"(db), "r"(sc), "n"(TB));
}
template<int TB> __device__ __forceinline__ void wgmma_n72_st(float (&d)[36], uint64_t da, uint64_t db, int sc) {
  asm volatile("{\n.reg .pred p;\nsetp.ne.b32 p, %38, 0;\n"
    "wgmma.mma_async.sync.aligned.m64n72k16.f32.bf16.bf16 {%0, %1, %2, %3, %4, %5, %6, %7, %8, %9, %10, %11, %12, %13, %14, %15, %16, %17, %18, %19, %20, %21, %22, %23, %24, %25, %26, %27, %28, %29, %30, %31, %32, %33, %34, %35}, %36, %37, p, 1, 1, 1, %39;\n}\n"
    : "+f"(d[0]), "+f"(d[1]), "+f"(d[2]), "+f"(d[3]), "+f"(d[4]), "+f"(d[5]), "+f"(d[6]), "+f"(d[7]), "+f"(d[8]), "+f"(d[9]), "+f"(d[10]), "+f"(d[11]), "+f"(d[12]), "+f"(d[13]), "+f"(d[14]), "+f"(d[15]), "+f"(d[16]), "+f"(d[17]), "+f"(d[18]), "+f"(d[19]), "+f"(d[20]), "+f"(d[21]), "+f"(d[22]), "+f"(d[23]), "+f"(d[24]), "+f"(d[25]), "+f"(d[26]), "+f"(d[27]), "+f"(d[28]), "+f"(d[29]), "+f"(d[30]), "+f"(d[31]), "+f"(d[32]), "+f"(d[33]), "+f"(d[34]), "+f"(d[35])
    : "l"(da), "l"(db), "r"(sc), "n"(TB));
}
template<int TB> __device__ __forceinline__ void wgmma_n80_ss(float (&d)[40], uint64_t da, uint64_t db, int sc) {
  asm volatile("{\n.reg .pred p;\nsetp.ne.b32 p, %42, 0;\n"
    "wgmma.mma_async.sync.aligned.m64n80k16.f32.bf16.bf16 {%0, %1, %2, %3, %4, %5, %6, %7, %8, %9, %10, %11, %12, %13, %14, %15, %16, %17, %18, %19, %20, %21, %22, %23, %24, %25, %26, %27, %28, %29, %30, %31, %32, %33, %34, %35, %36, %37, %38, %39}, %40, %41, p, 1, 1, 0, %43;\n}\n"
    : "+f"(d[0]), "+f"(d[1]), "+f"(d[2]), "+f"(d[3]), "+f"(d[4]), "+f"(d[5]), "+f"(d[6]), "+f"(d[7]), "+f"(d[8]), "+f"(d[9]), "+f"(d[10]), "+f"(d[11]), "+f"(d[12]), "+f"(d[13]), "+f"(d[14]), "+f"(d[15]), "+f"(d[16]), "+f"(d[17]), "+f"(d[18]), "+f"(d[19]), "+f"(d[20]), "+f"(d[21]), "+f"(d[22]), "+f"(d[23]), "+f"(d[24]), "+f"(d[25]), "+f"(d[26]), "+f"(d[27]), "+f"(d[28]), "+f"(d[29]), "+f"(d[30]), "+f"(d[31]), "+f"(d[32]), "+f"(d[33]), "+f"(d[34]), "+f"(d[35]), "+f"(d[36]), "+f"(d[37]), "+f"(d[38]), "+f"(d[39])
    : "l"(da), "l"(db), "r"(sc), "n"(TB));
}

struct FragAddr {
  uint32_t rowoff;
  uint32_t rx;
  uint32_t hi;
  __device__ __forceinline__ FragAddr(int warp_in_wg, int lane) {
    int row = 16 * warp_in_wg + (lane & 7) + ((lane >> 3) & 1) * 8;
    rowoff = row * 128;
    rx = row & 7;
    hi = lane >> 4;
  }
  __device__ __forceinline__ uint32_t at(uint32_t chunk_base, int kk4) const {
    return chunk_base + rowoff + ((((uint32_t)kk4 * 2 + hi) ^ rx) << 4);
  }
};

__device__ __forceinline__ void layernorm_frags(uint32_t (&f)[12][4]) {
  float s0[2] = {0.f, 0.f}, s1[2] = {0.f, 0.f}, q0[2] = {0.f, 0.f}, q1[2] = {0.f, 0.f};
#pragma unroll
  for (int k = 0; k < 12; k++) {
#pragma unroll
    for (int hf = 0; hf < 2; hf++) {
      const float a = bf_lo(f[k][2 * hf]), b = bf_hi(f[k][2 * hf]);
      const float c = bf_lo(f[k][2 * hf + 1]), d = bf_hi(f[k][2 * hf + 1]);
      s0[hf] += a + b; q0[hf] = fmaf(a, a, fmaf(b, b, q0[hf]));
      s1[hf] += c + d; q1[hf] = fmaf(c, c, fmaf(d, d, q1[hf]));
    }
  }
  float sa = s0[0] + s0[1], sb_ = s1[0] + s1[1], qa = q0[0] + q0[1], qb_ = q1[0] + q1[1];
  sa += __shfl_xor_sync(0xffffffffu, sa, 1); sb_ += __shfl_xor_sync(0xffffffffu, sb_, 1);
  qa += __shfl_xor_sync(0xffffffffu, qa, 1); qb_ += __shfl_xor_sync(0xffffffffu, qb_, 1);
  sa += __shfl_xor_sync(0xffffffffu, sa, 2); sb_ += __shfl_xor_sync(0xffffffffu, sb_, 2);
  qa += __shfl_xor_sync(0xffffffffu, qa, 2); qb_ += __shfl_xor_sync(0xffffffffu, qb_, 2);
  const float m0 = sa * (1.f / 192.f), m1 = sb_ * (1.f / 192.f);
  const float v0 = fmaxf(fmaf(-m0, m0, qa * (1.f / 192.f)), 0.f), v1 = fmaxf(fmaf(-m1, m1, qb_ * (1.f / 192.f)), 0.f);
  const float r0 = rsqrtf(v0 + 1e-5f), r1 = rsqrtf(v1 + 1e-5f);
  const float c0 = -m0 * r0, c1 = -m1 * r1;
#pragma unroll
  for (int k = 0; k < 12; k++) {
    f[k][0] = pack_bf16(fmaf(bf_lo(f[k][0]), r0, c0), fmaf(bf_hi(f[k][0]), r0, c0));
    f[k][2] = pack_bf16(fmaf(bf_lo(f[k][2]), r0, c0), fmaf(bf_hi(f[k][2]), r0, c0));
    f[k][1] = pack_bf16(fmaf(bf_lo(f[k][1]), r1, c1), fmaf(bf_hi(f[k][1]), r1, c1));
    f[k][3] = pack_bf16(fmaf(bf_lo(f[k][3]), r1, c1), fmaf(bf_hi(f[k][3]), r1, c1));
  }
}

#define XDELAY 600
constexpr int A_NST = 4;
constexpr int A_HB = 0;
constexpr int A_VB = 30720;
constexpr int A_QB = 61440;
constexpr int A_W = 110592;
constexpr int A_BAR = A_W + A_NST * 24576;
constexpr int A_SMEM = A_BAR + 256 + 1024;
constexpr int A_GRID = 130;
constexpr int A_FOLD = 36;

__device__ __forceinline__ void stsm_x4_t(uint32_t addr, uint32_t r0, uint32_t r1, uint32_t r2, uint32_t r3) {
  asm volatile("stmatrix.sync.aligned.m8n8.x4.trans.shared.b16 [%0], {%1,%2,%3,%4};"
               ::"r"(addr), "r"(r0), "r"(r1), "r"(r2), "r"(r3) : "memory");
}
__device__ __forceinline__ void stsm_x2_t(uint32_t addr, uint32_t r0, uint32_t r1) {
  asm volatile("stmatrix.sync.aligned.m8n8.x2.trans.shared.b16 [%0], {%1,%2};" ::"r"(addr), "r"(r0), "r"(r1) : "memory");
}
__device__ __forceinline__ void a_issue(float (&acc)[36], uint32_t sb, int s) {
  const int st = s % A_NST;
  mbar_wait(sb + A_BAR + st * 8, (s / A_NST) & 1);
  const uint64_t wd = mk_desc_o(sb + A_W + st * 24576, 8192, 1024);
  const uint64_t hd = mk_desc_o(sb + A_HB, 16, 1024);
  wg_fence();
#pragma unroll
  for (int kk = 0; kk < 12; kk++) wgmma_n72_st<0>(acc, wd + kk * 128, hd + (kk >> 2) * 640 + (kk & 3) * 2, kk > 0);
  wg_commit();
}
__device__ __forceinline__ void a_release(uint32_t sb, int s, int lane) {
  if (lane == 0) mbar_arrive(sb + A_BAR + 64 + (s % A_NST) * 8);
}
__device__ __forceinline__ void store_chunk_t(const float (&d)[36], uint32_t chunk_base, int wq, int lane) {
  const int mi = lane >> 3, i = lane & 7;
  const uint32_t cc = 2 * wq + (mi & 1);
  const uint32_t base = chunk_base + ((mi >> 1) * 8 + i) * 128 + ((cc ^ i) << 4);
#pragma unroll
  for (int j = 0; j < 8; j += 2)
    stsm_x4_t(base + j * 1024, pack_bf16(d[4 * j], d[4 * j + 1]), pack_bf16(d[4 * j + 2], d[4 * j + 3]),
              pack_bf16(d[4 * j + 4], d[4 * j + 5]), pack_bf16(d[4 * j + 6], d[4 * j + 7]));
  stsm_x2_t(chunk_base + (64 + i) * 128 + ((cc ^ i) << 4), pack_bf16(d[32], d[33]), pack_bf16(d[34], d[35]));
}
__device__ __forceinline__ void resid_chunk(uint32_t (*dst)[4], const float* acc, float s0, float s1, uint32_t chunk_base,
                                            const FragAddr& fa) {
#pragma unroll
  for (int k = 0; k < 4; k++) {
    uint32_t x[4];
    ldsm_x4(x, fa.at(chunk_base, k));
    uint32_t o[4];
    o[0] = pack_bf16(fmaf(acc[8 * k + 0], s0, bf_lo(x[0])), fmaf(acc[8 * k + 1], s0, bf_hi(x[0])));
    o[1] = pack_bf16(fmaf(acc[8 * k + 2], s1, bf_lo(x[1])), fmaf(acc[8 * k + 3], s1, bf_hi(x[1])));
    o[2] = pack_bf16(fmaf(acc[8 * k + 4], s0, bf_lo(x[2])), fmaf(acc[8 * k + 5], s0, bf_hi(x[2])));
    o[3] = pack_bf16(fmaf(acc[8 * k + 6], s1, bf_lo(x[3])), fmaf(acc[8 * k + 7], s1, bf_hi(x[3])));
    stsm_x4(fa.at(chunk_base, k), o);
    if (dst) { dst[k][0] = o[0]; dst[k][1] = o[1]; dst[k][2] = o[2]; dst[k][3] = o[3]; }
  }
}

__global__ void __launch_bounds__(384, 1)
kernelA(const __grid_constant__ CUtensorMap tm_x, const __grid_constant__ CUtensorMap tm_wq64t,
        const __grid_constant__ CUtensorMap tm_wot, const __grid_constant__ CUtensorMap tm_wq64s,
        const __grid_constant__ CUtensorMap tm_wos, const __grid_constant__ CUtensorMap tm_wf,
        const __grid_constant__ CUtensorMap tm_x1, const __grid_constant__ CUtensorMap tm_qkv) {
  extern __shared__ uint8_t smem_raw[];
  const uint32_t sb = (smem_u32(smem_raw) + 1023) & ~1023u;
  const int tid = threadIdx.x, warp = tid >> 5, lane = tid & 31;
  const bool is_fold = blockIdx.x < A_FOLD;
  const int n0 = blockIdx.x * 10;
  const uint32_t bX = sb + A_BAR + 128, bFF = sb + A_BAR + 136, bFD = sb + A_BAR + 144;
  if (tid == 256) {
    for (int i = 0; i < A_NST; i++) { mbar_init(sb + A_BAR + i * 8, 1); mbar_init(sb + A_BAR + 64 + i * 8, 4); }
    mbar_init(bX, 1); mbar_init(bFF, 1); mbar_init(bFD, 4);
    asm volatile("fence.mbarrier_init.release.cluster;" ::: "memory");
    if (is_fold) {
      const int mat = blockIdx.x / 9, rs = (blockIdx.x % 9) / 3, cs = blockIdx.x % 3;
      const CUtensorMap* mq = (mat < 2) ? &tm_wq64t : &tm_wq64s;
      const CUtensorMap* mo = (mat < 2) ? &tm_wot : &tm_wos;
      mbar_expect_tx(bFF, 2 * 24576);
      for (int c = 0; c < 3; c++) tma_load_2d(sb + A_W + c * 8192, mq, bFF, ((mat & 1) ? 384 : 0) + c * 64, rs * 64);
      if (mat & 1) tma_load_2d(sb + A_W + 24576, mo, bFF, cs * 64, 0);
      else for (int c = 0; c < 3; c++) tma_load_2d(sb + A_W + 24576 + c * 8192, mq, bFF, 192 + c * 64, cs * 64);
    }
  }
  asm volatile("griddepcontrol.launch_dependents;" ::: "memory");
  if (blockIdx.x == 129 && tid < 128) g_flag[tid] = 0;
  if (tid < 240) {
    const uint32_t a = sb + A_VB + (tid / 80) * 10240 + 70 * 128 + (tid % 80) * 16;
    asm volatile("st.shared.v4.b32 [%0], {%1,%1,%1,%1};" ::"r"(a), "r"(0) : "memory");
  }
  __syncthreads();

  if (warp >= 8) {
    asm volatile("setmaxnreg.dec.sync.aligned.u32 24;");
    if (warp == 8 && lane == 0) {
      __nanosleep(XDELAY);
      mbar_expect_tx(bX, 3 * 70 * 128);
      for (int c = 0; c < 3; c++) tma_load_3d(sb + A_VB + c * 10240, &tm_x, bX, c * 64, n0, 0);
      if (is_fold) mbar_wait(bFD, 0);
      for (int s = 0; s < 12; s++) {
        const int st = s % A_NST;
        const int g = s / 3;
        const int mat = (g == 0) ? 1 : (g == 1) ? 0 : g;
        if (s % 3 == 0) {
          uint32_t n = 0, v;
          do {
            asm volatile("ld.acquire.gpu.global.u32 %0, [%1];" : "=r"(v) : "l"(&g_wflag[mat]) : "memory");
          } while (v < 9u && ++n < (1u << 22));
          asm volatile("fence.proxy.async;" ::: "memory");
        }
        if (s >= A_NST) mbar_wait(sb + A_BAR + 64 + st * 8, ((s / A_NST) - 1) & 1);
        mbar_expect_tx(sb + A_BAR + st * 8, 24576);
        tma_load_2d(sb + A_W + st * 24576, &tm_wf, sb + A_BAR + st * 8, (mat & 1) * 192 + (s % 3) * 64, (mat >> 1) * 192);
      }
    }
    return;
  }

  asm volatile("setmaxnreg.inc.sync.aligned.u32 240;");
  const int wg = warp >> 2, wq = warp & 3;
  const bool elected = (tid & 127) == 0;
  TS(0, 0);

  if (is_fold && wg == 1) {
    const int mat = blockIdx.x / 9, rs = (blockIdx.x % 9) / 3, cs = blockIdx.x % 3;
    float d[32];
    mbar_wait(bFF, 0);
    const uint64_t ad = mk_desc_o(sb + A_W, 16, 1024);
    if (mat & 1) {
      const uint64_t bd = mk_desc_o(sb + A_W + 24576, 8192, 1024);
      wg_fence();
#pragma unroll
      for (int kk = 0; kk < 12; kk++) wgmma_n64_ss<1>(d, ad + (kk >> 2) * 512 + (kk & 3) * 2, bd + kk * 128, kk > 0);
      wg_commit();
    } else {
      const uint64_t bd = mk_desc_o(sb + A_W + 24576, 16, 1024);
      wg_fence();
#pragma unroll
      for (int kk = 0; kk < 12; kk++)
        wgmma_n64_ss<0>(d, ad + (kk >> 2) * 512 + (kk & 3) * 2, bd + (kk >> 2) * 512 + (kk & 3) * 2, kk > 0);
      wg_commit();
    }
    wg_wait<0>(); reg_fence(d);
    if (lane == 0) mbar_arrive(bFD);
    const int r0 = rs * 64 + wq * 16 + (lane >> 2);
    uint32_t* dst = reinterpret_cast<uint32_t*>(g_wf + ((size_t)(mat >> 1) * 192 + r0) * 384 + (mat & 1) * 192 + cs * 64 + (lane & 3) * 2);
#pragma unroll
    for (int j = 0; j < 8; j++) {
      dst[j * 4] = pack_bf16(d[4 * j], d[4 * j + 1]);
      dst[8 * 192 + j * 4] = pack_bf16(d[4 * j + 2], d[4 * j + 3]);
    }
    asm volatile("fence.proxy.async;" ::: "memory");
    named_bar(2, 128);
    if (elected) { __threadfence(); atomicAdd(&g_wflag[mat], 1u); }
  }

  const bool rows_ok = warp < 5;
  const FragAddr fa(warp, lane);
  uint32_t h[12][4];
  if (rows_ok) {
    mbar_wait(bX, 0);
#pragma unroll
    for (int k = 0; k < 12; k++) ldsm_x4(h[k], fa.at(sb + A_VB + (k >> 2) * 10240, k & 3));
    layernorm_frags(h);
#pragma unroll
    for (int k = 0; k < 12; k++) stsm_x4(fa.at(sb + A_HB + (k >> 2) * 10240, k & 3), h[k]);
  }
  fence_proxy_async();
  named_bar(1, 256);
  TS(0, 1);

  float acc0[36], acc1[36];
  {
    auto dst1 = [&](int s) { return s < 3 ? sb + A_VB + s * 10240 : sb + A_QB + (s - 3) * 16384; };
    a_issue(acc0, sb, wg);
    TS(0, 2);
    a_issue(acc1, sb, wg + 2); wg_wait<1>(); reg_fence(acc0); a_release(sb, wg, lane); store_chunk_t(acc0, dst1(wg), wq, lane);
    a_issue(acc0, sb, wg + 4); wg_wait<1>(); reg_fence(acc1); a_release(sb, wg + 2, lane); store_chunk_t(acc1, dst1(wg + 2), wq, lane);
    wg_wait<0>(); reg_fence(acc0); a_release(sb, wg + 4, lane); store_chunk_t(acc0, dst1(wg + 4), wq, lane);
  }
  fence_proxy_async();
  named_bar(1, 256);
  TS(0, 3);
  uint32_t pf[5][4];
  {
    float sacc[40];
    const uint64_t qd = mk_desc_o(sb + A_QB + wg * 8192, 16, 1024);
    const uint64_t kd = mk_desc_o(sb + A_HB, 16, 1024);
    wg_fence();
#pragma unroll
    for (int kk = 0; kk < 12; kk++)
      wgmma_n80_ss<0>(sacc, qd + (kk >> 2) * 1024 + (kk & 3) * 2, kd + (kk >> 2) * 640 + (kk & 3) * 2, kk > 0);
    wg_commit();
    wg_wait<0>(); reg_fence(sacc);
    named_bar(1, 256);
    if (tid == 0) {
      mbar_expect_tx(bX, 3 * 70 * 128);
      for (int c = 0; c < 3; c++) tma_load_3d(sb + A_QB + c * 16384, &tm_x, bX, c * 64, n0, 0);
    }
    TS(0, 4);
    const int r0 = 16 * warp + (lane >> 2), r1 = r0 + 8;
    const unsigned long long MLO = 0x1004010040100401ull;
    const int sh = 2 * (lane & 3);
    unsigned long long lo0, lo1; uint32_t hi0, hi1;
    {
      const int a = r0 % 10, b = r1 % 10;
      unsigned long long l = MLO << a; uint32_t hh = a >= 4 ? (1u << (a - 4)) : 0u;
      lo0 = (l >> sh) | (sh ? ((unsigned long long)hh << (64 - sh)) : 0ull); hi0 = hh >> sh;
      l = MLO << b; hh = b >= 4 ? (1u << (b - 4)) : 0u;
      lo1 = (l >> sh) | (sh ? ((unsigned long long)hh << (64 - sh)) : 0ull); hi1 = hh >> sh;
    }
    const float cs = 0.07216878364870322f * 1.4426950408889634f;
    float mx0 = -INFINITY, mx1 = -INFINITY;
#pragma unroll
    for (int j = 0; j < 10; j++) {
#pragma unroll
      for (int e = 0; e < 2; e++) {
        const int pos = 8 * j + e;
        const bool v0 = pos < 64 ? ((lo0 >> pos) & 1) : ((hi0 >> (pos - 64)) & 1);
        const bool v1 = pos < 64 ? ((lo1 >> pos) & 1) : ((hi1 >> (pos - 64)) & 1);
        sacc[4 * j + e] = v0 ? sacc[4 * j + e] * cs : -INFINITY;
        sacc[4 * j + 2 + e] = v1 ? sacc[4 * j + 2 + e] * cs : -INFINITY;
        mx0 = fmaxf(mx0, sacc[4 * j + e]);
        mx1 = fmaxf(mx1, sacc[4 * j + 2 + e]);
      }
    }
    mx0 = fmaxf(mx0, __shfl_xor_sync(0xffffffffu, mx0, 1)); mx1 = fmaxf(mx1, __shfl_xor_sync(0xffffffffu, mx1, 1));
    mx0 = fmaxf(mx0, __shfl_xor_sync(0xffffffffu, mx0, 2)); mx1 = fmaxf(mx1, __shfl_xor_sync(0xffffffffu, mx1, 2));
    float l0 = 0.f, l1 = 0.f;
#pragma unroll
    for (int j = 0; j < 10; j++) {
#pragma unroll
      for (int e = 0; e < 2; e++) {
        sacc[4 * j + e] = ex2(sacc[4 * j + e] - mx0); l0 += sacc[4 * j + e];
        sacc[4 * j + 2 + e] = ex2(sacc[4 * j + 2 + e] - mx1); l1 += sacc[4 * j + 2 + e];
      }
    }
    l0 += __shfl_xor_sync(0xffffffffu, l0, 1); l1 += __shfl_xor_sync(0xffffffffu, l1, 1);
    l0 += __shfl_xor_sync(0xffffffffu, l0, 2); l1 += __shfl_xor_sync(0xffffffffu, l1, 2);
    const float i0 = 1.f / l0, i1 = 1.f / l1;
#pragma unroll
    for (int k = 0; k < 5; k++) {
      pf[k][0] = pack_bf16(sacc[8 * k + 0] * i0, sacc[8 * k + 1] * i0); pf[k][1] = pack_bf16(sacc[8 * k + 2] * i1, sacc[8 * k + 3] * i1);
      pf[k][2] = pack_bf16(sacc[8 * k + 4] * i0, sacc[8 * k + 5] * i0); pf[k][3] = pack_bf16(sacc[8 * k + 6] * i1, sacc[8 * k + 7] * i1);
    }
  }
  TS(0, 5);
  {
    float oacc[96];
    const uint64_t vd = mk_desc_o(sb + A_VB, 10240, 1024);
    wg_fence();
#pragma unroll
    for (int kk = 0; kk < 5; kk++) wgmma_n192_rs<1>(oacc, pf[kk], vd + kk * 128, kk > 0);
    wg_commit();
    wg_wait<0>(); reg_fence(oacc);
    TS(0, 6);
    if (rows_ok) {
      mbar_wait(bX, 1);
#pragma unroll
      for (int c = 0; c < 3; c++) resid_chunk(&h[4 * c], &oacc[32 * c], 1.f, 1.f, sb + A_QB + c * 16384, fa);
      fence_proxy_async();
      named_bar(4, 160);
      if (tid == 0) {
        for (int c = 0; c < 3; c++) tma_store_3d(&tm_x1, sb + A_QB + c * 16384, c * 64, n0, 0);
        bulk_commit();
      }
      layernorm_frags(h);
#pragma unroll
      for (int k = 0; k < 12; k++) stsm_x4(fa.at(sb + A_HB + (k >> 2) * 10240, k & 3), h[k]);
    }
  }
  fence_proxy_async();
  named_bar(1, 256);
  TS(0, 7);
  if (tid == 128) {
    for (int c = 0; c < 3; c++) tma_store_3d(&tm_qkv, sb + A_HB + c * 10240, 192 + c * 64, n0, 0);
    bulk_commit();
  }
  {
    auto dst2 = [&](int s) { return s < 8 ? sb + A_VB + (s - 6) * 10240 : sb + A_W + (s % A_NST) * 24576; };
    auto flush = [&](int s) {
      fence_proxy_async();
      named_bar(2 + wg, 128);
      if (elected) { tma_store_3d(&tm_qkv, dst2(s), (s < 9 ? (s - 6) * 64 : 384 + (s - 9) * 64), n0, 0); bulk_commit(); }
    };
    a_issue(acc0, sb, 6 + wg);
    a_issue(acc1, sb, 8 + wg); wg_wait<1>(); reg_fence(acc0); a_release(sb, 6 + wg, lane);
    store_chunk_t(acc0, dst2(6 + wg), wq, lane);
    flush(6 + wg);
    a_issue(acc0, sb, 10 + wg); wg_wait<1>(); reg_fence(acc1);
    named_bar(2 + wg, 128);
    store_chunk_t(acc1, dst2(8 + wg), wq, lane);
    flush(8 + wg);
    wg_wait<0>(); reg_fence(acc0);
    named_bar(2 + wg, 128);
    store_chunk_t(acc0, dst2(10 + wg), wq, lane);
    flush(10 + wg);
  }
  TS(0, 9);
  if (elected) bulk_wait_read0();
  TS(0, 10);
}

constexpr int B_GRID = 132;
constexpr int B_SLOT = 55296;
constexpr int B_Q = 0;
constexpr int B_KV = 49152;
constexpr int B_BAR = B_KV + 3 * B_SLOT;
constexpr int B_SMEM = B_BAR + 256 + 1024;

__device__ __forceinline__ void bar_arrive(int id, int nthreads) {
  asm volatile("bar.arrive %0, %1;" ::"r"(id), "r"(nthreads) : "memory");
}
#define PP_MODE 0
#define PP_WAIT(x, y) named_bar(x, y)
#define PP_ARRIVE(x, y) bar_arrive(x, y)
__device__ __forceinline__ void b_segment(int sg, int& tile, int& k0, int& k1) {
  const int grp = blockIdx.x / 12, ci = blockIdx.x - grp * 12;
  if (ci < 7) { tile = grp * 7 + ci; k0 = 3; k1 = 9; }
  else {
    const int hh = ci - 7;
    tile = grp * 7 + ((0x54210 >> (4 * hh)) & 15) + sg;
    k0 = sg ? 0 : ((0x10210 >> (4 * hh)) & 15);
    k1 = sg ? ((0x31321 >> (4 * hh)) & 15) : 3;
  }
}

__global__ void __launch_bounds__(384, 1)
kernelB(const __grid_constant__ CUtensorMap tm_q, const __grid_constant__ CUtensorMap tm_kv,
        const __grid_constant__ CUtensorMap tm_x1, const __grid_constant__ CUtensorMap tm_out) {
  extern __shared__ uint8_t smem_raw[];
  const uint32_t sb = (smem_u32(smem_raw) + 1023) & ~1023u;
  const int tid = threadIdx.x, warp = tid >> 5, lane = tid & 31;
  const uint32_t bF = sb + B_BAR, bE = sb + B_BAR + 32, bQF = sb + B_BAR + 64, bQE = sb + B_BAR + 72;
  if (tid == 0) {
    for (int i = 0; i < 3; i++) { mbar_init(bF + i * 8, 1); mbar_init(bE + i * 8, 8); }
    mbar_init(bQF, 1); mbar_init(bQE, 8);
    asm volatile("fence.mbarrier_init.release.cluster;" ::: "memory");
    prefetch_tmap(&tm_q); prefetch_tmap(&tm_kv); prefetch_tmap(&tm_x1); prefetch_tmap(&tm_out);
  }
  __syncthreads();
  asm volatile("griddepcontrol.wait;" ::: "memory");
  const int grp = blockIdx.x / 12, ci = blockIdx.x - grp * 12;
  const bool owner = ci < 7;
  const int nseg = owner ? 1 : 2;

  if (warp >= 8) {
    asm volatile("setmaxnreg.dec.sync.aligned.u32 24;");
    if (warp == 8 && lane == 0) {
      if (blockIdx.x == 0) { g_wflag[0] = 0; g_wflag[1] = 0; g_wflag[2] = 0; g_wflag[3] = 0; }
      int it = 0;
      for (int sg = 0; sg < nseg; sg++) {
        int tile, k0, k1;
        b_segment(sg, tile, k0, k1);
        const int t = tile / 11, qt = tile - t * 11;
        if (sg > 0) mbar_wait(bQE, 0);
        mbar_expect_tx(bQF, 49152);
        for (int c = 0; c < 3; c++) tma_load_3d(sb + B_Q + c * 16384, &tm_q, bQF, c * 64, qt * 128, t);
        const int n = k1 - k0;
        for (int e = 0; e < 2 * n; e++) {
          const int sl = it % 3;
          if (it >= 3) mbar_wait(bE + sl * 8, ((it / 3) - 1) & 1);
#define EXP_NCH 3
          mbar_expect_tx(bF + sl * 8, EXP_NCH * 18432);
          for (int c = 0; c < EXP_NCH; c++)
            tma_load_3d(sb + B_KV + sl * B_SLOT + c * 18432, &tm_kv, bF + sl * 8, 192 + (e & 1) * 192 + c * 64, (k0 + (e >> 1)) * 144, t);
          if (it == 0) mbar_wait(bF, 0);
          it++;
        }
      }
      if (owner) {
        const int tile = grp * 7 + ci;
        const int t = tile / 11, qt = tile - t * 11;
        mbar_wait(bQE, 0);
        mbar_expect_tx(bQF, 49152);
        for (int c = 0; c < 3; c++) tma_load_3d(sb + B_Q + c * 16384, &tm_x1, bQF, c * 64, qt * 128, t);
      }
    } else if ((warp == 9 || warp == 10) && !owner) {
      for (int sg = 0; sg < 2; sg++) {
        named_bar(5 + (warp - 9), 160);
        if (lane == 0) {
          __threadfence();
          atomicAdd(&g_flag[(grp * 5 + (ci - 7)) * 2 + sg], 1u);
        }
        __syncwarp();
      }
    }
    return;
  }

  asm volatile("setmaxnreg.inc.sync.aligned.u32 240;");
  const int wg = warp >> 2, wq = warp & 3;
  const int wtid = tid & 127;
  const float cs = 0.07216878364870322f * 1.4426950408889634f;
  float oacc[96], sacc[72];
  uint32_t pf[9][4];
  float m0, m1, l0, l1;
  int it = 0;
  const uint32_t qb = sb + B_Q + wg * 8192;
  if (wg == 1) { PP_ARRIVE(3, 256); }
  TS(1, 0);
  int tsi = 1;

  auto issue_qk = [&](int slot) {
    const uint64_t kd = mk_desc_o(sb + B_KV + slot * B_SLOT, 16, 1024);
    const uint64_t qd = mk_desc_o(qb, 16, 1024);
#pragma unroll
    for (int kk = 0; kk < 12; kk++)
      wgmma_n144_ss<0>(sacc, qd + (kk >> 2) * 1024 + (kk & 3) * 2, kd + (kk >> 2) * 1152 + (kk & 3) * 2, kk > 0);
    wg_commit();
  };
  auto issue_pv = [&](int slot, int accum) {
    const uint64_t vd = mk_desc_o(sb + B_KV + slot * B_SLOT, 18432, 1024);
#pragma unroll
    for (int kk = 0; kk < 9; kk++) wgmma_n192_rs<1>(oacc, pf[kk], vd + kk * 128, kk > 0 ? 1 : accum);
    wg_commit();
  };
  auto softmax = [&](bool first) {
    float t0[4], t1[4];
#pragma unroll
    for (int q = 0; q < 4; q++) {
      t0[q] = fmaxf(sacc[4 * q], sacc[4 * q + 1]);
      t1[q] = fmaxf(sacc[4 * q + 2], sacc[4 * q + 3]);
    }
#pragma unroll
    for (int j = 4; j < 18; j++) {
      t0[j & 3] = fmaxf(t0[j & 3], fmaxf(sacc[4 * j], sacc[4 * j + 1]));
      t1[j & 3] = fmaxf(t1[j & 3], fmaxf(sacc[4 * j + 2], sacc[4 * j + 3]));
    }
    float mx0 = fmaxf(fmaxf(t0[0], t0[1]), fmaxf(t0[2], t0[3]));
    float mx1 = fmaxf(fmaxf(t1[0], t1[1]), fmaxf(t1[2], t1[3]));
    mx0 = fmaxf(mx0, __shfl_xor_sync(0xffffffffu, mx0, 1)); mx1 = fmaxf(mx1, __shfl_xor_sync(0xffffffffu, mx1, 1));
    mx0 = fmaxf(mx0, __shfl_xor_sync(0xffffffffu, mx0, 2)); mx1 = fmaxf(mx1, __shfl_xor_sync(0xffffffffu, mx1, 2));
    if (first) {
      m0 = mx0; m1 = mx1; l0 = 0.f; l1 = 0.f;
    } else {
      const bool need = !((mx0 - m0) * cs <= 8.f) || !((mx1 - m1) * cs <= 8.f);
      if (__any_sync(0xffffffffu, need)) {
        mx0 = fmaxf(mx0, m0); mx1 = fmaxf(mx1, m1);
        const float a0 = ex2((m0 - mx0) * cs), a1 = ex2((m1 - mx1) * cs);
        m0 = mx0; m1 = mx1;
        l0 *= a0; l1 *= a1;
#pragma unroll
        for (int i = 0; i < 24; i++) {
          oacc[4 * i] *= a0; oacc[4 * i + 1] *= a0; oacc[4 * i + 2] *= a1; oacc[4 * i + 3] *= a1;
        }
      }
    }
    const float mc0 = m0 * cs, mc1 = m1 * cs;
#pragma unroll
    for (int q = 0; q < 4; q++) { t0[q] = 0.f; t1[q] = 0.f; }
#pragma unroll
    for (int k = 0; k < 9; k++) {
      float p[8];
#pragma unroll
      for (int e = 0; e < 8; e++) p[e] = ex2(fmaf(sacc[8 * k + e], cs, (e & 2) ? -mc1 : -mc0));
      t0[0] += p[0]; t0[1] += p[1]; t0[2] += p[4]; t0[3] += p[5];
      t1[0] += p[2]; t1[1] += p[3]; t1[2] += p[6]; t1[3] += p[7];
      pf[k][0] = pack_bf16(p[0], p[1]); pf[k][1] = pack_bf16(p[2], p[3]);
      pf[k][2] = pack_bf16(p[4], p[5]); pf[k][3] = pack_bf16(p[6], p[7]);
    }
    l0 += (t0[0] + t0[1]) + (t0[2] + t0[3]);
    l1 += (t1[0] + t1[1]) + (t1[2] + t1[3]);
  };

  auto part_fetch = [&](uint4 (&pv)[13], int slot) {
    if (wtid == 0) {
      uint32_t n = 0, v;
      do {
        asm volatile("ld.acquire.gpu.global.u32 %0, [%1];" : "=r"(v) : "l"(&g_flag[slot]) : "memory");
      } while (v < 2u && ++n < (1u << 22));
    }
    named_bar(1 + wg, 128);
    const uint4* src = g_part + (size_t)(slot * 2 + wg) * 13 * 128 + wtid;
#pragma unroll
    for (int i = 0; i < 13; i++) pv[i] = __ldcg(src + i * 128);
  };
  auto part_merge = [&](const uint4 (&pv)[13]) {
    const float pm0 = __uint_as_float(pv[12].x), pm1 = __uint_as_float(pv[12].y);
    const float mx0 = fmaxf(m0, pm0), mx1 = fmaxf(m1, pm1);
    const float a0 = ex2((m0 - mx0) * cs), a1 = ex2((m1 - mx1) * cs);
    const float b0 = ex2((pm0 - mx0) * cs), b1 = ex2((pm1 - mx1) * cs);
    m0 = mx0; m1 = mx1;
    l0 = l0 * a0 + __uint_as_float(pv[12].z) * b0; l1 = l1 * a1 + __uint_as_float(pv[12].w) * b1;
#pragma unroll
    for (int i = 0; i < 12; i++) {
      const uint4 v = pv[i];
      oacc[8 * i + 0] = oacc[8 * i + 0] * a0 + bf_lo(v.x) * b0; oacc[8 * i + 1] = oacc[8 * i + 1] * a0 + bf_hi(v.x) * b0;
      oacc[8 * i + 2] = oacc[8 * i + 2] * a1 + bf_lo(v.y) * b1; oacc[8 * i + 3] = oacc[8 * i + 3] * a1 + bf_hi(v.y) * b1;
      oacc[8 * i + 4] = oacc[8 * i + 4] * a0 + bf_lo(v.z) * b0; oacc[8 * i + 5] = oacc[8 * i + 5] * a0 + bf_hi(v.z) * b0;
      oacc[8 * i + 6] = oacc[8 * i + 6] * a1 + bf_lo(v.w) * b1; oacc[8 * i + 7] = oacc[8 * i + 7] * a1 + bf_hi(v.w) * b1;
    }
  };

  for (int sg = 0; sg < nseg; sg++) {
    int n;
    { int tile, k0, k1; b_segment(sg, tile, k0, k1); n = k1 - k0; }
    mbar_wait(bQF, sg & 1);
    if (sg == 0) TS(1, 12);
    {
      const int sl = it % 3;
      mbar_wait(bF + sl * 8, (it / 3) & 1);
      if (sg == 0) TS(1, 13);
      PP_WAIT(3 + wg, 256);
      wg_fence();
      issue_qk(sl);
      PP_ARRIVE(3 + (wg ^ 1), 256);
      wg_wait<0>(); reg_fence(sacc);
      if (sg == 0) TS(1, 14);
      if (lane == 0) { mbar_arrive(bE + sl * 8); if (n == 1) mbar_arrive(bQE); }
      it++;
      softmax(true);
    }
    TS(1, tsi); tsi++;
    for (int j = 1; j < n; j++) {
      const int slv = it % 3, slk = (it + 1) % 3;
      mbar_wait(bF + slv * 8, (it / 3) & 1);
      PP_WAIT(3 + wg, 256);
      wg_fence();
      issue_pv(slv, j > 1);
      mbar_wait(bF + slk * 8, ((it + 1) / 3) & 1);
      issue_qk(slk);
      PP_ARRIVE(3 + (wg ^ 1), 256);
      wg_wait<1>(); reg_fence(oacc);
      if (lane == 0) mbar_arrive(bE + slv * 8);
      wg_wait<0>(); reg_fence(sacc);
      if (lane == 0) { mbar_arrive(bE + slk * 8); if (j == n - 1) mbar_arrive(bQE); }
      it += 2;
      softmax(false);
      TS(1, tsi); tsi++;
    }
    {
      const int sl = it % 3;
      mbar_wait(bF + sl * 8, (it / 3) & 1);
      PP_WAIT(3 + wg, 256);
      wg_fence();
      issue_pv(sl, n > 1);
      if (!(wg == 1 && sg == nseg - 1)) { PP_ARRIVE(3 + (wg ^ 1), 256); }
      const bool do_merge = owner || (sg == 1 && (ci == 7 || ci == 8 || ci == 10));
      uint4 pv[13];
      if (do_merge) part_fetch(pv, owner ? grp * 10 + ((0x9765310 >> (4 * ci)) & 15) : (grp * 5 + (ci - 6)) * 2);
      wg_wait<0>(); reg_fence(oacc);
      if (lane == 0) mbar_arrive(bE + sl * 8);
      it++;
      TS(1, tsi); tsi++;
      if (do_merge) part_merge(pv);
    }
    if (!owner) {
      const int slot = (grp * 5 + (ci - 7)) * 2 + sg;
      uint4* dst = g_part + (size_t)(slot * 2 + wg) * 13 * 128 + wtid;
#pragma unroll
      for (int i = 0; i < 12; i++)
        dst[i * 128] = make_uint4(pack_bf16(oacc[8 * i], oacc[8 * i + 1]), pack_bf16(oacc[8 * i + 2], oacc[8 * i + 3]),
                                  pack_bf16(oacc[8 * i + 4], oacc[8 * i + 5]), pack_bf16(oacc[8 * i + 6], oacc[8 * i + 7]));
      dst[12 * 128] = make_uint4(__float_as_uint(m0), __float_as_uint(m1), __float_as_uint(l0), __float_as_uint(l1));
      bar_arrive(5 + wg, 160);
      TS(1, tsi); tsi++;
    }
  }
  if (!owner) return;
  TS(1, 21);
  l0 += __shfl_xor_sync(0xffffffffu, l0, 1); l0 += __shfl_xor_sync(0xffffffffu, l0, 2);
  l1 += __shfl_xor_sync(0xffffffffu, l1, 1); l1 += __shfl_xor_sync(0xffffffffu, l1, 2);
  const float i0 = 1.f / l0, i1 = 1.f / l1;
  mbar_wait(bQF, 1);
  const FragAddr fa(wq, lane);
#pragma unroll
  for (int c = 0; c < 3; c++) resid_chunk(nullptr, &oacc[32 * c], i0, i1, qb + c * 16384, fa);
  fence_proxy_async();
  named_bar(1 + wg, 128);
  TS(1, 22);
  if (wtid == 0) {
    const int tile = grp * 7 + ci;
    const int t = tile / 11, qt = tile - t * 11;
    if (qt * 128 + wg * 64 < NL) {
      for (int c = 0; c < 3; c++) tma_store_3d(&tm_out, qb + c * 16384, c * 64, qt * 128 + wg * 64, t);
      bulk_commit();
      bulk_wait_read0();
    }
  }
  TS(1, 23);
}

typedef CUresult (*EncodeFn)(CUtensorMap*, CUtensorMapDataType, cuuint32_t, void*, const cuuint64_t*, const cuuint64_t*,
                             const cuuint32_t*, const cuuint32_t*, CUtensorMapInterleave, CUtensorMapSwizzle,
                             CUtensorMapL2promotion, CUtensorMapFloatOOBfill);

void make_map(EncodeFn enc, CUtensorMap* m, const void* ptr, int rank, const uint64_t* dims, const uint32_t* box) {
  cuuint64_t gd[3], gs[2];
  cuuint32_t bx[3], es[3] = {1, 1, 1};
  uint64_t stride = 2;
  for (int i = 0; i < rank; i++) {
    gd[i] = dims[i]; bx[i] = box[i];
    stride *= dims[i];
    if (i < rank - 1) gs[i] = stride;
  }
  enc(m, CU_TENSOR_MAP_DATA_TYPE_BFLOAT16, rank, const_cast<void*>(ptr), gd, gs, bx, es, CU_TENSOR_MAP_INTERLEAVE_NONE,
      CU_TENSOR_MAP_SWIZZLE_128B, CU_TENSOR_MAP_L2_PROMOTION_L2_256B, CU_TENSOR_MAP_FLOAT_OOB_FILL_NONE);
}

}

extern "C" void kernel_launch(void* const* d_in, const int* in_sizes, int n_in, void* d_out, int out_size) {
  (void)in_sizes; (void)n_in; (void)out_size;
  EncodeFn enc = nullptr;
  cudaDriverEntryPointQueryResult qres;
  cudaGetDriverEntryPoint("cuTensorMapEncodeTiled", (void**)&enc, cudaEnableDefault, &qres);
  void *p_x1, *p_qkv, *p_wf;
  cudaGetSymbolAddress(&p_wf, g_wf);
  cudaGetSymbolAddress(&p_x1, g_x1);
  cudaGetSymbolAddress(&p_qkv, g_qkv);
  cudaFuncSetAttribute(kernelA, cudaFuncAttributeMaxDynamicSharedMemorySize, A_SMEM);
  cudaFuncSetAttribute(kernelB, cudaFuncAttributeMaxDynamicSharedMemorySize, B_SMEM);

  CUtensorMap tm_x, tm_wqkvt, tm_wot, tm_wqkvs, tm_x1s, tm_qkvs, tm_q, tm_kv, tm_wos, tm_x1l, tm_out, tm_wf;
  const uint64_t d_act[3] = {192, 1296, 7}, d_qkv[3] = {576, 1296, 7}, d_w3[2] = {576, 192}, d_w1[2] = {192, 192}, d_wf[2] = {384, 384};
  const uint32_t b_a[3] = {64, 10, 7}, b_w[2] = {64, 192}, b_q[3] = {64, 128, 1}, b_kv[3] = {64, 144, 1}, b_o[3] = {64, 64, 1}, b_w64[2] = {64, 64};
  make_map(enc, &tm_x, d_in[0], 3, d_act, b_a);
  make_map(enc, &tm_wqkvt, d_in[1], 2, d_w3, b_w64);
  make_map(enc, &tm_wot, d_in[2], 2, d_w1, b_w);
  make_map(enc, &tm_wqkvs, d_in[3], 2, d_w3, b_w64);
  make_map(enc, &tm_wos, d_in[4], 2, d_w1, b_w);
  make_map(enc, &tm_wf, p_wf, 2, d_wf, b_w);
  make_map(enc, &tm_x1s, p_x1, 3, d_act, b_a);
  make_map(enc, &tm_qkvs, p_qkv, 3, d_qkv, b_a);
  make_map(enc, &tm_q, p_qkv, 3, d_qkv, b_q);
  make_map(enc, &tm_kv, p_qkv, 3, d_qkv, b_kv);
  make_map(enc, &tm_x1l, p_x1, 3, d_act, b_q);
  make_map(enc, &tm_out, d_out, 3, d_act, b_o);

  kernelA<<<A_GRID, 384, A_SMEM, cudaStreamPerThread>>>(tm_x, tm_wqkvt, tm_wot, tm_wqkvs, tm_wos, tm_wf, tm_x1s, tm_qkvs);
  cudaLaunchConfig_t cfg = {};
  cfg.gridDim = dim3(B_GRID); cfg.blockDim = dim3(384); cfg.dynamicSmemBytes = B_SMEM; cfg.stream = cudaStreamPerThread;
  cudaLaunchAttribute at[1];
  at[0].id = cudaLaunchAttributeProgrammaticStreamSerialization;
  at[0].val.programmaticStreamSerializationAllowed = 1;
  cfg.attrs = at; cfg.numAttrs = 1;
  cudaLaunchKernelEx(&cfg, kernelB, tm_q, tm_kv, tm_x1l, tm_out);
}
```

```cpp
#include <cuda_runtime.h>
#include <cuda_bf16.h>
#include <cuda.h>
#include <stdint.h>

namespace {

constexpr int TT = 7, NL = 1296, CC = 192;

__device__ __align__(1024) __nv_bfloat16 g_x1[TT * NL * CC];
__device__ __align__(1024) __nv_bfloat16 g_qkv[TT * NL * 3 * CC];
__device__ __align__(1024) __nv_bfloat16 g_wf[2 * CC * 2 * CC];
__device__ __align__(1024) uint4 g_part[121 * 2 * 13 * 128];
__device__ unsigned int g_flag[128];
__device__ unsigned int g_wflag[4];

#define TS(k, i)

__device__ __forceinline__ uint32_t smem_u32(const void* p) { return (uint32_t)__cvta_generic_to_shared(p); }
__device__ __forceinline__ void mbar_init(uint32_t bar, uint32_t cnt) {
  asm volatile("mbarrier.init.shared::cta.b64 [%0], %1;" ::"r"(bar), "r"(cnt));
}
__device__ __forceinline__ void mbar_expect_tx(uint32_t bar, uint32_t bytes) {
  asm volatile("mbarrier.arrive.expect_tx.shared::cta.b64 _, [%0], %1;" ::"r"(bar), "r"(bytes) : "memory");
}
__device__ __forceinline__ void mbar_arrive(uint32_t bar) {
  asm volatile("mbarrier.arrive.shared::cta.b64 _, [%0];" ::"r"(bar) : "memory");
}
__device__ __forceinline__ bool mbar_try(uint32_t bar, uint32_t parity) {
  uint32_t ok;
  asm volatile("{\n.reg .pred p;\nmbarrier.try_wait.parity.shared::cta.b64 p, [%1], %2;\nselp.u32 %0, 1, 0, p;\n}"
               : "=r"(ok) : "r"(bar), "r"(parity) : "memory");
  return ok != 0;
}
__device__ __forceinline__ void mbar_wait(uint32_t bar, uint32_t parity) {
  if (mbar_try(bar, parity)) return;
  uint32_t n = 0;
  while (!mbar_try(bar, parity)) {
    if (++n > (1u << 22)) break;
  }
}
__device__ __forceinline__ void tma_load_2d(uint32_t dst, const CUtensorMap* m, uint32_t bar, int c0, int c1) {
  asm volatile("cp.async.bulk.tensor.2d.shared::cluster.global.mbarrier::complete_tx::bytes [%0], [%1, {%3, %4}], [%2];"
               ::"r"(dst), "l"(m), "r"(bar), "r"(c0), "r"(c1) : "memory");
}
__device__ __forceinline__ void tma_load_3d(uint32_t dst, const CUtensorMap* m, uint32_t bar, int c0, int c1, int c2) {
  asm volatile("cp.async.bulk.tensor.3d.shared::cluster.global.mbarrier::complete_tx::bytes [%0], [%1, {%3, %4, %5}], [%2];"
               ::"r"(dst), "l"(m), "r"(bar), "r"(c0), "r"(c1), "r"(c2) : "memory");
}
__device__ __forceinline__ void tma_store_3d(const CUtensorMap* m, uint32_t src, int c0, int c1, int c2) {
  asm volatile("cp.async.bulk.tensor.3d.global.shared::cta.bulk_group [%0, {%2, %3, %4}], [%1];"
               ::"l"(m), "r"(src), "r"(c0), "r"(c1), "r"(c2) : "memory");
}
__device__ __forceinline__ void bulk_commit() { asm volatile("cp.async.bulk.commit_group;" ::: "memory"); }
__device__ __forceinline__ void bulk_wait_read0() { asm volatile("cp.async.bulk.wait_group.read 0;" ::: "memory"); }
__device__ __forceinline__ void bulk_wait_read1() { asm volatile("cp.async.bulk.wait_group.read 1;" ::: "memory"); }
__device__ __forceinline__ void bulk_wait0() { asm volatile("cp.async.bulk.wait_group 0;" ::: "memory"); }
__device__ __forceinline__ void fence_proxy_async() { asm volatile("fence.proxy.async.shared::cta;" ::: "memory"); }
__device__ __forceinline__ void prefetch_tmap(const CUtensorMap* m) {
  asm volatile("prefetch.tensormap [%0];" ::"l"(m) : "memory");
}
__device__ __forceinline__ void wg_fence() { asm volatile("wgmma.fence.sync.aligned;" ::: "memory"); }
__device__ __forceinline__ void wg_commit() { asm volatile("wgmma.commit_group.sync.aligned;" ::: "memory"); }
template <int N> __device__ __forceinline__ void wg_wait() { asm volatile("wgmma.wait_group.sync.aligned %0;" ::"n"(N) : "memory"); }
__device__ __forceinline__ void named_bar(int id, int nthreads) {
  asm volatile("bar.sync %0, %1;" ::"r"(id), "r"(nthreads) : "memory");
}
__device__ __forceinline__ void ldsm_x4(uint32_t (&r)[4], uint32_t addr) {
  asm volatile("ldmatrix.sync.aligned.m8n8.x4.shared.b16 {%0,%1,%2,%3}, [%4];"
               : "=r"(r[0]), "=r"(r[1]), "=r"(r[2]), "=r"(r[3]) : "r"(addr) : "memory");
}
__device__ __forceinline__ void stsm_x4(uint32_t addr, const uint32_t (&r)[4]) {
  asm volatile("stmatrix.sync.aligned.m8n8.x4.shared.b16 [%0], {%1,%2,%3,%4};"
               ::"r"(addr), "r"(r[0]), "r"(r[1]), "r"(r[2]), "r"(r[3]) : "memory");
}
__device__ __forceinline__ uint32_t pack_bf16(float lo, float hi) {
  uint32_t r;
  asm("cvt.rn.bf16x2.f32 %0, %1, %2;" : "=r"(r) : "f"(hi), "f"(lo));
  return r;
}
__device__ __forceinline__ float bf_lo(uint32_t v) { return __uint_as_float(v << 16); }
__device__ __forceinline__ float bf_hi(uint32_t v) { return __uint_as_float(v & 0xffff0000u); }
__device__ __forceinline__ float ex2(float x) {
  float y;
  asm("ex2.approx.ftz.f32 %0, %1;" : "=f"(y) : "f"(x));
  return y;
}
__device__ __forceinline__ uint64_t mk_desc(uint32_t addr, uint32_t lbo, uint32_t sbo) {
  return (uint64_t)((addr & 0x3FFFF) >> 4) | ((uint64_t)((lbo & 0x3FFFF) >> 4) << 16) |
         ((uint64_t)((sbo & 0x3FFFF) >> 4) << 32) | (1ull << 62);
}
__device__ __forceinline__ uint64_t mk_desc_o(uint32_t addr, uint32_t lbo, uint32_t sbo) {
  asm volatile("" : "+r"(addr));
  return mk_desc(addr, lbo, sbo);
}
template <int N> __device__ __forceinline__ void reg_fence(uint32_t (&d)[N]) {
#pragma unroll
  for (int i = 0; i < N; i++) asm volatile("" : "+r"(d[i])::"memory");
}
template <int N> __device__ __forceinline__ void reg_fence(float (&d)[N]) {
#pragma unroll
  for (int i = 0; i < N; i++) asm volatile("" : "+f"(d[i])::"memory");
}

template<int TB> __device__ __forceinline__ void wgmma_n144_ss(float (&d)[72], uint64_t da, uint64_t db, int sc) {
  asm volatile("{\n.reg .pred p;\nsetp.ne.b32 p, %74, 0;\n"
    "wgmma.mma_async.sync.aligned.m64n144k16.f32.bf16.bf16 {%0, %1, %2, %3, %4, %5, %6, %7, %8, %9, %10, %11, %12, %13, %14, %15, %16, %17, %18, %19, %20, %21, %22, %23, %24, %25, %26, %27, %28, %29, %30, %31, %32, %33, %34, %35, %36, %37, %38, %39, %40, %41, %42, %43, %44, %45, %46, %47, %48, %49, %50, %51, %52, %53, %54, %55, %56, %57, %58, %59, %60, %61, %62, %63, %64, %65, %66, %67, %68, %69, %70, %71}, %72, %73, p, 1, 1, 0, %75;\n}\n"
    : "+f"(d[0]), "+f"(d[1]), "+f"(d[2]), "+f"(d[3]), "+f"(d[4]), "+f"(d[5]), "+f"(d[6]), "+f"(d[7]), "+f"(d[8]), "+f"(d[9]), "+f"(d[10]), "+f"(d[11]), "+f"(d[12]), "+f"(d[13]), "+f"(d[14]), "+f"(d[15]), "+f"(d[16]), "+f"(d[17]), "+f"(d[18]), "+f"(d[19]), "+f"(d[20]), "+f"(d[21]), "+f"(d[22]), "+f"(d[23]), "+f"(d[24]), "+f"(d[25]), "+f"(d[26]), "+f"(d[27]), "+f"(d[28]), "+f"(d[29]), "+f"(d[30]), "+f"(d[31]), "+f"(d[32]), "+f"(d[33]), "+f"(d[34]), "+f"(d[35]), "+f"(d[36]), "+f"(d[37]), "+f"(d[38]), "+f"(d[39]), "+f"(d[40]), "+f"(d[41]), "+f"(d[42]), "+f"(d[43]), "+f"(d[44]), "+f"(d[45]), "+f"(d[46]), "+f"(d[47]), "+f"(d[48]), "+f"(d[49]), "+f"(d[50]), "+f"(d[51]), "+f"(d[52]), "+f"(d[53]), "+f"(d[54]), "+f"(d[55]), "+f"(d[56]), "+f"(d[57]), "+f"(d[58]), "+f"(d[59]), "+f"(d[60]), "+f"(d[61]), "+f"(d[62]), "+f"(d[63]), "+f"(d[64]), "+f"(d[65]), "+f"(d[66]), "+f"(d[67]), "+f"(d[68]), "+f"(d[69]), "+f"(d[70]), "+f"(d[71])
    : "l"(da), "l"(db), "r"(sc), "n"(TB));
}
template<int TB> __device__ __forceinline__ void wgmma_n192_rs(float (&d)[96], const uint32_t (&a)[4], uint64_t db, int sc) {
  asm volatile("{\n.reg .pred p;\nsetp.ne.b32 p, %101, 0;\n"
    "wgmma.mma_async.sync.aligned.m64n192k16.f32.bf16.bf16 {%0, %1, %2, %3, %4, %5, %6, %7, %8, %9, %10, %11, %12, %13, %14, %15, %16, %17, %18, %19, %20, %21, %22, %23, %24, %25, %26, %27, %28, %29, %30, %31, %32, %33, %34, %35, %36, %37, %38, %39, %40, %41, %42, %43, %44, %45, %46, %47, %48, %49, %50, %51, %52, %53, %54, %55, %56, %57, %58, %59, %60, %61, %62, %63, %64, %65, %66, %67, %68, %69, %70, %71, %72, %73, %74, %75, %76, %77, %78, %79, %80, %81, %82, %83, %84, %85, %86, %87, %88, %89, %90, %91, %92, %93, %94, %95}, {%96, %97, %98, %99}, %100, p, 1, 1, %102;\n}\n"
    : "+f"(d[0]), "+f"(d[1]), "+f"(d[2]), "+f"(d[3]), "+f"(d[4]), "+f"(d[5]), "+f"(d[6]), "+f"(d[7]), "+f"(d[8]), "+f"(d[9]), "+f"(d[10]), "+f"(d[11]), "+f"(d[12]), "+f"(d[13]), "+f"(d[14]), "+f"(d[15]), "+f"(d[16]), "+f"(d[17]), "+f"(d[18]), "+f"(d[19]), "+f"(d[20]), "+f"(d[21]), "+f"(d[22]), "+f"(d[23]), "+f"(d[24]), "+f"(d[25]), "+f"(d[26]), "+f"(d[27]), "+f"(d[28]), "+f"(d[29]), "+f"(d[30]), "+f"(d[31]), "+f"(d[32]), "+f"(d[33]), "+f"(d[34]), "+f"(d[35]), "+f"(d[36]), "+f"(d[37]), "+f"(d[38]), "+f"(d[39]), "+f"(d[40]), "+f"(d[41]), "+f"(d[42]), "+f"(d[43]), "+f"(d[44]), "+f"(d[45]), "+f"(d[46]), "+f"(d[47]), "+f"(d[48]), "+f"(d[49]), "+f"(d[50]), "+f"(d[51]), "+f"(d[52]), "+f"(d[53]), "+f"(d[54]), "+f"(d[55]), "+f"(d[56]), "+f"(d[57]), "+f"(d[58]), "+f"(d[59]), "+f"(d[60]), "+f"(d[61]), "+f"(d[62]), "+f"(d[63]), "+f"(d[64]), "+f"(d[65]), "+f"(d[66]), "+f"(d[67]), "+f"(d[68]), "+f"(d[69]), "+f"(d[70]), "+f"(d[71]), "+f"(d[72]), "+f"(d[73]), "+f"(d[74]), "+f"(d[75]), "+f"(d[76]), "+f"(d[77]), "+f"(d[78]), "+f"(d[79]), "+f"(d[80]), "+f"(d[81]), "+f"(d[82]), "+f"(d[83]), "+f"(d[84]), "+f"(d[85]), "+f"(d[86]), "+f"(d[87]), "+f"(d[88]), "+f"(d[89]), "+f"(d[90]), "+f"(d[91]), "+f"(d[92]), "+f"(d[93]), "+f"(d[94]), "+f"(d[95])
    : "r"(a[0]), "r"(a[1]), "r"(a[2]), "r"(a[3]), "l"(db), "r"(sc), "n"(TB));
}
template<int TB> __device__ __forceinline__ void wgmma_n64_ss(float (&d)[32], uint64_t da, uint64_t db, int sc) {
  asm volatile("{\n.reg .pred p;\nsetp.ne.b32 p, %34, 0;\n"
    "wgmma.mma_async.sync.aligned.m64n64k16.f32.bf16.bf16 {%0, %1, %2, %3, %4, %5, %6, %7, %8, %9, %10, %11, %12, %13, %14, %15, %16, %17, %18, %19, %20, %21, %22, %23, %24, %25, %26, %27, %28, %29, %30, %31}, %32, %33, p, 1, 1, 0, %35;\n}\n"
    : "+f"(d[0]), "+f"(d[1]), "+f"(d[2]), "+f"(d[3]), "+f"(d[4]), "+f"(d[5]), "+f"(d[6]), "+f"(d[7]), "+f"(d[8]), "+f"(d[9]), "+f"(d[10]), "+f"(d[11]), "+f"(d[12]), "+f"(d[13]), "+f"(d[14]), "+f"(d[15]), "+f"(d[16]), "+f"(d[17]), "+f"(d[18]), "+f"(d[19]), "+f"(d[20]), "+f"(d[21]), "+f"(d[22]), "+f"(d[23]), "+f"(d[24]), "+f"(d[25]), "+f"(d[26]), "+f"(d[27]), "+f"(d[28]), "+f"(d[29]), "+f"(d[30]), "+f"(d[31])
    : "l"(da), "l"(db), "r"(sc), "n"(TB));
}
template<int TB> __device__ __forceinline__ void wgmma_n72_st(float (&d)[36], uint64_t da, uint64_t db, int sc) {
  asm volatile("{\n.reg .pred p;\nsetp.ne.b32 p, %38, 0;\n"
    "wgmma.mma_async.sync.aligned.m64n72k16.f32.bf16.bf16 {%0, %1, %2, %3, %4, %5, %6, %7, %8, %9, %10, %11, %12, %13, %14, %15, %16, %17, %18, %19, %20, %21, %22, %23, %24, %25, %26, %27, %28, %29, %30, %31, %32, %33, %34, %35}, %36, %37, p, 1, 1, 1, %39;\n}\n"
    : "+f"(d[0]), "+f"(d[1]), "+f"(d[2]), "+f"(d[3]), "+f"(d[4]), "+f"(d[5]), "+f"(d[6]), "+f"(d[7]), "+f"(d[8]), "+f"(d[9]), "+f"(d[10]), "+f"(d[11]), "+f"(d[12]), "+f"(d[13]), "+f"(d[14]), "+f"(d[15]), "+f"(d[16]), "+f"(d[17]), "+f"(d[18]), "+f"(d[19]), "+f"(d[20]), "+f"(d[21]), "+f"(d[22]), "+f"(d[23]), "+f"(d[24]), "+f"(d[25]), "+f"(d[26]), "+f"(d[27]), "+f"(d[28]), "+f"(d[29]), "+f"(d[30]), "+f"(d[31]), "+f"(d[32]), "+f"(d[33]), "+f"(d[34]), "+f"(d[35])
    : "l"(da), "l"(db), "r"(sc), "n"(TB));
}
template<int TB> __device__ __forceinline__ void wgmma_n80_ss(float (&d)[40], uint64_t da, uint64_t db, int sc) {
  asm volatile("{\n.reg .pred p;\nsetp.ne.b32 p, %42, 0;\n"
    "wgmma.mma_async.sync.aligned.m64n80k16.f32.bf16.bf16 {%0, %1, %2, %3, %4, %5, %6, %7, %8, %9, %10, %11, %12, %13, %14, %15, %16, %17, %18, %19, %20, %21, %22, %23, %24, %25, %26, %27, %28, %29, %30, %31, %32, %33, %34, %35, %36, %37, %38, %39}, %40, %41, p, 1, 1, 0, %43;\n}\n"
    : "+f"(d[0]), "+f"(d[1]), "+f"(d[2]), "+f"(d[3]), "+f"(d[4]), "+f"(d[5]), "+f"(d[6]), "+f"(d[7]), "+f"(d[8]), "+f"(d[9]), "+f"(d[10]), "+f"(d[11]), "+f"(d[12]), "+f"(d[13]), "+f"(d[14]), "+f"(d[15]), "+f"(d[16]), "+f"(d[17]), "+f"(d[18]), "+f"(d[19]), "+f"(d[20]), "+f"(d[21]), "+f"(d[22]), "+f"(d[23]), "+f"(d[24]), "+f"(d[25]), "+f"(d[26]), "+f"(d[27]), "+f"(d[28]), "+f"(d[29]), "+f"(d[30]), "+f"(d[31]), "+f"(d[32]), "+f"(d[33]), "+f"(d[34]), "+f"(d[35]), "+f"(d[36]), "+f"(d[37]), "+f"(d[38]), "+f"(d[39])
    : "l"(da), "l"(db), "r"(sc), "n"(TB));
}

struct FragAddr {
  uint32_t rowoff;
  uint32_t rx;
  uint32_t hi;
  __device__ __forceinline__ FragAddr(int warp_in_wg, int lane) {
    int row = 16 * warp_in_wg + (lane & 7) + ((lane >> 3) & 1) * 8;
    rowoff = row * 128;
    rx = row & 7;
    hi = lane >> 4;
  }
  __device__ __forceinline__ uint32_t at(uint32_t chunk_base, int kk4) const {
    return chunk_base + rowoff + ((((uint32_t)kk4 * 2 + hi) ^ rx) << 4);
  }
};

__device__ __forceinline__ void layernorm_frags(uint32_t (&f)[12][4]) {
  float s0[2] = {0.f, 0.f}, s1[2] = {0.f, 0.f}, q0[2] = {0.f, 0.f}, q1[2] = {0.f, 0.f};
#pragma unroll
  for (int k = 0; k < 12; k++) {
#pragma unroll
    for (int hf = 0; hf < 2; hf++) {
      const float a = bf_lo(f[k][2 * hf]), b = bf_hi(f[k][2 * hf]);
      const float c = bf_lo(f[k][2 * hf + 1]), d = bf_hi(f[k][2 * hf + 1]);
      s0[hf] += a + b; q0[hf] = fmaf(a, a, fmaf(b, b, q0[hf]));
      s1[hf] += c + d; q1[hf] = fmaf(c, c, fmaf(d, d, q1[hf]));
    }
  }
  float sa = s0[0] + s0[1], sb_ = s1[0] + s1[1], qa = q0[0] + q0[1], qb_ = q1[0] + q1[1];
  sa += __shfl_xor_sync(0xffffffffu, sa, 1); sb_ += __shfl_xor_sync(0xffffffffu, sb_, 1);
  qa += __shfl_xor_sync(0xffffffffu, qa, 1); qb_ += __shfl_xor_sync(0xffffffffu, qb_, 1);
  sa += __shfl_xor_sync(0xffffffffu, sa, 2); sb_ += __shfl_xor_sync(0xffffffffu, sb_, 2);
  qa += __shfl_xor_sync(0xffffffffu, qa, 2); qb_ += __shfl_xor_sync(0xffffffffu, qb_, 2);
  const float m0 = sa * (1.f / 192.f), m1 = sb_ * (1.f / 192.f);
  const float v0 = fmaxf(fmaf(-m0, m0, qa * (1.f / 192.f)), 0.f), v1 = fmaxf(fmaf(-m1, m1, qb_ * (1.f / 192.f)), 0.f);
  const float r0 = rsqrtf(v0 + 1e-5f), r1 = rsqrtf(v1 + 1e-5f);
  const float c0 = -m0 * r0, c1 = -m1 * r1;
#pragma unroll
  for (int k = 0; k < 12; k++) {
    f[k][0] = pack_bf16(fmaf(bf_lo(f[k][0]), r0, c0), fmaf(bf_hi(f[k][0]), r0, c0));
    f[k][2] = pack_bf16(fmaf(bf_lo(f[k][2]), r0, c0), fmaf(bf_hi(f[k][2]), r0, c0));
    f[k][1] = pack_bf16(fmaf(bf_lo(f[k][1]), r1, c1), fmaf(bf_hi(f[k][1]), r1, c1));
    f[k][3] = pack_bf16(fmaf(bf_lo(f[k][3]), r1, c1), fmaf(bf_hi(f[k][3]), r1, c1));
  }
}

#define XDELAY 600
constexpr int A_NST = 4;
constexpr int A_HB = 0;
constexpr int A_VB = 30720;
constexpr int A_QB = 61440;
constexpr int A_W = 110592;
constexpr int A_BAR = A_W + A_NST * 24576;
constexpr int A_SMEM = A_BAR + 256 + 1024;
constexpr int A_GRID = 130;
constexpr int A_FOLD = 36;

__device__ __forceinline__ void stsm_x4_t(uint32_t addr, uint32_t r0, uint32_t r1, uint32_t r2, uint32_t r3) {
  asm volatile("stmatrix.sync.aligned.m8n8.x4.trans.shared.b16 [%0], {%1,%2,%3,%4};"
               ::"r"(addr), "r"(r0), "r"(r1), "r"(r2), "r"(r3) : "memory");
}
__device__ __forceinline__ void stsm_x2_t(uint32_t addr, uint32_t r0, uint32_t r1) {
  asm volatile("stmatrix.sync.aligned.m8n8.x2.trans.shared.b16 [%0], {%1,%2};" ::"r"(addr), "r"(r0), "r"(r1) : "memory");
}
__device__ __forceinline__ void a_issue(float (&acc)[36], uint32_t sb, int s) {
  const int st = s % A_NST;
  mbar_wait(sb + A_BAR + st * 8, (s / A_NST) & 1);
  const uint64_t wd = mk_desc_o(sb + A_W + st * 24576, 8192, 1024);
  const uint64_t hd = mk_desc_o(sb + A_HB, 16, 1024);
  wg_fence();
#pragma unroll
  for (int kk = 0; kk < 12; kk++) wgmma_n72_st<0>(acc, wd + kk * 128, hd + (kk >> 2) * 640 + (kk & 3) * 2, kk > 0);
  wg_commit();
}
__device__ __forceinline__ void a_release(uint32_t sb, int s, int lane) {
  if (lane == 0) mbar_arrive(sb + A_BAR + 64 + (s % A_NST) * 8);
}
__device__ __forceinline__ void store_chunk_t(const float (&d)[36], uint32_t chunk_base, int wq, int lane) {
  const int mi = lane >> 3, i = lane & 7;
  const uint32_t cc = 2 * wq + (mi & 1);
  const uint32_t base = chunk_base + ((mi >> 1) * 8 + i) * 128 + ((cc ^ i) << 4);
#pragma unroll
  for (int j = 0; j < 8; j += 2)
    stsm_x4_t(base + j * 1024, pack_bf16(d[4 * j], d[4 * j + 1]), pack_bf16(d[4 * j + 2], d[4 * j + 3]),
              pack_bf16(d[4 * j + 4], d[4 * j + 5]), pack_bf16(d[4 * j + 6], d[4 * j + 7]));
  stsm_x2_t(chunk_base + (64 + i) * 128 + ((cc ^ i) << 4), pack_bf16(d[32], d[33]), pack_bf16(d[34], d[35]));
}
__device__ __forceinline__ void resid_chunk(uint32_t (*dst)[4], const float* acc, float s0, float s1, uint32_t chunk_base,
                                            const FragAddr& fa) {
#pragma unroll
  for (int k = 0; k < 4; k++) {
    uint32_t x[4];
    ldsm_x4(x, fa.at(chunk_base, k));
    uint32_t o[4];
    o[0] = pack_bf16(fmaf(acc[8 * k + 0], s0, bf_lo(x[0])), fmaf(acc[8 * k + 1], s0, bf_hi(x[0])));
    o[1] = pack_bf16(fmaf(acc[8 * k + 2], s1, bf_lo(x[1])), fmaf(acc[8 * k + 3], s1, bf_hi(x[1])));
    o[2] = pack_bf16(fmaf(acc[8 * k + 4], s0, bf_lo(x[2])), fmaf(acc[8 * k + 5], s0, bf_hi(x[2])));
    o[3] = pack_bf16(fmaf(acc[8 * k + 6], s1, bf_lo(x[3])), fmaf(acc[8 * k + 7], s1, bf_hi(x[3])));
    stsm_x4(fa.at(chunk_base, k), o);
    if (dst) { dst[k][0] = o[0]; dst[k][1] = o[1]; dst[k][2] = o[2]; dst[k][3] = o[3]; }
  }
}

__global__ void __launch_bounds__(384, 1)
kernelA(const __grid_constant__ CUtensorMap tm_x, const __grid_constant__ CUtensorMap tm_wq64t,
        const __grid_constant__ CUtensorMap tm_wot, const __grid_constant__ CUtensorMap tm_wq64s,
        const __grid_constant__ CUtensorMap tm_wos, const __grid_constant__ CUtensorMap tm_wf,
        const __grid_constant__ CUtensorMap tm_x1, const __grid_constant__ CUtensorMap tm_qkv) {
  extern __shared__ uint8_t smem_raw[];
  const uint32_t sb = (smem_u32(smem_raw) + 1023) & ~1023u;
  const int tid = threadIdx.x, warp = tid >> 5, lane = tid & 31;
  const bool is_fold = blockIdx.x < A_FOLD;
  const int n0 = blockIdx.x * 10;
  const uint32_t bX = sb + A_BAR + 128, bFF = sb + A_BAR + 136, bFD = sb + A_BAR + 144;
  if (tid == 256) {
    for (int i = 0; i < A_NST; i++) { mbar_init(sb + A_BAR + i * 8, 1); mbar_init(sb + A_BAR + 64 + i * 8, 4); }
    mbar_init(bX, 1); mbar_init(bFF, 1); mbar_init(bFD, 4);
    asm volatile("fence.mbarrier_init.release.cluster;" ::: "memory");
    if (is_fold) {
      const int mat = blockIdx.x / 9, rs = (blockIdx.x % 9) / 3, cs = blockIdx.x % 3;
      const CUtensorMap* mq = (mat < 2) ? &tm_wq64t : &tm_wq64s;
      const CUtensorMap* mo = (mat < 2) ? &tm_wot : &tm_wos;
      mbar_expect_tx(bFF, 2 * 24576);
      for (int c = 0; c < 3; c++) tma_load_2d(sb + A_W + c * 8192, mq, bFF, ((mat & 1) ? 384 : 0) + c * 64, rs * 64);
      if (mat & 1) tma_load_2d(sb + A_W + 24576, mo, bFF, cs * 64, 0);
      else for (int c = 0; c < 3; c++) tma_load_2d(sb + A_W + 24576 + c * 8192, mq, bFF, 192 + c * 64, cs * 64);
    }
  }
  asm volatile("griddepcontrol.launch_dependents;" ::: "memory");
  if (blockIdx.x == 129 && tid < 128) g_flag[tid] = 0;
  if (tid < 240) {
    const uint32_t a = sb + A_VB + (tid / 80) * 10240 + 70 * 128 + (tid % 80) * 16;
    asm volatile("st.shared.v4.b32 [%0], {%1,%1,%1,%1};" ::"r"(a), "r"(0) : "memory");
  }
  __syncthreads();

  if (warp >= 8) {
    asm volatile("setmaxnreg.dec.sync.aligned.u32 24;");
    if (warp == 8 && lane == 0) {
      __nanosleep(XDELAY);
      mbar_expect_tx(bX, 3 * 70 * 128);
      for (int c = 0; c < 3; c++) tma_load_3d(sb + A_VB + c * 10240, &tm_x, bX, c * 64, n0, 0);
      if (is_fold) mbar_wait(bFD, 0);
      for (int s = 0; s < 12; s++) {
        const int st = s % A_NST;
        const int g = s / 3;
        const int mat = (g == 0) ? 1 : (g == 1) ? 0 : g;
        if (s % 3 == 0) {
          uint32_t n = 0, v;
          do {
            asm volatile("ld.acquire.gpu.global.u32 %0, [%1];" : "=r"(v) : "l"(&g_wflag[mat]) : "memory");
          } while (v < 9u && ++n < (1u << 22));
          asm volatile("fence.proxy.async;" ::: "memory");
        }
        if (s >= A_NST) mbar_wait(sb + A_BAR + 64 + st * 8, ((s / A_NST) - 1) & 1);
        mbar_expect_tx(sb + A_BAR + st * 8, 24576);
        tma_load_2d(sb + A_W + st * 24576, &tm_wf, sb + A_BAR + st * 8, (mat & 1) * 192 + (s % 3) * 64, (mat >> 1) * 192);
      }
    }
    return;
  }

  asm volatile("setmaxnreg.inc.sync.aligned.u32 240;");
  const int wg = warp >> 2, wq = warp & 3;
  const bool elected = (tid & 127) == 0;
  TS(0, 0);

  if (is_fold && wg == 1) {
    const int mat = blockIdx.x / 9, rs = (blockIdx.x % 9) / 3, cs = blockIdx.x % 3;
    float d[32];
    mbar_wait(bFF, 0);
    const uint64_t ad = mk_desc_o(sb + A_W, 16, 1024);
    if (mat & 1) {
      const uint64_t bd = mk_desc_o(sb + A_W + 24576, 8192, 1024);
      wg_fence();
#pragma unroll
      for (int kk = 0; kk < 12; kk++) wgmma_n64_ss<1>(d, ad + (kk >> 2) * 512 + (kk & 3) * 2, bd + kk * 128, kk > 0);
      wg_commit();
    } else {
      const uint64_t bd = mk_desc_o(sb + A_W + 24576, 16, 1024);
      wg_fence();
#pragma unroll
      for (int kk = 0; kk < 12; kk++)
        wgmma_n64_ss<0>(d, ad + (kk >> 2) * 512 + (kk & 3) * 2, bd + (kk >> 2) * 512 + (kk & 3) * 2, kk > 0);
      wg_commit();
    }
    wg_wait<0>(); reg_fence(d);
    if (lane == 0) mbar_arrive(bFD);
    const int r0 = rs * 64 + wq * 16 + (lane >> 2);
    uint32_t* dst = reinterpret_cast<uint32_t*>(g_wf + ((size_t)(mat >> 1) * 192 + r0) * 384 + (mat & 1) * 192 + cs * 64 + (lane & 3) * 2);
#pragma unroll
    for (int j = 0; j < 8; j++) {
      dst[j * 4] = pack_bf16(d[4 * j], d[4 * j + 1]);
      dst[8 * 192 + j * 4] = pack_bf16(d[4 * j + 2], d[4 * j + 3]);
    }
    asm volatile("fence.proxy.async;" ::: "memory");
    named_bar(2, 128);
    if (elected) { __threadfence(); atomicAdd(&g_wflag[mat], 1u); }
  }

  const bool rows_ok = warp < 5;
  const FragAddr fa(warp, lane);
  uint32_t h[12][4];
  if (rows_ok) {
    mbar_wait(bX, 0);
#pragma unroll
    for (int k = 0; k < 12; k++) ldsm_x4(h[k], fa.at(sb + A_VB + (k >> 2) * 10240, k & 3));
    layernorm_frags(h);
#pragma unroll
    for (int k = 0; k < 12; k++) stsm_x4(fa.at(sb + A_HB + (k >> 2) * 10240, k & 3), h[k]);
  }
  fence_proxy_async();
  named_bar(1, 256);
  TS(0, 1);

  float acc0[36], acc1[36];
  {
    auto dst1 = [&](int s) { return s < 3 ? sb + A_VB + s * 10240 : sb + A_QB + (s - 3) * 16384; };
    a_issue(acc0, sb, wg);
    TS(0, 2);
    a_issue(acc1, sb, wg + 2); wg_wait<1>(); reg_fence(acc0); a_release(sb, wg, lane); store_chunk_t(acc0, dst1(wg), wq, lane);
    a_issue(acc0, sb, wg + 4); wg_wait<1>(); reg_fence(acc1); a_release(sb, wg + 2, lane); store_chunk_t(acc1, dst1(wg + 2), wq, lane);
    wg_wait<0>(); reg_fence(acc0); a_release(sb, wg + 4, lane); store_chunk_t(acc0, dst1(wg + 4), wq, lane);
  }
  fence_proxy_async();
  named_bar(1, 256);
  TS(0, 3);
  uint32_t pf[5][4];
  {
    float sacc[40];
    const uint64_t qd = mk_desc_o(sb + A_QB + wg * 8192, 16, 1024);
    const uint64_t kd = mk_desc_o(sb + A_HB, 16, 1024);
    wg_fence();
#pragma unroll
    for (int kk = 0; kk < 12; kk++)
      wgmma_n80_ss<0>(sacc, qd + (kk >> 2) * 1024 + (kk & 3) * 2, kd + (kk >> 2) * 640 + (kk & 3) * 2, kk > 0);
    wg_commit();
    wg_wait<0>(); reg_fence(sacc);
    named_bar(1, 256);
    if (tid == 0) {
      mbar_expect_tx(bX, 3 * 70 * 128);
      for (int c = 0; c < 3; c++) tma_load_3d(sb + A_QB + c * 16384, &tm_x, bX, c * 64, n0, 0);
    }
    TS(0, 4);
    const int r0 = 16 * warp + (lane >> 2), r1 = r0 + 8;
    const unsigned long long MLO = 0x1004010040100401ull;
    const int sh = 2 * (lane & 3);
    unsigned long long lo0, lo1; uint32_t hi0, hi1;
    {
      const int a = r0 % 10, b = r1 % 10;
      unsigned long long l = MLO << a; uint32_t hh = a >= 4 ? (1u << (a - 4)) : 0u;
      lo0 = (l >> sh) | (sh ? ((unsigned long long)hh << (64 - sh)) : 0ull); hi0 = hh >> sh;
      l = MLO << b; hh = b >= 4 ? (1u << (b - 4)) : 0u;
      lo1 = (l >> sh) | (sh ? ((unsigned long long)hh << (64 - sh)) : 0ull); hi1 = hh >> sh;
    }
    const float cs = 0.07216878364870322f * 1.4426950408889634f;
    float mx0 = -INFINITY, mx1 = -INFINITY;
#pragma unroll
    for (int j = 0; j < 10; j++) {
#pragma unroll
      for (int e = 0; e < 2; e++) {
        const int pos = 8 * j + e;
        const bool v0 = pos < 64 ? ((lo0 >> pos) & 1) : ((hi0 >> (pos - 64)) & 1);
        const bool v1 = pos < 64 ? ((lo1 >> pos) & 1) : ((hi1 >> (pos - 64)) & 1);
        sacc[4 * j + e] = v0 ? sacc[4 * j + e] * cs : -INFINITY;
        sacc[4 * j + 2 + e] = v1 ? sacc[4 * j + 2 + e] * cs : -INFINITY;
        mx0 = fmaxf(mx0, sacc[4 * j + e]);
        mx1 = fmaxf(mx1, sacc[4 * j + 2 + e]);
      }
    }
    mx0 = fmaxf(mx0, __shfl_xor_sync(0xffffffffu, mx0, 1)); mx1 = fmaxf(mx1, __shfl_xor_sync(0xffffffffu, mx1, 1));
    mx0 = fmaxf(mx0, __shfl_xor_sync(0xffffffffu, mx0, 2)); mx1 = fmaxf(mx1, __shfl_xor_sync(0xffffffffu, mx1, 2));
    float l0 = 0.f, l1 = 0.f;
#pragma unroll
    for (int j = 0; j < 10; j++) {
#pragma unroll
      for (int e = 0; e < 2; e++) {
        sacc[4 * j + e] = ex2(sacc[4 * j + e] - mx0); l0 += sacc[4 * j + e];
        sacc[4 * j + 2 + e] = ex2(sacc[4 * j + 2 + e] - mx1); l1 += sacc[4 * j + 2 + e];
      }
    }
    l0 += __shfl_xor_sync(0xffffffffu, l0, 1); l1 += __shfl_xor_sync(0xffffffffu, l1, 1);
    l0 += __shfl_xor_sync(0xffffffffu, l0, 2); l1 += __shfl_xor_sync(0xffffffffu, l1, 2);
    const float i0 = 1.f / l0, i1 = 1.f / l1;
#pragma unroll
    for (int k = 0; k < 5; k++) {
      pf[k][0] = pack_bf16(sacc[8 * k + 0] * i0, sacc[8 * k + 1] * i0); pf[k][1] = pack_bf16(sacc[8 * k + 2] * i1, sacc[8 * k + 3] * i1);
      pf[k][2] = pack_bf16(sacc[8 * k + 4] * i0, sacc[8 * k + 5] * i0); pf[k][3] = pack_bf16(sacc[8 * k + 6] * i1, sacc[8 * k + 7] * i1);
    }
  }
  TS(0, 5);
  {
    float oacc[96];
    const uint64_t vd = mk_desc_o(sb + A_VB, 10240, 1024);
    wg_fence();
#pragma unroll
    for (int kk = 0; kk < 5; kk++) wgmma_n192_rs<1>(oacc, pf[kk], vd + kk * 128, kk > 0);
    wg_commit();
    wg_wait<0>(); reg_fence(oacc);
    TS(0, 6);
    if (rows_ok) {
      mbar_wait(bX, 1);
#pragma unroll
      for (int c = 0; c < 3; c++) resid_chunk(&h[4 * c], &oacc[32 * c], 1.f, 1.f, sb + A_QB + c * 16384, fa);
      fence_proxy_async();
      named_bar(4, 160);
      if (tid == 0) {
        for (int c = 0; c < 3; c++) tma_store_3d(&tm_x1, sb + A_QB + c * 16384, c * 64, n0, 0);
        bulk_commit();
      }
      layernorm_frags(h);
#pragma unroll
      for (int k = 0; k < 12; k++) stsm_x4(fa.at(sb + A_HB + (k >> 2) * 10240, k & 3), h[k]);
    }
  }
  fence_proxy_async();
  named_bar(1, 256);
  TS(0, 7);
  if (tid == 128) {
    for (int c = 0; c < 3; c++) tma_store_3d(&tm_qkv, sb + A_HB + c * 10240, 192 + c * 64, n0, 0);
    bulk_commit();
  }
  {
    auto dst2 = [&](int s) { return s < 8 ? sb + A_VB + (s - 6) * 10240 : sb + A_W + (s % A_NST) * 24576; };
    auto flush = [&](int s) {
      fence_proxy_async();
      named_bar(2 + wg, 128);
      if (elected) { tma_store_3d(&tm_qkv, dst2(s), (s < 9 ? (s - 6) * 64 : 384 + (s - 9) * 64), n0, 0); bulk_commit(); }
    };
    a_issue(acc0, sb, 6 + wg);
    a_issue(acc1, sb, 8 + wg); wg_wait<1>(); reg_fence(acc0); a_release(sb, 6 + wg, lane);
    store_chunk_t(acc0, dst2(6 + wg), wq, lane);
    flush(6 + wg);
    a_issue(acc0, sb, 10 + wg); wg_wait<1>(); reg_fence(acc1);
    named_bar(2 + wg, 128);
    store_chunk_t(acc1, dst2(8 + wg), wq, lane);
    flush(8 + wg);
    wg_wait<0>(); reg_fence(acc0);
    named_bar(2 + wg, 128);
    store_chunk_t(acc0, dst2(10 + wg), wq, lane);
    flush(10 + wg);
  }
  TS(0, 9);
  if (elected) bulk_wait_read0();
  TS(0, 10);
}

constexpr int B_GRID = 132;
constexpr int B_SLOT = 55296;
constexpr int B_Q = 0;
constexpr int B_KV = 49152;
constexpr int B_BAR = B_KV + 3 * B_SLOT;
constexpr int B_SMEM = B_BAR + 256 + 1024;

__device__ __forceinline__ void bar_arrive(int id, int nthreads) {
  asm volatile("bar.arrive %0, %1;" ::"r"(id), "r"(nthreads) : "memory");
}
#define PP_WAIT(x, y) named_bar(x, y)
#define PP_ARRIVE(x, y) bar_arrive(x, y)
__device__ __forceinline__ void b_segment(int sg, int& tile, int& k0, int& k1) {
  const int grp = blockIdx.x / 12, ci = blockIdx.x - grp * 12;
  if (ci < 7) { tile = grp * 7 + ci; k0 = 3; k1 = 9; }
  else {
    const int hh = ci - 7;
    tile = grp * 7 + ((0x54210 >> (4 * hh)) & 15) + sg;
    k0 = sg ? 0 : ((0x10210 >> (4 * hh)) & 15);
    k1 = sg ? ((0x31321 >> (4 * hh)) & 15) : 3;
  }
}

__global__ void __launch_bounds__(384, 1)
kernelB(const __grid_constant__ CUtensorMap tm_q, const __grid_constant__ CUtensorMap tm_kv,
        const __grid_constant__ CUtensorMap tm_x1, const __grid_constant__ CUtensorMap tm_out) {
  extern __shared__ uint8_t smem_raw[];
  const uint32_t sb = (smem_u32(smem_raw) + 1023) & ~1023u;
  const int tid = threadIdx.x, warp = tid >> 5, lane = tid & 31;
  const uint32_t bF = sb + B_BAR, bE = sb + B_BAR + 32, bQF = sb + B_BAR + 64, bQE = sb + B_BAR + 72, bP = sb + B_BAR + 80, bS = sb + B_BAR + 96;
  if (tid == 0) {
    for (int i = 0; i < 3; i++) { mbar_init(bF + i * 8, 1); mbar_init(bE + i * 8, 8); }
    mbar_init(bQF, 1); mbar_init(bQE, 8); mbar_init(bP, 1);
    for (int i = 0; i < 3; i++) mbar_init(bS + i * 8, 1);
    asm volatile("fence.mbarrier_init.release.cluster;" ::: "memory");
    prefetch_tmap(&tm_q); prefetch_tmap(&tm_kv); prefetch_tmap(&tm_x1); prefetch_tmap(&tm_out);
  }
  __syncthreads();
  asm volatile("griddepcontrol.wait;" ::: "memory");
  const int grp = blockIdx.x / 12, ci = blockIdx.x - grp * 12;
  const bool owner = ci < 7;
  const int nseg = owner ? 1 : 2;

  if (warp >= 8) {
    asm volatile("setmaxnreg.dec.sync.aligned.u32 24;");
    if (warp == 8 && lane == 0) {
      if (blockIdx.x == 0) { g_wflag[0] = 0; g_wflag[1] = 0; g_wflag[2] = 0; g_wflag[3] = 0; }
      int it = 0;
      for (int sg = 0; sg < nseg; sg++) {
        int tile, k0, k1;
        b_segment(sg, tile, k0, k1);
        const int t = tile / 11, qt = tile - t * 11;
        const int n = k1 - k0;
        if (sg == 0) {
          for (int c = 0; c < 3; c++) {
            mbar_expect_tx(bS + c * 8, 16384 + 18432);
            tma_load_3d(sb + B_Q + c * 16384, &tm_q, bS + c * 8, c * 64, qt * 128, t);
            tma_load_3d(sb + B_KV + c * 18432, &tm_kv, bS + c * 8, 192 + c * 64, k0 * 144, t);
          }
          mbar_arrive(bQF); mbar_arrive(bF);
          mbar_wait(bS + 16, 0);
          it = 1;
        } else {
          mbar_wait(bQE, 0);
          mbar_expect_tx(bQF, 49152);
          for (int c = 0; c < 3; c++) tma_load_3d(sb + B_Q + c * 16384, &tm_q, bQF, c * 64, qt * 128, t);
        }
        for (int e = (sg == 0 ? 1 : 0); e < 2 * n; e++) {
          const int sl = it % 3;
          if (it >= 3) mbar_wait(bE + sl * 8, ((it / 3) - 1) & 1);
          mbar_expect_tx(bF + sl * 8, B_SLOT);
          for (int c = 0; c < 3; c++)
            tma_load_3d(sb + B_KV + sl * B_SLOT + c * 18432, &tm_kv, bF + sl * 8, 192 + (e & 1) * 192 + c * 64, (k0 + (e >> 1)) * 144, t);
          it++;
        }
      }
      if (owner) {
        const int tile = grp * 7 + ci;
        const int t = tile / 11, qt = tile - t * 11;
        mbar_wait(bQE, 0);
        mbar_expect_tx(bQF, 49152);
        for (int c = 0; c < 3; c++) tma_load_3d(sb + B_Q + c * 16384, &tm_x1, bQF, c * 64, qt * 128, t);
      }
    } else if (warp == 9 && owner) {
      if (lane == 0) {
        const int first = (0x9765310 >> (4 * ci)) & 15, cnt = (0x1211221 >> (4 * ci)) & 15;
        for (int q = 0; q < cnt; q++) {
          uint32_t n = 0, v;
          do {
            asm volatile("ld.acquire.gpu.global.u32 %0, [%1];" : "=r"(v) : "l"(&g_flag[grp * 10 + first + q]) : "memory");
            if (v < 2u) __nanosleep(200);
          } while (v < 2u && ++n < (1u << 20));
        }
        mbar_arrive(bP);
      }
    } else if ((warp == 9 || warp == 10) && !owner) {
      for (int sg = 0; sg < 2; sg++) {
        named_bar(5 + (warp - 9), 160);
        if (lane == 0) {
          __threadfence();
          atomicAdd(&g_flag[(grp * 5 + (ci - 7)) * 2 + sg], 1u);
        }
        __syncwarp();
      }
    }
    return;
  }

  asm volatile("setmaxnreg.inc.sync.aligned.u32 240;");
  const int wg = warp >> 2, wq = warp & 3;
  const int wtid = tid & 127;
  const float cs = 0.07216878364870322f * 1.4426950408889634f;
  float oacc[96], sacc[72];
  uint32_t pf[9][4];
  float m0, m1, l0, l1;
  int it = 0;
  const uint32_t qb = sb + B_Q + wg * 8192;
  if (wg == 1) { PP_ARRIVE(3, 256); }
  TS(1, 0);
  int tsi = 1;

  auto issue_qk = [&](int slot) {
    const uint64_t kd = mk_desc_o(sb + B_KV + slot * B_SLOT, 16, 1024);
    const uint64_t qd = mk_desc_o(qb, 16, 1024);
#pragma unroll
    for (int kk = 0; kk < 12; kk++)
      wgmma_n144_ss<0>(sacc, qd + (kk >> 2) * 1024 + (kk & 3) * 2, kd + (kk >> 2) * 1152 + (kk & 3) * 2, kk > 0);
    wg_commit();
  };
  auto issue_pv = [&](int slot, int accum) {
    const uint64_t vd = mk_desc_o(sb + B_KV + slot * B_SLOT, 18432, 1024);
#pragma unroll
    for (int kk = 0; kk < 9; kk++) wgmma_n192_rs<1>(oacc, pf[kk], vd + kk * 128, kk > 0 ? 1 : accum);
    wg_commit();
  };
  auto softmax = [&](bool first) {
    float t0[4], t1[4];
#pragma unroll
    for (int q = 0; q < 4; q++) {
      t0[q] = fmaxf(sacc[4 * q], sacc[4 * q + 1]);
      t1[q] = fmaxf(sacc[4 * q + 2], sacc[4 * q + 3]);
    }
#pragma unroll
    for (int j = 4; j < 18; j++) {
      t0[j & 3] = fmaxf(t0[j & 3], fmaxf(sacc[4 * j], sacc[4 * j + 1]));
      t1[j & 3] = fmaxf(t1[j & 3], fmaxf(sacc[4 * j + 2], sacc[4 * j + 3]));
    }
    float mx0 = fmaxf(fmaxf(t0[0], t0[1]), fmaxf(t0[2], t0[3]));
    float mx1 = fmaxf(fmaxf(t1[0], t1[1]), fmaxf(t1[2], t1[3]));
    mx0 = fmaxf(mx0, __shfl_xor_sync(0xffffffffu, mx0, 1)); mx1 = fmaxf(mx1, __shfl_xor_sync(0xffffffffu, mx1, 1));
    mx0 = fmaxf(mx0, __shfl_xor_sync(0xffffffffu, mx0, 2)); mx1 = fmaxf(mx1, __shfl_xor_sync(0xffffffffu, mx1, 2));
    if (first) {
      m0 = mx0; m1 = mx1; l0 = 0.f; l1 = 0.f;
    } else {
      const bool need = !((mx0 - m0) * cs <= 8.f) || !((mx1 - m1) * cs <= 8.f);
      if (__any_sync(0xffffffffu, need)) {
        mx0 = fmaxf(mx0, m0); mx1 = fmaxf(mx1, m1);
        const float a0 = ex2((m0 - mx0) * cs), a1 = ex2((m1 - mx1) * cs);
        m0 = mx0; m1 = mx1;
        l0 *= a0; l1 *= a1;
#pragma unroll
        for (int i = 0; i < 24; i++) {
          oacc[4 * i] *= a0; oacc[4 * i + 1] *= a0; oacc[4 * i + 2] *= a1; oacc[4 * i + 3] *= a1;
        }
      }
    }
    const float mc0 = m0 * cs, mc1 = m1 * cs;
#pragma unroll
    for (int q = 0; q < 4; q++) { t0[q] = 0.f; t1[q] = 0.f; }
#pragma unroll
    for (int k = 0; k < 9; k++) {
      float p[8];
#pragma unroll
      for (int e = 0; e < 8; e++) p[e] = ex2(fmaf(sacc[8 * k + e], cs, (e & 2) ? -mc1 : -mc0));
      t0[0] += p[0]; t0[1] += p[1]; t0[2] += p[4]; t0[3] += p[5];
      t1[0] += p[2]; t1[1] += p[3]; t1[2] += p[6]; t1[3] += p[7];
      pf[k][0] = pack_bf16(p[0], p[1]); pf[k][1] = pack_bf16(p[2], p[3]);
      pf[k][2] = pack_bf16(p[4], p[5]); pf[k][3] = pack_bf16(p[6], p[7]);
    }
    l0 += (t0[0] + t0[1]) + (t0[2] + t0[3]);
    l1 += (t1[0] + t1[1]) + (t1[2] + t1[3]);
  };

  for (int sg = 0; sg < nseg; sg++) {
    int n;
    { int tile, k0, k1; b_segment(sg, tile, k0, k1); n = k1 - k0; }
    mbar_wait(bQF, sg & 1);
    {
      const int sl = it % 3;
      mbar_wait(bF + sl * 8, (it / 3) & 1);
      PP_WAIT(3 + wg, 256);
      if (sg == 0) {
        const uint64_t kd = mk_desc_o(sb + B_KV, 16, 1024);
        const uint64_t qd = mk_desc_o(qb, 16, 1024);
#pragma unroll
        for (int c = 0; c < 3; c++) {
          mbar_wait(bS + c * 8, 0);
          wg_fence();
#pragma unroll
          for (int k4 = 0; k4 < 4; k4++)
            wgmma_n144_ss<0>(sacc, qd + c * 1024 + k4 * 2, kd + c * 1152 + k4 * 2, (c + k4) > 0);
          wg_commit();
        }
      } else {
        wg_fence();
        issue_qk(sl);
      }
      PP_ARRIVE(3 + (wg ^ 1), 256);
      wg_wait<0>(); reg_fence(sacc);
      if (lane == 0) { mbar_arrive(bE + sl * 8); if (n == 1) mbar_arrive(bQE); }
      it++;
      softmax(true);
    }
    TS(1, tsi); tsi++;
    for (int j = 1; j < n; j++) {
      const int slv = it % 3, slk = (it + 1) % 3;
      mbar_wait(bF + slv * 8, (it / 3) & 1);
      PP_WAIT(3 + wg, 256);
      wg_fence();
      issue_pv(slv, j > 1);
      mbar_wait(bF + slk * 8, ((it + 1) / 3) & 1);
      issue_qk(slk);
      PP_ARRIVE(3 + (wg ^ 1), 256);
      wg_wait<1>(); reg_fence(oacc);
      if (lane == 0) mbar_arrive(bE + slv * 8);
      wg_wait<0>(); reg_fence(sacc);
      if (lane == 0) { mbar_arrive(bE + slk * 8); if (j == n - 1) mbar_arrive(bQE); }
      it += 2;
      softmax(false);
      TS(1, tsi); tsi++;
    }
    if (owner) break;
    {
      const int sl = it % 3;
      mbar_wait(bF + sl * 8, (it / 3) & 1);
      PP_WAIT(3 + wg, 256);
      wg_fence();
      issue_pv(sl, n > 1);
      if (!(wg == 1 && sg == nseg - 1)) { PP_ARRIVE(3 + (wg ^ 1), 256); }
      wg_wait<0>(); reg_fence(oacc);
      if (lane == 0) mbar_arrive(bE + sl * 8);
      it++;
    }
    TS(1, tsi); tsi++;
    {
      const int slot = (grp * 5 + (ci - 7)) * 2 + sg;
      uint4* dst = g_part + (size_t)(slot * 2 + wg) * 13 * 128 + wtid;
#pragma unroll
      for (int i = 0; i < 12; i++)
        dst[i * 128] = make_uint4(pack_bf16(oacc[8 * i], oacc[8 * i + 1]), pack_bf16(oacc[8 * i + 2], oacc[8 * i + 3]),
                                  pack_bf16(oacc[8 * i + 4], oacc[8 * i + 5]), pack_bf16(oacc[8 * i + 6], oacc[8 * i + 7]));
      dst[12 * 128] = make_uint4(__float_as_uint(m0), __float_as_uint(m1), __float_as_uint(l0), __float_as_uint(l1));
      bar_arrive(5 + wg, 160);
      TS(1, tsi); tsi++;
    }
  }
  if (!owner) return;

  {
    const int first = (0x9765310 >> (4 * ci)) & 15, cnt = (0x1211221 >> (4 * ci)) & 15;
    const int slot0 = grp * 10 + first;
    const int sl = it % 3;
    mbar_wait(bF + sl * 8, (it / 3) & 1);
    PP_WAIT(3 + wg, 256);
    wg_fence();
    issue_pv(sl, 1);
    if (wg == 0) { PP_ARRIVE(3 + 1, 256); }
    mbar_wait(bP, 0);
    uint4 pv0[13];
    {
      const uint4* src = g_part + (size_t)(slot0 * 2 + wg) * 13 * 128 + wtid;
#pragma unroll
      for (int i = 0; i < 13; i++) pv0[i] = __ldcg(src + i * 128);
    }
    wg_wait<0>(); reg_fence(oacc);
    TS(1, 20);
    uint4 pv1[13];
    if (cnt > 1) {
      const uint4* src = g_part + (size_t)((slot0 + 1) * 2 + wg) * 13 * 128 + wtid;
#pragma unroll
      for (int i = 0; i < 13; i++) pv1[i] = __ldcg(src + i * 128);
    }
    auto merge = [&](const uint4 (&pv)[13]) {
      const float pm0 = __uint_as_float(pv[12].x), pm1 = __uint_as_float(pv[12].y);
      const float mx0 = fmaxf(m0, pm0), mx1 = fmaxf(m1, pm1);
      const float a0 = ex2((m0 - mx0) * cs), a1 = ex2((m1 - mx1) * cs);
      const float b0 = ex2((pm0 - mx0) * cs), b1 = ex2((pm1 - mx1) * cs);
      m0 = mx0; m1 = mx1;
      l0 = l0 * a0 + __uint_as_float(pv[12].z) * b0; l1 = l1 * a1 + __uint_as_float(pv[12].w) * b1;
#pragma unroll
      for (int i = 0; i < 12; i++) {
        const uint4 v = pv[i];
        oacc[8 * i + 0] = oacc[8 * i + 0] * a0 + bf_lo(v.x) * b0; oacc[8 * i + 1] = oacc[8 * i + 1] * a0 + bf_hi(v.x) * b0;
        oacc[8 * i + 2] = oacc[8 * i + 2] * a1 + bf_lo(v.y) * b1; oacc[8 * i + 3] = oacc[8 * i + 3] * a1 + bf_hi(v.y) * b1;
        oacc[8 * i + 4] = oacc[8 * i + 4] * a0 + bf_lo(v.z) * b0; oacc[8 * i + 5] = oacc[8 * i + 5] * a0 + bf_hi(v.z) * b0;
        oacc[8 * i + 6] = oacc[8 * i + 6] * a1 + bf_lo(v.w) * b1; oacc[8 * i + 7] = oacc[8 * i + 7] * a1 + bf_hi(v.w) * b1;
      }
    };
    merge(pv0);
    if (cnt > 1) merge(pv1);
  }
  TS(1, 21);
  l0 += __shfl_xor_sync(0xffffffffu, l0, 1); l0 += __shfl_xor_sync(0xffffffffu, l0, 2);
  l1 += __shfl_xor_sync(0xffffffffu, l1, 1); l1 += __shfl_xor_sync(0xffffffffu, l1, 2);
  const float i0 = 1.f / l0, i1 = 1.f / l1;
  mbar_wait(bQF, 1);
  const FragAddr fa(wq, lane);
  {
    const int tile = grp * 7 + ci;
    const int t = tile / 11, qt = tile - t * 11;
    const bool st_ok = (wtid == 0) && (qt * 128 + wg * 64 < NL);
#pragma unroll
    for (int c = 0; c < 3; c++) {
      resid_chunk(nullptr, &oacc[32 * c], i0, i1, qb + c * 16384, fa);
      fence_proxy_async();
      named_bar(1 + wg, 128);
      if (st_ok) { tma_store_3d(&tm_out, qb + c * 16384, c * 64, qt * 128 + wg * 64, t); bulk_commit(); }
    }
    TS(1, 22);
    if (st_ok) bulk_wait_read0();
  }
  TS(1, 23);
}

typedef CUresult (*EncodeFn)(CUtensorMap*, CUtensorMapDataType, cuuint32_t, void*, const cuuint64_t*, const cuuint64_t*,
                             const cuuint32_t*, const cuuint32_t*, CUtensorMapInterleave, CUtensorMapSwizzle,
                             CUtensorMapL2promotion, CUtensorMapFloatOOBfill);

void make_map(EncodeFn enc, CUtensorMap* m, const void* ptr, int rank, const uint64_t* dims, const uint32_t* box) {
  cuuint64_t gd[3], gs[2];
  cuuint32_t bx[3], es[3] = {1, 1, 1};
  uint64_t stride = 2;
  for (int i = 0; i < rank; i++) {
    gd[i] = dims[i]; bx[i] = box[i];
    stride *= dims[i];
    if (i < rank - 1) gs[i] = stride;
  }
  enc(m, CU_TENSOR_MAP_DATA_TYPE_BFLOAT16, rank, const_cast<void*>(ptr), gd, gs, bx, es, CU_TENSOR_MAP_INTERLEAVE_NONE,
      CU_TENSOR_MAP_SWIZZLE_128B, CU_TENSOR_MAP_L2_PROMOTION_L2_256B, CU_TENSOR_MAP_FLOAT_OOB_FILL_NONE);
}

}

extern "C" void kernel_launch(void* const* d_in, const int* in_sizes, int n_in, void* d_out, int out_size) {
  (void)in_sizes; (void)n_in; (void)out_size;
  EncodeFn enc = nullptr;
  cudaDriverEntryPointQueryResult qres;
  cudaGetDriverEntryPoint("cuTensorMapEncodeTiled", (void**)&enc, cudaEnableDefault, &qres);
  void *p_x1, *p_qkv, *p_wf;
  cudaGetSymbolAddress(&p_wf, g_wf);
  cudaGetSymbolAddress(&p_x1, g_x1);
  cudaGetSymbolAddress(&p_qkv, g_qkv);
  cudaFuncSetAttribute(kernelA, cudaFuncAttributeMaxDynamicSharedMemorySize, A_SMEM);
  cudaFuncSetAttribute(kernelB, cudaFuncAttributeMaxDynamicSharedMemorySize, B_SMEM);

  CUtensorMap tm_x, tm_wqkvt, tm_wot, tm_wqkvs, tm_x1s, tm_qkvs, tm_q, tm_kv, tm_wos, tm_x1l, tm_out, tm_wf;
  const uint64_t d_act[3] = {192, 1296, 7}, d_qkv[3] = {576, 1296, 7}, d_w3[2] = {576, 192}, d_w1[2] = {192, 192}, d_wf[2] = {384, 384};
  const uint32_t b_a[3] = {64, 10, 7}, b_w[2] = {64, 192}, b_q[3] = {64, 128, 1}, b_kv[3] = {64, 144, 1}, b_o[3] = {64, 64, 1}, b_w64[2] = {64, 64};
  make_map(enc, &tm_x, d_in[0], 3, d_act, b_a);
  make_map(enc, &tm_wqkvt, d_in[1], 2, d_w3, b_w64);
  make_map(enc, &tm_wot, d_in[2], 2, d_w1, b_w);
  make_map(enc, &tm_wqkvs, d_in[3], 2, d_w3, b_w64);
  make_map(enc, &tm_wos, d_in[4], 2, d_w1, b_w);
  make_map(enc, &tm_wf, p_wf, 2, d_wf, b_w);
  make_map(enc, &tm_x1s, p_x1, 3, d_act, b_a);
  make_map(enc, &tm_qkvs, p_qkv, 3, d_qkv, b_a);
  make_map(enc, &tm_q, p_qkv, 3, d_qkv, b_q);
  make_map(enc, &tm_kv, p_qkv, 3, d_qkv, b_kv);
  make_map(enc, &tm_x1l, p_x1, 3, d_act, b_q);
  make_map(enc, &tm_out, d_out, 3, d_act, b_o);

  kernelA<<<A_GRID, 384, A_SMEM, cudaStreamPerThread>>>(tm_x, tm_wqkvt, tm_wot, tm_wqkvs, tm_wos, tm_wf, tm_x1s, tm_qkvs);
  cudaLaunchConfig_t cfg = {};
  cfg.gridDim = dim3(B_GRID); cfg.blockDim = dim3(384); cfg.dynamicSmemBytes = B_SMEM; cfg.stream = cudaStreamPerThread;
  cudaLaunchAttribute at[1];
  at[0].id = cudaLaunchAttributeProgrammaticStreamSerialization;
  at[0].val.programmaticStreamSerializationAllowed = 1;
  cfg.attrs = at; cfg.numAttrs = 1;
  cudaLaunchKernelEx(&cfg, kernelB, tm_q, tm_kv, tm_x1l, tm_out);
}
```
